```python
import torch

def _softmax(x, axis=-1):
    return torch.softmax(x, dim=axis)
def _gelu(x):
    return torch.nn.functional.gelu(x, approximate="tanh")
def _silu(x):
    return torch.nn.functional.silu(x)
def _sigmoid(x):
    return torch.sigmoid(x)
def _layernorm(x, axis=-1, eps=1e-5):
    m = x.mean(dim=axis, keepdim=True)
    v = x.var(dim=axis, keepdim=True, unbiased=False)
    return (x - m) / torch.sqrt(v + eps)
def _scatter_add(tgt, idx, src, axis=0):
    return tgt.clone().index_add_(axis, idx, src)
def _segment_sum(src, seg, n):
    out = torch.zeros((n,) + src.shape[1:], dtype=src.dtype)
    return out.index_add_(0, seg, src)
def _pad(x, pw):
    flat = tuple(v for pair in reversed(pw) for v in pair)
    return torch.nn.functional.pad(x, flat)

kernel_name = 'interleave_layers__sliding_block__sliding_local_dilated__prompt'

def setup_inputs():

    _w = (lambda a: (lambda t: t.to(torch.bfloat16) if t.is_floating_point() else t)(torch.as_tensor(a)))
    def _A_setup():
        B, S, D = 1, 2048, 1024
        return {
            "x": _w((lambda *s: torch.randn(*s, dtype=torch.bfloat16) * 0.05)(B, S, D)),
            "wqkv": _w((lambda *s: torch.randn(*s, dtype=torch.bfloat16) * 0.05)(D, 3 * D)),
            "wo": _w((lambda *s: torch.randn(*s, dtype=torch.bfloat16) * 0.05)(D, D)),
        }
    _A_in = _A_setup()

    def _B_setup():
        B, S, D = 1, 2048, 1024
        return {
            "x": _w((lambda *s: torch.randn(*s, dtype=torch.bfloat16) * 0.05)(B, S, D)),
            "wqkv": _w((lambda *s: torch.randn(*s, dtype=torch.bfloat16) * 0.05)(D, 3 * D)),
            "wo": _w((lambda *s: torch.randn(*s, dtype=torch.bfloat16) * 0.05)(D, D)),
        }
    _B_in = _B_setup()

    return {
        "A_x": _A_in["x"],
        "A_wqkv": _A_in["wqkv"],
        "A_wo": _A_in["wo"],
        "B_x": _B_in["x"],
        "B_wqkv": _B_in["wqkv"],
        "B_wo": _B_in["wo"],
    }

def reference(A_x, A_wqkv, A_wo, B_x, B_wqkv, B_wo):
    def _A_ref(x, wqkv, wo):
        B, S, D = x.shape
        H = 32; Dh = D // H; W = 256
        qkv = (lambda x, *d: x.permute(*d))((x @ wqkv).reshape(B, S, 3, H, Dh), 2, 0, 3, 1, 4)
        q, k, v = qkv[0], qkv[1], qkv[2]
        scores = torch.einsum("bhqd,bhkd->bhqk", q, k) * (Dh ** -0.5)
        idx = torch.arange(S)
        mask = (idx[:, None] - idx[None, :] >= 0) & (idx[:, None] - idx[None, :] < W)
        scores = torch.where(mask[None, None], scores, -1e9)
        p = _softmax(scores, axis=-1)
        o = torch.einsum("bhqk,bhkd->bhqd", p, v)
        return (lambda x, *d: x.permute(*d))(o, 0, 2, 1, 3).reshape(B, S, D) @ wo

    def _B_ref(x, wqkv, wo):
        B, S, D = x.shape
        H = 32; Dh = D // H
        W, dil = 8, 2
        qkv = (lambda x, *d: x.permute(*d))((x @ wqkv).reshape(B, S, 3, H, Dh), 2, 0, 3, 1, 4)
        q, k, v = qkv[0], qkv[1], qkv[2]
        scale = Dh ** -0.5
        pos = torch.arange(S)
        off = torch.arange(W) * dil
        idx = pos[:, None] - off[None, :]
        mask = idx >= 0
        idx_c = torch.where(mask, idx, 0).reshape(-1)
        kg = k[:, :, idx_c, :].reshape(B, H, S, W, Dh)
        vg = v[:, :, idx_c, :].reshape(B, H, S, W, Dh)
        logits = torch.einsum("bhsd,bhswd->bhsw", q, kg) * scale
        logits = torch.where(mask[None, None, :, :], logits, -1e9)
        attn = _softmax(logits, axis=-1)
        o = torch.einsum("bhsw,bhswd->bhsd", attn, vg)
        return (lambda x, *d: x.permute(*d))(o, 0, 2, 1, 3).reshape(B, S, D) @ wo

    x = A_x
    x = x + _A_ref(_layernorm(x, axis=-1), A_wqkv, A_wo)
    x = x + _B_ref(_layernorm(x, axis=-1), B_wqkv, B_wo)
    x = x + _A_ref(_layernorm(x, axis=-1), A_wqkv, A_wo)
    x = x + _B_ref(_layernorm(x, axis=-1), B_wqkv, B_wo)
    return x
```

```cpp
#include <cuda_runtime.h>
#include <cuda_bf16.h>
#include <cuda.h>
#include <stdint.h>

namespace {

constexpr int S_LEN = 2048;
constexpr int DM = 1024;
constexpr int NQKV = 3072;
constexpr int NCTA = 128;

__device__ __align__(1024) uint8_t g_kvA[2][16][16][2][16384];
__device__ __align__(1024) uint8_t g_kvB[2][16][16][4096];
__device__ __align__(1024) uint8_t g_zero[16384];
__device__ __align__(1024) __nv_bfloat16 g_o[S_LEN * DM];
__device__ __align__(1024) __nv_bfloat16 g_x[S_LEN * DM];
__device__ __align__(1024) float4 g_stats[4][8][S_LEN];
__device__ __align__(1024) float4 g_cs[2][16][8][64];
constexpr int F_X = 0;
constexpr int XSTR = 32, OSTR = 32, KSTR = 32;
constexpr int F_O = F_X + 16 * XSTR;
constexpr int F_KV = F_O + 32 * OSTR;
constexpr int F_DONE = F_KV + 256 * KSTR;
__device__ __align__(1024) unsigned g_flags[F_DONE + 32];

constexpr uint32_t SBASE = 1024;
constexpr int UNIT = 8192;
constexpr int NUNITS = 20;
constexpr int OFF_SLOT = NUNITS * UNIT;
constexpr int OFF_BAR = OFF_SLOT + 4 * 16384;
constexpr int OFF_EPOCH = OFF_BAR + 296;
constexpr int OFF_CS = OFF_BAR + 304;
constexpr int OFF_RS = OFF_CS + 1536;
constexpr int OFF_TS = OFF_RS + 1024;
constexpr int SMEM_BYTES = OFF_RS + 1024;
constexpr int B_FULL = 0, B_EMPTY = 8, B_PREP = 16, B_HALO = 18, B_REL = 22, B_AFREE = 25, B_TURN = 26, B_XRDY = 28,
              B_CS = 30, B_CSD = 31, B_GO = 32, B_PRE = 33, B_RESF = 34, B_RESE = 35;

__device__ __forceinline__ uint32_t smem_u32(const void* p) { return (uint32_t)__cvta_generic_to_shared(p); }

__device__ __forceinline__ void mbar_init(uint32_t bar, uint32_t cnt) {
  asm volatile("mbarrier.init.shared::cta.b64 [%0], %1;" ::"r"(bar), "r"(cnt));
}
__device__ __forceinline__ void mbar_expect_tx(uint32_t bar, uint32_t bytes) {
  asm volatile("mbarrier.arrive.expect_tx.shared::cta.b64 _, [%0], %1;" ::"r"(bar), "r"(bytes) : "memory");
}
__device__ __forceinline__ void mbar_arrive(uint32_t bar) {
  asm volatile("mbarrier.arrive.shared::cta.b64 _, [%0];" ::"r"(bar) : "memory");
}
__device__ __forceinline__ bool mbar_try_wait(uint32_t bar, uint32_t parity) {
  uint32_t ok;
  asm volatile(
      "{\n.reg .pred p;\nmbarrier.try_wait.parity.shared::cta.b64 p, [%1], %2;\nselp.b32 %0, 1, 0, p;\n}\n"
      : "=r"(ok)
      : "r"(bar), "r"(parity)
      : "memory");
  return ok != 0;
}
__device__ __forceinline__ bool mbar_test(uint32_t bar, uint32_t parity) {
  uint32_t ok;
  asm volatile(
      "{\n.reg .pred p;\nmbarrier.test_wait.parity.shared::cta.b64 p, [%1], %2;\nselp.b32 %0, 1, 0, p;\n}\n"
      : "=r"(ok)
      : "r"(bar), "r"(parity)
      : "memory");
  return ok != 0;
}
__device__ __forceinline__ void mbar_wait(uint32_t bar, uint32_t parity) {
#pragma unroll 1
  for (uint32_t it = 0; it < (1u << 18); ++it) {
    if (mbar_try_wait(bar, parity)) return;
  }
}
__device__ __forceinline__ void mbar_pace(uint32_t bar, uint32_t parity) {
#pragma unroll 1
  for (uint32_t it = 0; it < 24; ++it) {
    if (mbar_try_wait(bar, parity)) return;
  }
}
template <int NS>
__device__ __forceinline__ void mbar_wait_lazy(uint32_t bar, uint32_t parity) {
#pragma unroll 1
  for (uint32_t it = 0; it < (1u << 18); ++it) {
    if (mbar_try_wait(bar, parity)) return;
    __nanosleep(NS);
  }
}
__device__ __forceinline__ bool elect_one() {
  uint32_t ok;
  asm volatile("{\n.reg .pred p;\nelect.sync _|p, 0xffffffff;\nselp.b32 %0, 1, 0, p;\n}\n" : "=r"(ok));
  return ok != 0;
}
__device__ __forceinline__ void fence_barrier_init() { asm volatile("fence.mbarrier_init.release.cluster;" ::: "memory"); }
__device__ __forceinline__ void fence_proxy_async_smem() { asm volatile("fence.proxy.async.shared::cta;" ::: "memory"); }
__device__ __forceinline__ void fence_proxy_async_all() { asm volatile("fence.proxy.async.global;" ::: "memory"); }

__device__ __forceinline__ void tma_load_3d(uint32_t dst, const CUtensorMap* map, uint32_t bar, int c0, int c1, int c2) {
  asm volatile(
      "cp.async.bulk.tensor.3d.shared::cluster.global.mbarrier::complete_tx::bytes [%0], [%1, {%3, %4, %5}], [%2];" ::"r"(dst),
      "l"(map), "r"(bar), "r"(c0), "r"(c1), "r"(c2)
      : "memory");
}
__device__ __forceinline__ void bulk_load(uint32_t dst, const void* src, uint32_t bytes, uint32_t bar) {
  asm volatile("cp.async.bulk.shared::cluster.global.mbarrier::complete_tx::bytes [%0], [%1], %2, [%3];" ::"r"(dst),
               "l"(src), "r"(bytes), "r"(bar)
               : "memory");
}
__device__ __forceinline__ void bulk_store(void* dst, uint32_t src, uint32_t bytes) {
  asm volatile("cp.async.bulk.global.shared::cta.bulk_group [%0], [%1], %2;" ::"l"(dst), "r"(src), "r"(bytes) : "memory");
}
__device__ __forceinline__ void tma_store_3d(const CUtensorMap* map, uint32_t src, int c0, int c1, int c2) {
  asm volatile("cp.async.bulk.tensor.3d.global.shared::cta.bulk_group [%0, {%2, %3, %4}], [%1];" ::"l"(map), "r"(src),
               "r"(c0), "r"(c1), "r"(c2)
               : "memory");
}
__device__ __forceinline__ void bulk_commit() { asm volatile("cp.async.bulk.commit_group;" ::: "memory"); }
__device__ __forceinline__ void bulk_wait_read0() { asm volatile("cp.async.bulk.wait_group.read 0;" ::: "memory"); }
__device__ __forceinline__ void bulk_wait0() { asm volatile("cp.async.bulk.wait_group 0;" ::: "memory"); }
__device__ __forceinline__ void named_bar_sync(int id, int nthreads) {
  asm volatile("bar.sync %0, %1;" ::"r"(id), "r"(nthreads) : "memory");
}
__device__ __forceinline__ void named_bar_arrive(int id, int nthreads) {
  asm volatile("bar.arrive %0, %1;" ::"r"(id), "r"(nthreads) : "memory");
}

__device__ __forceinline__ void wgmma_fence() { asm volatile("wgmma.fence.sync.aligned;\n" ::: "memory"); }
__device__ __forceinline__ void wgmma_commit() { asm volatile("wgmma.commit_group.sync.aligned;\n" ::: "memory"); }
template <int N>
__device__ __forceinline__ void wgmma_wait() {
  asm volatile("wgmma.wait_group.sync.aligned %0;\n" ::"n"(N) : "memory");
}
template <int R>
__device__ __forceinline__ void setmaxnreg_inc() { asm volatile("setmaxnreg.inc.sync.aligned.u32 %0;\n" ::"n"(R)); }
template <int R>
__device__ __forceinline__ void setmaxnreg_dec() { asm volatile("setmaxnreg.dec.sync.aligned.u32 %0;\n" ::"n"(R)); }
template <int N>
__device__ __forceinline__ void reg_fence(float* r) {
#pragma unroll
  for (int i = 0; i < N; i++) asm volatile("" : "+f"(r[i])::"memory");
}

template <int N>
__device__ __forceinline__ void reg_define(float* r) {
#pragma unroll
  for (int i = 0; i < N; i++) r[i] = 0.f;
}

__device__ __forceinline__ uint64_t desc_lo(uint32_t lo) {
  uint64_t d;
  asm("mov.b64 %0, {%1, %2};" : "=l"(d) : "r"(lo), "r"(0x40000040u));
  return d;
}
__device__ __forceinline__ uint64_t make_desc(uint32_t addr, uint32_t lbo_bytes) {
  return desc_lo((addr >> 4) + ((lbo_bytes >> 4) << 16));
}

__device__ __forceinline__ void wgmma_n192_ss_ta0_tb1(float* d, uint64_t descA, uint64_t descB, int scaleD) {
  asm volatile("{\n.reg .pred p;\nsetp.ne.b32 p, %98, 0;\n"
    "wgmma.mma_async.sync.aligned.m64n192k16.f32.bf16.bf16 {%0, %1, %2, %3, %4, %5, %6, %7, %8, %9, %10, %11, %12, %13, %14, %15, %16, %17, %18, %19, %20, %21, %22, %23, %24, %25, %26, %27, %28, %29, %30, %31, %32, %33, %34, %35, %36, %37, %38, %39, %40, %41, %42, %43, %44, %45, %46, %47, %48, %49, %50, %51, %52, %53, %54, %55, %56, %57, %58, %59, %60, %61, %62, %63, %64, %65, %66, %67, %68, %69, %70, %71, %72, %73, %74, %75, %76, %77, %78, %79, %80, %81, %82, %83, %84, %85, %86, %87, %88, %89, %90, %91, %92, %93, %94, %95}, %96, %97, p, 1, 1, 0, 1;\n}\n"
    : "+f"(d[0]), "+f"(d[1]), "+f"(d[2]), "+f"(d[3]), "+f"(d[4]), "+f"(d[5]), "+f"(d[6]), "+f"(d[7]), "+f"(d[8]), "+f"(d[9]), "+f"(d[10]), "+f"(d[11]), "+f"(d[12]), "+f"(d[13]), "+f"(d[14]), "+f"(d[15]), "+f"(d[16]), "+f"(d[17]), "+f"(d[18]), "+f"(d[19]), "+f"(d[20]), "+f"(d[21]), "+f"(d[22]), "+f"(d[23]), "+f"(d[24]), "+f"(d[25]), "+f"(d[26]), "+f"(d[27]), "+f"(d[28]), "+f"(d[29]), "+f"(d[30]), "+f"(d[31]), "+f"(d[32]), "+f"(d[33]), "+f"(d[34]), "+f"(d[35]), "+f"(d[36]), "+f"(d[37]), "+f"(d[38]), "+f"(d[39]), "+f"(d[40]), "+f"(d[41]), "+f"(d[42]), "+f"(d[43]), "+f"(d[44]), "+f"(d[45]), "+f"(d[46]), "+f"(d[47]), "+f"(d[48]), "+f"(d[49]), "+f"(d[50]), "+f"(d[51]), "+f"(d[52]), "+f"(d[53]), "+f"(d[54]), "+f"(d[55]), "+f"(d[56]), "+f"(d[57]), "+f"(d[58]), "+f"(d[59]), "+f"(d[60]), "+f"(d[61]), "+f"(d[62]), "+f"(d[63]), "+f"(d[64]), "+f"(d[65]), "+f"(d[66]), "+f"(d[67]), "+f"(d[68]), "+f"(d[69]), "+f"(d[70]), "+f"(d[71]), "+f"(d[72]), "+f"(d[73]), "+f"(d[74]), "+f"(d[75]), "+f"(d[76]), "+f"(d[77]), "+f"(d[78]), "+f"(d[79]), "+f"(d[80]), "+f"(d[81]), "+f"(d[82]), "+f"(d[83]), "+f"(d[84]), "+f"(d[85]), "+f"(d[86]), "+f"(d[87]), "+f"(d[88]), "+f"(d[89]), "+f"(d[90]), "+f"(d[91]), "+f"(d[92]), "+f"(d[93]), "+f"(d[94]), "+f"(d[95])
    : "l"(descA), "l"(descB), "r"(scaleD));
}

__device__ __forceinline__ void wgmma_n128_ss_ta0_tb1(float* d, uint64_t descA, uint64_t descB, int scaleD) {
  asm volatile("{\n.reg .pred p;\nsetp.ne.b32 p, %66, 0;\n"
    "wgmma.mma_async.sync.aligned.m64n128k16.f32.bf16.bf16 {%0, %1, %2, %3, %4, %5, %6, %7, %8, %9, %10, %11, %12, %13, %14, %15, %16, %17, %18, %19, %20, %21, %22, %23, %24, %25, %26, %27, %28, %29, %30, %31, %32, %33, %34, %35, %36, %37, %38, %39, %40, %41, %42, %43, %44, %45, %46, %47, %48, %49, %50, %51, %52, %53, %54, %55, %56, %57, %58, %59, %60, %61, %62, %63}, %64, %65, p, 1, 1, 0, 1;\n}\n"
    : "+f"(d[0]), "+f"(d[1]), "+f"(d[2]), "+f"(d[3]), "+f"(d[4]), "+f"(d[5]), "+f"(d[6]), "+f"(d[7]), "+f"(d[8]), "+f"(d[9]), "+f"(d[10]), "+f"(d[11]), "+f"(d[12]), "+f"(d[13]), "+f"(d[14]), "+f"(d[15]), "+f"(d[16]), "+f"(d[17]), "+f"(d[18]), "+f"(d[19]), "+f"(d[20]), "+f"(d[21]), "+f"(d[22]), "+f"(d[23]), "+f"(d[24]), "+f"(d[25]), "+f"(d[26]), "+f"(d[27]), "+f"(d[28]), "+f"(d[29]), "+f"(d[30]), "+f"(d[31]), "+f"(d[32]), "+f"(d[33]), "+f"(d[34]), "+f"(d[35]), "+f"(d[36]), "+f"(d[37]), "+f"(d[38]), "+f"(d[39]), "+f"(d[40]), "+f"(d[41]), "+f"(d[42]), "+f"(d[43]), "+f"(d[44]), "+f"(d[45]), "+f"(d[46]), "+f"(d[47]), "+f"(d[48]), "+f"(d[49]), "+f"(d[50]), "+f"(d[51]), "+f"(d[52]), "+f"(d[53]), "+f"(d[54]), "+f"(d[55]), "+f"(d[56]), "+f"(d[57]), "+f"(d[58]), "+f"(d[59]), "+f"(d[60]), "+f"(d[61]), "+f"(d[62]), "+f"(d[63])
    : "l"(descA), "l"(descB), "r"(scaleD));
}

__device__ __forceinline__ void wgmma_n192_ssz_ta0_tb1(float* d, uint64_t descA, uint64_t descB) {
  asm volatile("{\n.reg .pred p;\nsetp.ne.b32 p, 0, 0;\n"
    "wgmma.mma_async.sync.aligned.m64n192k16.f32.bf16.bf16 {%0, %1, %2, %3, %4, %5, %6, %7, %8, %9, %10, %11, %12, %13, %14, %15, %16, %17, %18, %19, %20, %21, %22, %23, %24, %25, %26, %27, %28, %29, %30, %31, %32, %33, %34, %35, %36, %37, %38, %39, %40, %41, %42, %43, %44, %45, %46, %47, %48, %49, %50, %51, %52, %53, %54, %55, %56, %57, %58, %59, %60, %61, %62, %63, %64, %65, %66, %67, %68, %69, %70, %71, %72, %73, %74, %75, %76, %77, %78, %79, %80, %81, %82, %83, %84, %85, %86, %87, %88, %89, %90, %91, %92, %93, %94, %95}, %96, %97, p, 1, 1, 0, 1;\n}\n"
    : "=f"(d[0]), "=f"(d[1]), "=f"(d[2]), "=f"(d[3]), "=f"(d[4]), "=f"(d[5]), "=f"(d[6]), "=f"(d[7]), "=f"(d[8]), "=f"(d[9]), "=f"(d[10]), "=f"(d[11]), "=f"(d[12]), "=f"(d[13]), "=f"(d[14]), "=f"(d[15]), "=f"(d[16]), "=f"(d[17]), "=f"(d[18]), "=f"(d[19]), "=f"(d[20]), "=f"(d[21]), "=f"(d[22]), "=f"(d[23]), "=f"(d[24]), "=f"(d[25]), "=f"(d[26]), "=f"(d[27]), "=f"(d[28]), "=f"(d[29]), "=f"(d[30]), "=f"(d[31]), "=f"(d[32]), "=f"(d[33]), "=f"(d[34]), "=f"(d[35]), "=f"(d[36]), "=f"(d[37]), "=f"(d[38]), "=f"(d[39]), "=f"(d[40]), "=f"(d[41]), "=f"(d[42]), "=f"(d[43]), "=f"(d[44]), "=f"(d[45]), "=f"(d[46]), "=f"(d[47]), "=f"(d[48]), "=f"(d[49]), "=f"(d[50]), "=f"(d[51]), "=f"(d[52]), "=f"(d[53]), "=f"(d[54]), "=f"(d[55]), "=f"(d[56]), "=f"(d[57]), "=f"(d[58]), "=f"(d[59]), "=f"(d[60]), "=f"(d[61]), "=f"(d[62]), "=f"(d[63]), "=f"(d[64]), "=f"(d[65]), "=f"(d[66]), "=f"(d[67]), "=f"(d[68]), "=f"(d[69]), "=f"(d[70]), "=f"(d[71]), "=f"(d[72]), "=f"(d[73]), "=f"(d[74]), "=f"(d[75]), "=f"(d[76]), "=f"(d[77]), "=f"(d[78]), "=f"(d[79]), "=f"(d[80]), "=f"(d[81]), "=f"(d[82]), "=f"(d[83]), "=f"(d[84]), "=f"(d[85]), "=f"(d[86]), "=f"(d[87]), "=f"(d[88]), "=f"(d[89]), "=f"(d[90]), "=f"(d[91]), "=f"(d[92]), "=f"(d[93]), "=f"(d[94]), "=f"(d[95])
    : "l"(descA), "l"(descB));
}

__device__ __forceinline__ void wgmma_n128_ssz_ta0_tb1(float* d, uint64_t descA, uint64_t descB) {
  asm volatile("{\n.reg .pred p;\nsetp.ne.b32 p, 0, 0;\n"
    "wgmma.mma_async.sync.aligned.m64n128k16.f32.bf16.bf16 {%0, %1, %2, %3, %4, %5, %6, %7, %8, %9, %10, %11, %12, %13, %14, %15, %16, %17, %18, %19, %20, %21, %22, %23, %24, %25, %26, %27, %28, %29, %30, %31, %32, %33, %34, %35, %36, %37, %38, %39, %40, %41, %42, %43, %44, %45, %46, %47, %48, %49, %50, %51, %52, %53, %54, %55, %56, %57, %58, %59, %60, %61, %62, %63}, %64, %65, p, 1, 1, 0, 1;\n}\n"
    : "=f"(d[0]), "=f"(d[1]), "=f"(d[2]), "=f"(d[3]), "=f"(d[4]), "=f"(d[5]), "=f"(d[6]), "=f"(d[7]), "=f"(d[8]), "=f"(d[9]), "=f"(d[10]), "=f"(d[11]), "=f"(d[12]), "=f"(d[13]), "=f"(d[14]), "=f"(d[15]), "=f"(d[16]), "=f"(d[17]), "=f"(d[18]), "=f"(d[19]), "=f"(d[20]), "=f"(d[21]), "=f"(d[22]), "=f"(d[23]), "=f"(d[24]), "=f"(d[25]), "=f"(d[26]), "=f"(d[27]), "=f"(d[28]), "=f"(d[29]), "=f"(d[30]), "=f"(d[31]), "=f"(d[32]), "=f"(d[33]), "=f"(d[34]), "=f"(d[35]), "=f"(d[36]), "=f"(d[37]), "=f"(d[38]), "=f"(d[39]), "=f"(d[40]), "=f"(d[41]), "=f"(d[42]), "=f"(d[43]), "=f"(d[44]), "=f"(d[45]), "=f"(d[46]), "=f"(d[47]), "=f"(d[48]), "=f"(d[49]), "=f"(d[50]), "=f"(d[51]), "=f"(d[52]), "=f"(d[53]), "=f"(d[54]), "=f"(d[55]), "=f"(d[56]), "=f"(d[57]), "=f"(d[58]), "=f"(d[59]), "=f"(d[60]), "=f"(d[61]), "=f"(d[62]), "=f"(d[63])
    : "l"(descA), "l"(descB));
}

__device__ __forceinline__ void wgmma_n64_rs_tb0(float* d, const uint32_t* a, uint64_t descB, int scaleD) {
  asm volatile("{\n.reg .pred p;\nsetp.ne.b32 p, %37, 0;\n"
    "wgmma.mma_async.sync.aligned.m64n64k16.f32.bf16.bf16 {%0, %1, %2, %3, %4, %5, %6, %7, %8, %9, %10, %11, %12, %13, %14, %15, %16, %17, %18, %19, %20, %21, %22, %23, %24, %25, %26, %27, %28, %29, %30, %31}, {%32, %33, %34, %35}, %36, p, 1, 1, 0;\n}\n"
    : "+f"(d[0]), "+f"(d[1]), "+f"(d[2]), "+f"(d[3]), "+f"(d[4]), "+f"(d[5]), "+f"(d[6]), "+f"(d[7]), "+f"(d[8]), "+f"(d[9]), "+f"(d[10]), "+f"(d[11]), "+f"(d[12]), "+f"(d[13]), "+f"(d[14]), "+f"(d[15]), "+f"(d[16]), "+f"(d[17]), "+f"(d[18]), "+f"(d[19]), "+f"(d[20]), "+f"(d[21]), "+f"(d[22]), "+f"(d[23]), "+f"(d[24]), "+f"(d[25]), "+f"(d[26]), "+f"(d[27]), "+f"(d[28]), "+f"(d[29]), "+f"(d[30]), "+f"(d[31])
    : "r"(a[0]), "r"(a[1]), "r"(a[2]), "r"(a[3]), "l"(descB), "r"(scaleD));
}

__device__ __forceinline__ void wgmma_n80_ss_ta0_tb0(float* d, uint64_t descA, uint64_t descB, int scaleD) {
  asm volatile("{\n.reg .pred p;\nsetp.ne.b32 p, %42, 0;\n"
    "wgmma.mma_async.sync.aligned.m64n80k16.f32.bf16.bf16 {%0, %1, %2, %3, %4, %5, %6, %7, %8, %9, %10, %11, %12, %13, %14, %15, %16, %17, %18, %19, %20, %21, %22, %23, %24, %25, %26, %27, %28, %29, %30, %31, %32, %33, %34, %35, %36, %37, %38, %39}, %40, %41, p, 1, 1, 0, 0;\n}\n"
    : "+f"(d[0]), "+f"(d[1]), "+f"(d[2]), "+f"(d[3]), "+f"(d[4]), "+f"(d[5]), "+f"(d[6]), "+f"(d[7]), "+f"(d[8]), "+f"(d[9]), "+f"(d[10]), "+f"(d[11]), "+f"(d[12]), "+f"(d[13]), "+f"(d[14]), "+f"(d[15]), "+f"(d[16]), "+f"(d[17]), "+f"(d[18]), "+f"(d[19]), "+f"(d[20]), "+f"(d[21]), "+f"(d[22]), "+f"(d[23]), "+f"(d[24]), "+f"(d[25]), "+f"(d[26]), "+f"(d[27]), "+f"(d[28]), "+f"(d[29]), "+f"(d[30]), "+f"(d[31]), "+f"(d[32]), "+f"(d[33]), "+f"(d[34]), "+f"(d[35]), "+f"(d[36]), "+f"(d[37]), "+f"(d[38]), "+f"(d[39])
    : "l"(descA), "l"(descB), "r"(scaleD));
}

__device__ __forceinline__ void wgmma_n32_rs_tb1(float* d, const uint32_t* a, uint64_t descB, int scaleD) {
  asm volatile("{\n.reg .pred p;\nsetp.ne.b32 p, %21, 0;\n"
    "wgmma.mma_async.sync.aligned.m64n32k16.f32.bf16.bf16 {%0, %1, %2, %3, %4, %5, %6, %7, %8, %9, %10, %11, %12, %13, %14, %15}, {%16, %17, %18, %19}, %20, p, 1, 1, 1;\n}\n"
    : "+f"(d[0]), "+f"(d[1]), "+f"(d[2]), "+f"(d[3]), "+f"(d[4]), "+f"(d[5]), "+f"(d[6]), "+f"(d[7]), "+f"(d[8]), "+f"(d[9]), "+f"(d[10]), "+f"(d[11]), "+f"(d[12]), "+f"(d[13]), "+f"(d[14]), "+f"(d[15])
    : "r"(a[0]), "r"(a[1]), "r"(a[2]), "r"(a[3]), "l"(descB), "r"(scaleD));
}

__device__ __forceinline__ uint32_t pack_bf16x2(float lo, float hi) {
  uint32_t r;
  asm("cvt.rn.bf16x2.f32 %0, %1, %2;" : "=r"(r) : "f"(hi), "f"(lo));
  return r;
}
__device__ __forceinline__ float bf_lo(uint32_t p) { return __uint_as_float(p << 16); }
__device__ __forceinline__ float bf_hi(uint32_t p) { return __uint_as_float(p & 0xffff0000u); }
__device__ __forceinline__ float bf16_round(float v) { return __bfloat162float(__float2bfloat16_rn(v)); }
__device__ __forceinline__ float ex2_approx(float x) {
  float r;
  asm("ex2.approx.ftz.f32 %0, %1;" : "=f"(r) : "f"(x));
  return r;
}
__device__ __forceinline__ float rcp_fast(float x) {
  float r;
  asm("rcp.approx.ftz.f32 %0, %1;" : "=f"(r) : "f"(x));
  return r;
}
__device__ __forceinline__ void ldmatrix_x4(uint32_t (&r)[4], uint32_t addr) {
  asm volatile("ldmatrix.sync.aligned.m8n8.x4.shared.b16 {%0,%1,%2,%3}, [%4];"
               : "=r"(r[0]), "=r"(r[1]), "=r"(r[2]), "=r"(r[3])
               : "r"(addr)
               : "memory");
}
__device__ __forceinline__ void stmatrix_x4(uint32_t addr, uint32_t r0, uint32_t r1, uint32_t r2, uint32_t r3) {
  asm volatile("stmatrix.sync.aligned.m8n8.x4.shared.b16 [%0], {%1,%2,%3,%4};" ::"r"(addr), "r"(r0), "r"(r1), "r"(r2),
               "r"(r3));
}
__device__ __forceinline__ uint32_t add_bf16x2(uint32_t a, uint32_t b) {
  uint32_t r;
  asm("add.rn.bf16x2 %0, %1, %2;" : "=r"(r) : "r"(a), "r"(b));
  return r;
}
__device__ __forceinline__ uint4 lds128(uint32_t addr) {
  uint4 v;
  asm volatile("ld.shared.v4.b32 {%0,%1,%2,%3}, [%4];" : "=r"(v.x), "=r"(v.y), "=r"(v.z), "=r"(v.w) : "r"(addr) : "memory");
  return v;
}
__device__ __forceinline__ uint32_t lds32(uint32_t addr) {
  uint32_t v;
  asm volatile("ld.shared.b32 %0, [%1];" : "=r"(v) : "r"(addr) : "memory");
  return v;
}
__device__ __forceinline__ void sts32(uint32_t addr, uint32_t v) {
  asm volatile("st.shared.b32 [%0], %1;" ::"r"(addr), "r"(v) : "memory");
}

__device__ __forceinline__ unsigned ld_acquire_u32(const unsigned* p) {
  unsigned v;
  asm volatile("ld.acquire.gpu.global.u32 %0, [%1];" : "=r"(v) : "l"(p) : "memory");
  return v;
}
__device__ __forceinline__ void red_relaxed_add(unsigned* p, unsigned v) {
  asm volatile("red.relaxed.gpu.global.add.u32 [%0], %1;" ::"l"(p), "r"(v) : "memory");
}
__device__ __forceinline__ void wait_ge(const unsigned* p, unsigned target) {
#pragma unroll 1
  for (uint32_t it = 0; it < (1u << 17); ++it) {
    if ((int)(ld_acquire_u32(p) - target) >= 0) return;
  }
}

template <bool SLOW>
__device__ __forceinline__ void wait_mask(const unsigned* f, int cnt, unsigned target, uint32_t need, uint32_t& seen, int lane) {
  if ((seen & need) == need) return;
  const unsigned* fp = f + (lane & (cnt - 1));
#pragma unroll 1
  for (uint32_t it = 0; it < (1u << 17); ++it) {
    seen = __ballot_sync(0xffffffffu, (int)(ld_acquire_u32(fp) - target) >= 0);
    if ((seen & need) == need) break;
    if (SLOW) __nanosleep(400);
  }
  fence_proxy_async_all();
}
__device__ __forceinline__ float4 ld_rec(const float4* p) {
  float4 v;
  asm volatile("ld.relaxed.gpu.global.v4.f32 {%0,%1,%2,%3}, [%4];" : "=f"(v.x), "=f"(v.y), "=f"(v.z), "=f"(v.w) : "l"(p) : "memory");
  return v;
}
__device__ __forceinline__ void st_rec(float4* p, float a, float b, float c, unsigned tag) {
  asm volatile("st.relaxed.gpu.global.v4.f32 [%0], {%1,%2,%3,%4};" ::"l"(p), "f"(a), "f"(b), "f"(c), "f"(__uint_as_float(tag)) : "memory");
}
template <int N>
__device__ __forceinline__ float4 sum_recs(const float4* p, int stride, unsigned tag) {
  float4 s;
#pragma unroll 1
  for (uint32_t it = 0; it < (1u << 17); ++it) {
    float4 v[N];
#pragma unroll
    for (int t = 0; t < N; t++) v[t] = ld_rec(p + t * stride);
    bool ok = true;
    s = make_float4(0.f, 0.f, 0.f, 0.f);
#pragma unroll
    for (int t = 0; t < N; t++) {
      ok &= __float_as_uint(v[t].w) == tag;
      s.x += v[t].x;
      s.y += v[t].y;
      s.z += v[t].z;
    }
    if (ok) break;
    __nanosleep(200);
  }
  return s;
}

__device__ __forceinline__ int fresh_tid() {
  int t;
  asm volatile("mov.u32 %0, %%tid.x;" : "=r"(t));
  return t;
}
#define PHASE_IDS                                  \
  const int tid_ = fresh_tid();                    \
  const int lane = tid_ & 31, wwarp = __shfl_sync(0xffffffffu, (tid_ >> 5) & 3, 0), tid = tid_ & 127; \
  const int g = lane >> 2, c = lane & 3;           \
  (void)tid; (void)g; (void)c; (void)wwarp;

#define STAMPW(cond, i) do { } while (0)
#define STAMP(cond, i) do { } while (0)
#define GTL(i) do { } while (0)
#define GTLX(c, i) do { } while (0)
#define TGET(v) do { } while (0)
#define TPUT(c, i, v) do { } while (0)

constexpr float SM_C = 0.17677669529663687f * 1.4426950408889634f;

__device__ __forceinline__ void sched_fence(uint32_t never) {
  asm volatile("{\n.reg .pred p;\nSF%=:\nsetp.ne.u32 p, %0, 0;\n@p nanosleep.u32 32;\n@p bra.uni SF%=;\n}\n" ::"r"(never) : "memory");
}

__device__ __forceinline__ void attn_soft(float (&s)[32], float (&mneg)[2], int i, bool valid, int dbase) {
  if ((i & 3) == 0) {
   if (i == 0) {
#pragma unroll
    for (int k = 0; k < 32; k++)
      if (8 * (k >> 2) + (k & 1) - 8 * ((k >> 1) & 1) > dbase) s[k] = -INFINITY;
#pragma unroll
    for (int r = 0; r < 2; r++) {
      float mx = fmaxf(fmaxf(fmaxf(s[2 * r], s[2 * r + 1]), fmaxf(s[4 + 2 * r], s[4 + 2 * r + 1])),
                       fmaxf(fmaxf(s[8 + 2 * r], s[8 + 2 * r + 1]), fmaxf(s[12 + 2 * r], s[12 + 2 * r + 1])));
      mx = fmaxf(mx, __shfl_xor_sync(0xffffffffu, mx, 1));
      mx = fmaxf(mx, __shfl_xor_sync(0xffffffffu, mx, 2));
      mneg[r] = -SM_C * mx;
    }
   } else {
#pragma unroll
    for (int k = 0; k < 32; k++)
      if (8 * (k >> 2) + (k & 1) - 8 * ((k >> 1) & 1) <= dbase) s[k] = -INFINITY;
   }
  }
  const float m0 = valid ? mneg[0] : -INFINITY, m1 = valid ? mneg[1] : -INFINITY;
#pragma unroll
  for (int k = 0; k < 32; k++) s[k] = ex2_approx(fmaf(s[k], SM_C, (k & 2) ? m1 : m0));
}

template <bool NEXT>
__device__ __forceinline__ void attn_mma(float (&s)[32], float (&o)[16], float (&l)[2], uint32_t vdesc,
                                         const uint32_t (&q)[2][4], uint32_t kdesc) {
  uint32_t p[4][4];
#pragma unroll
  for (int k = 0; k < 16; k++) p[k >> 2][k & 3] = pack_bf16x2(s[2 * k], s[2 * k + 1]);
  wgmma_fence();
  if (NEXT) {
    wgmma_n64_rs_tb0(s, q[0], desc_lo(kdesc), 0);
    wgmma_n64_rs_tb0(s, q[1], desc_lo(kdesc + 2), 1);
    wgmma_commit();
  }
#pragma unroll
  for (int k = 0; k < 4; k++) wgmma_n32_rs_tb1(o, p[k], desc_lo(vdesc + k * 128), 1);
  wgmma_commit();
#pragma unroll
  for (int r = 0; r < 2; r++) {
    const uint32_t t0 = add_bf16x2(add_bf16x2(p[0][r], p[0][2 + r]), add_bf16x2(p[1][r], p[1][2 + r]));
    const uint32_t t1 = add_bf16x2(add_bf16x2(p[2][r], p[2][2 + r]), add_bf16x2(p[3][r], p[3][2 + r]));
    l[r] += (bf_lo(t0) + bf_hi(t0)) + (bf_lo(t1) + bf_hi(t1));
  }
}

__device__ __forceinline__ void attn_a_slow(const uint8_t* __restrict__ kvimg, int L, int gb, int hp,
                                         int hh, int wwarp, int lane) {
  constexpr uint32_t sq = SBASE + OFF_SLOT + 3 * 16384;
  wait_ge(g_flags + F_KV + (gb * 16 + hp) * KSTR, 8u * ((*(volatile unsigned*)(g_flags + F_DONE)) / NCTA) + 2u * L + 2u);
#pragma unroll 1
  for (int t = 0; t < 32; t++) {
    const int row = (t >> 4) * 64 + wwarp * 16 + (t & 15);
    const int qpos = gb * 128 + row;
    const uint32_t qaddr = sq + row * 128;
    float mx = -INFINITY, sum = 0.f, acc = 0.f;
#pragma unroll 1
    for (int pass = 0; pass < 2; pass++) {
#pragma unroll 1
      for (int j = 0; j < 8; j++) {
        const int kp = qpos - (lane + 32 * j);
        const uint8_t* kr = kvimg + ((size_t)((kp >> 7) * 16 + hp) * 2 + ((kp >> 6) & 1)) * 16384 + (kp & 63) * 128;
        float d = -INFINITY;
        if (kp >= 0) {
          d = 0.f;
#pragma unroll 1
          for (int q = 0; q < 4; q++) {
            const uint4 kv = __ldcg(reinterpret_cast<const uint4*>(kr + (((hh * 4 + q) ^ (kp & 7)) << 4)));
            const uint4 qv = lds128(qaddr + (((hh * 4 + q) ^ (row & 7)) << 4));
            const uint32_t kw[4] = {kv.x, kv.y, kv.z, kv.w}, qw[4] = {qv.x, qv.y, qv.z, qv.w};
#pragma unroll
            for (int e = 0; e < 4; e++) d = fmaf(bf_lo(kw[e]), bf_lo(qw[e]), fmaf(bf_hi(kw[e]), bf_hi(qw[e]), d));
          }
        }
        if (pass == 0) {
          mx = fmaxf(mx, d);
        } else {
          const float ev = ex2_approx((d - mx) * SM_C);
          sum += ev;
          const float pv = bf16_round(ev);
#pragma unroll 1
          for (int kk = 0; kk < 32; kk++) {
            const float pk = __shfl_sync(0xffffffffu, pv, kk);
            const int k2 = qpos - (kk + 32 * j);
            if (k2 >= 0) {
              const uint8_t* vr = kvimg + ((size_t)((k2 >> 7) * 16 + hp) * 2 + ((k2 >> 6) & 1)) * 16384 + 8192 + (k2 & 63) * 128;
              const unsigned short vv =
                  __ldcg(reinterpret_cast<const unsigned short*>(vr + (((hh * 4 + (lane >> 3)) ^ (k2 & 7)) << 4) + (lane & 7) * 2));
              acc = fmaf(pk, __uint_as_float((uint32_t)vv << 16), acc);
            }
          }
        }
      }
      if (pass == 0) {
#pragma unroll
        for (int o = 16; o > 0; o >>= 1) mx = fmaxf(mx, __shfl_xor_sync(0xffffffffu, mx, o));
      }
    }
#pragma unroll
    for (int o = 16; o > 0; o >>= 1) sum += __shfl_xor_sync(0xffffffffu, sum, o);
    acc *= rcp_fast(sum);
    const float hi = __shfl_down_sync(0xffffffffu, acc, 1);
    __syncwarp();
    if ((lane & 1) == 0) sts32(qaddr + (((hh * 4 + (lane >> 3)) ^ (row & 7)) << 4) + (lane & 7) * 2, pack_bf16x2(acc, hi));
    __syncwarp();
  }
}

__device__ __forceinline__ void store_o(const float (&o)[16], const float (&inv)[2], uint32_t rowaddr, int hh, int lane) {
  const int mat = lane >> 3, r7 = lane & 7;
#pragma unroll
  for (int jp = 0; jp < 2; jp++)
    stmatrix_x4(rowaddr + (((hh * 4 + 2 * jp + (mat >> 1)) ^ r7) << 4),
                pack_bf16x2(o[8 * jp] * inv[0], o[8 * jp + 1] * inv[0]),
                pack_bf16x2(o[8 * jp + 2] * inv[1], o[8 * jp + 3] * inv[1]),
                pack_bf16x2(o[8 * jp + 4] * inv[0], o[8 * jp + 5] * inv[0]),
                pack_bf16x2(o[8 * jp + 6] * inv[1], o[8 * jp + 7] * inv[1]));
}

__device__ __forceinline__ void attention_a(int HH, int L, int gb, int hp, uint32_t par0, uint32_t parA, int wwarp, int lane,
                                            uint32_t zero) {
  constexpr uint32_t bars = SBASE + OFF_BAR;
  const uint32_t dslot = ((SBASE + OFF_SLOT) >> 4) + 0x10000u + HH * 4;
  const int db = 16 * wwarp + (lane >> 2) - 2 * (lane & 3);
  float s[32], o[2][16], l[2][2], mneg[2][2];
  uint32_t q[2][2][4];
  const uint32_t ra = SBASE + OFF_SLOT + 3 * 16384 + (wwarp * 16 + ((lane >> 3) & 1) * 8 + (lane & 7)) * 128;
#pragma unroll
  for (int h = 0; h < 2; h++) {
#pragma unroll
    for (int ks = 0; ks < 2; ks++) ldmatrix_x4(q[h][ks], ra + h * 8192 + (((HH * 4 + ks * 2 + (lane >> 4)) ^ (lane & 7)) << 4));
#pragma unroll
    for (int i = 0; i < 16; i++) o[h][i] = 0.f;
    l[h][0] = l[h][1] = 0.f;
    mneg[h][0] = mneg[h][1] = 0.f;
  }
  reg_define<32>(s);
  const int nmax = 2 * gb + 1;
  uint32_t d1 = dslot + 1024, d0 = dslot;
#pragma unroll 1
  for (int i = 0; i < 5; i++) {
    attn_mma<true>(s, o[0], l[0], d1 + 512, q[1], d1);
    if (i >= 1) mbar_wait(bars + 8u * (B_HALO - 1) + 8u * i, i == 1 ? par0 : parA);
    wgmma_wait<1>();
    reg_fence<32>(s);
    attn_soft(s, mneg[1], i, i <= nmax, db);
    wgmma_wait<0>();
    attn_mma<true>(s, o[1], l[1], d1 + 512, q[0], d0);
    wgmma_wait<1>();
    reg_fence<32>(s);
    attn_soft(s, mneg[0], i, i + 1 <= nmax, db);
    d1 = d0;
    d0 = d0 == dslot ? dslot + 2048 : d0 - 1024;
    sched_fence(zero);
    wgmma_wait<0>();
    if (i < 3 && lane == 0) mbar_arrive(bars + 8u * B_REL + 8u * i);
  }
  attn_mma<false>(s, o[0], l[0], dslot + 2048 + 512, q[0], 0u);
  wgmma_wait<0>();
  reg_fence<16>(o[0]);
  reg_fence<16>(o[1]);
  float inv[2][2];
  bool bad = false;
#pragma unroll
  for (int h = 0; h < 2; h++)
#pragma unroll
    for (int r = 0; r < 2; r++) {
      float v = l[h][r];
      v += __shfl_xor_sync(0xffffffffu, v, 1);
      v += __shfl_xor_sync(0xffffffffu, v, 2);
      bad |= !(v <= 1.152921504606846976e18f);
      inv[h][r] = rcp_fast(v);
    }
  if (HH == 0) GTL(45);
  if (__any_sync(0xffffffffu, bad)) {
    attn_a_slow(g_kvA[L >> 1][0][0][0], L, gb, hp, HH, wwarp, lane);
  } else {
    store_o(o[0], inv[0], ra, HH, lane);
    store_o(o[1], inv[1], ra + 8192, HH, lane);
  }
}

constexpr uint32_t KB_ROW0 = SBASE + OFF_SLOT + 2048, VB_ROW0 = SBASE + OFF_SLOT + 24576 + 2048;

__device__ __forceinline__ void attnB_soft(const float (&s)[40], int wwarp, int D, bool edge, bool odd,
                                           uint32_t (&p)[5][4], float (&sum)[2]) {
  float z[2][3];
#define GATHER_(W)                                                                                  \
  _Pragma("unroll") for (int r = 0; r < 2; r++) _Pragma("unroll") for (int t = 0; t < 3; t++)       \
      z[r][t] = odd ? s[4 * (2 * W + r + t) + 2 * r + 1] : s[4 * (2 * W + r + t) + 2 * r];
  if (wwarp < 2) {
    if (wwarp == 0) { GATHER_(0) } else { GATHER_(1) }
  } else {
    if (wwarp == 2) { GATHER_(2) } else { GATHER_(3) }
  }
#undef GATHER_
  float y[2];
  y[0] = D >= 2 ? z[0][0] : z[0][2];
  y[1] = D >= 2 ? z[1][0] : z[1][2];
  if (edge) {
    z[0][1] = -INFINITY;
    if (D >= 2) y[0] = y[1] = -INFINITY;
  }
  float m0 = fmaxf(z[0][1], y[0]), m1 = fmaxf(z[1][1], y[1]);
  m0 = fmaxf(m0, __shfl_xor_sync(0xffffffffu, m0, 1));
  m1 = fmaxf(m1, __shfl_xor_sync(0xffffffffu, m1, 1));
  m0 = -SM_C * fmaxf(m0, __shfl_xor_sync(0xffffffffu, m0, 2));
  m1 = -SM_C * fmaxf(m1, __shfl_xor_sync(0xffffffffu, m1, 2));
  const float e00 = ex2_approx(fmaf(z[0][1], SM_C, m0)), e01 = ex2_approx(fmaf(y[0], SM_C, m0));
  const float e10 = ex2_approx(fmaf(z[1][1], SM_C, m1)), e11 = ex2_approx(fmaf(y[1], SM_C, m1));
  sum[0] = e00 + e01;
  sum[1] = e10 + e11;
  const int sh = odd ? 16 : 0;
  const uint32_t a0 = pack_bf16x2(e00, 0.f) << sh, a1 = pack_bf16x2(e10, 0.f) << sh;
  const uint32_t b0 = pack_bf16x2(e01, 0.f) << sh, b1 = pack_bf16x2(e11, 0.f) << sh;
  const int kb = wwarp + (D >= 2 ? 0 : 1);
#pragma unroll
  for (int k = 0; k < 5; k++) {
    p[k][0] = k == kb ? b0 : 0u;
    p[k][1] = k == wwarp + 1 ? a1 : 0u;
    p[k][2] = k == wwarp ? a0 : 0u;
    p[k][3] = k == kb ? b1 : 0u;
#pragma unroll
    for (int q = 0; q < 4; q++) asm volatile("" : "+r"(p[k][q]));
  }
}

__device__ __forceinline__ void attnB_s(float (&s)[40], int HH, int h) {
  constexpr uint32_t sq = SBASE + OFF_SLOT + 3 * 16384;
#pragma unroll
  for (int ks = 0; ks < 2; ks++)
    wgmma_n80_ss_ta0_tb0(s, make_desc(sq + h * 8192 + HH * 64 + ks * 32, 16),
                         make_desc(KB_ROW0 + h * 8192 - 2048 + HH * 64 + ks * 32, 16), ks);
}
__device__ __forceinline__ void attnB_pv(float (&o)[16], const uint32_t (&p)[5][4], int HH, int h) {
#pragma unroll
  for (int k = 0; k < 5; k++)
    wgmma_n32_rs_tb1(o, p[k], make_desc(VB_ROW0 + h * 8192 - 2048 + k * 2048 + HH * 64, 16), k);
}

__device__ __forceinline__ void attention_b(int HH, int gb, uint32_t par0, int wwarp, int lane) {
  constexpr uint32_t bars = SBASE + OFF_BAR, sq = SBASE + OFF_SLOT + 3 * 16384;
  float s[40];
  reg_define<40>(s);
  wgmma_fence();
  attnB_s(s, HH, 1);
  wgmma_commit();
  const int g = lane >> 2;
  const bool odd = g & 1;
  const int D = 2 * (lane & 3) + (g & 1) - g;
  const uint32_t ra = sq + (wwarp * 16 + ((lane >> 3) & 1) * 8 + (lane & 7)) * 128;
  wgmma_wait<0>();
  reg_fence<40>(s);
#pragma unroll 1
  for (int h = 1; h >= 0; h--) {
    float o[16], inv[2];
    uint32_t p[5][4];
    reg_define<16>(o);
    attnB_soft(s, wwarp, D, h == 0 && gb == 0 && wwarp == 0, odd, p, inv);
    if (h == 1) {
      mbar_wait(bars + 8u * B_HALO, par0);
      wgmma_fence();
      attnB_s(s, HH, 0);
    }
    wgmma_fence();
    attnB_pv(o, p, HH, h);
    wgmma_commit();
#pragma unroll
    for (int r = 0; r < 2; r++) {
      inv[r] += __shfl_xor_sync(0xffffffffu, inv[r], 1);
      inv[r] += __shfl_xor_sync(0xffffffffu, inv[r], 2);
      inv[r] = rcp_fast(inv[r]);
    }
    wgmma_wait<0>();
    reg_fence<40>(s);
    reg_fence<16>(o);
    store_o(o, inv, ra + h * 8192, HH, lane);
  }
}

#define KTQM 0
#define TRICKLE 300
#define CSPF 4
#define QTURN 2
struct Params {
  CUtensorMap xq[2], xr[3], o, wqkv[2], wo[2];
  const __nv_bfloat16* in_x;
  const __nv_bfloat16* wqkv_p[2];
  const __nv_bfloat16* wo_p[2];
  __nv_bfloat16* out;
  uint32_t zero;
};

__device__ __forceinline__ void colsum_part(const CUtensorMap* wmap, int ty, int qr, int hp) {
  constexpr uint32_t bars = SBASE + OFF_BAR, slots = SBASE + OFF_SLOT;
  PHASE_IDS
  const unsigned ep1 = (*(volatile unsigned*)(g_flags + F_DONE)) / NCTA + 1u;
  if (wwarp == 0 && elect_one()) {
    mbar_expect_tx(bars + 8u * B_CS, 6 * UNIT);
#pragma unroll 1
    for (int j = 0; j < 2; j++) {
      if (ty == 0) mbar_pace(bars + 8u * (B_EMPTY + 1 + 3 * j), 0);
      else __nanosleep(1000);
      tma_load_3d(slots + j * 3 * UNIT, wmap, bars + 8u * B_CS, hp * 64, qr * 128 + j * 64, 0);
    }
  }
  mbar_wait(bars + 8u * B_CS, ty);
  const uint32_t src = slots + (tid >> 3) * 128 + (((tid & 7) ^ ((tid >> 3) & 7)) << 4);
#pragma unroll 1
  for (int p = 0; p < 3; p++) {
    float s[8];
#pragma unroll
    for (int e = 0; e < 8; e++) s[e] = 0.f;
#pragma unroll
    for (int j = 0; j < 8; j++) {
      const uint4 v = lds128(src + p * UNIT + (j >> 2) * 3 * UNIT + (j & 3) * 2048);
      const uint32_t x[4] = {v.x, v.y, v.z, v.w};
#pragma unroll
      for (int e = 0; e < 4; e++) {
        s[2 * e] += bf_lo(x[e]);
        s[2 * e + 1] += bf_hi(x[e]);
      }
    }
#pragma unroll
    for (int st = 0; st < 2; st++) {
      const bool up = (lane >> (st + 3)) & 1;
#pragma unroll
      for (int e = 0; e < (4 >> st); e++) {
        const float keep = up ? s[e + (4 >> st)] : s[e], give = up ? s[e] : s[e + (4 >> st)];
        s[e] = keep + __shfl_xor_sync(0xffffffffu, give, 8 << st);
      }
    }
    const uint32_t dst = slots + 6 * UNIT + ((wwarp * 3 + p) * 64 + (lane & 7) * 8 + ((lane >> 3) & 1) * 4 + (lane >> 4) * 2) * 4;
    sts32(dst, __float_as_uint(s[0]));
    sts32(dst + 4, __float_as_uint(s[1]));
  }
  named_bar_sync(6, 128);
  if (tid < 64) {
    float r[3] = {0.f, 0.f, 0.f};
#pragma unroll
    for (int e = 0; e < 12; e++) r[e % 3] += __uint_as_float(lds32(slots + 6 * UNIT + (e * 64 + tid) * 4));
    st_rec(&g_cs[ty][hp][qr][tid], r[0], r[1], r[2], ep1);
  }
  named_bar_sync(6, 128);
}

__device__ __forceinline__ int cs_pos(int col) { return (col & ~15) + ((col & 7) >> 1) * 4 + ((col >> 3) & 1) * 2 + (col & 1); }

__device__ __forceinline__ uint32_t ln_params(float s1, float s2) {
  const float mean = s1 * (1.0f / DM);
  const float var = fmaxf(fmaf(-mean, mean, s2 * (1.0f / DM)), 0.f);
  float sd;
  asm("sqrt.approx.f32 %0, %1;" : "=f"(sd) : "f"(bf16_round(bf16_round(var) + 1e-5f)));
  return pack_bf16x2(mean, sd);
}

__host__ __device__ constexpr int w_ua(int kt) { return (kt == 6 ? 20 : 3 * kt) % 20; }
__host__ __device__ constexpr int w_ub(int kt) { return (kt == 6 ? 18 : 3 * kt + 1) % 20; }

constexpr int NSEG = 20;
__host__ __device__ constexpr int SEGQ(int ch, int L, int k0, int k1) { return ch | (L << 2) | ((k0 / 4) << 4) | ((k1 / 4 - 1) << 6); }
__host__ __device__ constexpr int SEGW(int ch, int L) { return ch | 2 | (L << 2); }
__host__ __device__ constexpr unsigned long long pack8(int a, int b, int c, int d, int e, int f, int g, int h) {
  return (unsigned long long)a | ((unsigned long long)b << 8) | ((unsigned long long)c << 16) | ((unsigned long long)d << 24) |
         ((unsigned long long)e << 32) | ((unsigned long long)f << 40) | ((unsigned long long)g << 48) | ((unsigned long long)h << 56);
}
#define SP2 12
#define SP3 12
#define SP4 12
#define SP6 12
__device__ __forceinline__ int seg_code(int sg) {
  constexpr unsigned long long T0 = pack8(SEGQ(0, 0, 0, 16), SEGQ(1, 0, 0, 16), SEGW(0, 0), SEGQ(0, 1, 0, SP2), SEGW(1, 0),
                                          SEGQ(0, 1, SP2, 16), SEGQ(1, 1, 0, SP3), SEGW(0, 1));
  constexpr unsigned long long T1 = pack8(SEGQ(1, 1, SP3, 16), SEGQ(0, 2, 0, SP4), SEGW(1, 1), SEGQ(0, 2, SP4, 16),
                                          SEGQ(1, 2, 0, 16), SEGW(0, 2), SEGQ(0, 3, 0, SP6), SEGW(1, 2));
  constexpr unsigned long long T2 = pack8(SEGQ(0, 3, SP6, 16), SEGQ(1, 3, 0, 16), SEGW(0, 3), SEGW(1, 3), 0, 0, 0, 0);
  return (int)(((sg < 8 ? T0 : (sg < 16 ? T1 : T2)) >> (8 * (sg & 7))) & 255ull);
}
__device__ __forceinline__ int q_first(int inst) { return (int)((pack8(0, 16, 48, 80, 112, 144, 176, 208) >> (8 * inst)) & 255ull); }
__device__ __forceinline__ int w_first(int inst) {
  return (int)((pack8(32, 48 + SP2, 80 + SP3, 112 + SP4, 160, 176 + SP6, 224, 240) >> (8 * inst)) & 255ull);
}
#define PREMASK 0x2Cu
#define PRE0 3
#define PRESH 2
__host__ __device__ constexpr int pre_idx(int kt) {
  const int d = kt - PRE0;
  return (d >= 0 && (d & ((1 << PRESH) - 1)) == 0 && (d >> PRESH) < 4) ? d >> PRESH : -1;
}
__device__ __forceinline__ bool w_pre(int inst) { return (PREMASK >> inst) & 1u; }
__device__ __forceinline__ int q_split(int inst) { return (int)(((0x40400044u | ((SP2 / 4) << 8) | ((SP3 / 4) << 12) | ((SP4 / 4) << 16) | ((SP6 / 4) << 24)) >> (4 * inst)) & 15u); }

__global__ void __launch_bounds__(512, 1) fused_kernel(const __grid_constant__ Params P) {
  extern __shared__ __align__(1024) uint8_t smem_raw[];
  constexpr uint32_t base = SBASE, bars = base + OFF_BAR, slots = base + OFF_SLOT;
  if (smem_u32(smem_raw) != base) __trap();
  const int warp = __shfl_sync(0xffffffffu, threadIdx.x >> 5, 0), lane = threadIdx.x & 31;
  const int b = blockIdx.x;
#define QS 0
#define WS 1
  const int qr = ((b & ((8 << QS) - 1)) >> QS) ^ (((b >> (3 + QS)) & 1) * 7);
  const int hp = ((b >> (3 + QS)) << QS) + (b & ((1 << QS) - 1));
  const int rt = ((b & ((16 << WS) - 1)) >> WS) ^ (((b >> (4 + WS)) & 1) * 15);
  const int ct = ((b >> (4 + WS)) << WS) + (b & ((1 << WS) - 1));

  if (warp == 12) {
    if (elect_one()) {
#pragma unroll
      for (int s = 0; s < 8; s++) {
        mbar_init(bars + 8u * (B_FULL + s), 2);
        mbar_init(bars + 8u * (B_EMPTY + s), 4);
      }
      mbar_init(bars + 8u * B_GO, 1);
      fence_barrier_init();
    }
    __syncwarp();
    named_bar_arrive(0, 512);
  }
  if (threadIdx.x == 0) {
    mbar_init(bars + 8u * B_PREP, 1);
    mbar_init(bars + 8u * (B_PREP + 1), 1);
    for (int s = 0; s < 4; s++) mbar_init(bars + 8u * (B_HALO + s), 1);
    for (int s = 0; s < 3; s++) mbar_init(bars + 8u * (B_REL + s), 8);
    mbar_init(bars + 8u * B_AFREE, 2);
    mbar_init(bars + 8u * B_TURN, 4);
    mbar_init(bars + 8u * (B_TURN + 1), 4);
    mbar_init(bars + 8u * B_CS, 1);
    mbar_init(bars + 8u * B_PRE, 1);
    mbar_init(bars + 8u * B_RESF, 1);
    mbar_init(bars + 8u * B_RESE, 4);
    mbar_init(bars + 8u * B_CSD, 4);
    mbar_init(bars + 8u * B_XRDY, 1);
    mbar_init(bars + 8u * (B_XRDY + 1), 1);
    fence_barrier_init();
  }
  if (warp != 12) named_bar_sync(0, 512);

  if (warp >= 12) {
    setmaxnreg_dec<32>();
    if (warp <= 13) {
      const bool act = warp == 13;
      uint32_t q = 4, dl = 0;
      bool prevw = false;
      unsigned ep1 = 0;
      if (act) {
        mbar_wait(bars + 8u * B_GO, 0);
        ep1 = __shfl_sync(0xffffffffu, (*(volatile unsigned*)(g_flags + F_DONE)) / NCTA + 1u, 0);
      } else {
#pragma unroll 1
        for (int s = 0; s < 16; s++) {
          const uint32_t fb = bars + 8u * (B_FULL + (s & 7)), sa = base + (s & 3) * 5 * UNIT;
          if (s >= 4) mbar_wait(bars + 8u * (B_EMPTY + ((s - 4) & 7)), ((s - 4) >> 3) & 1);
          if (elect_one()) {
            mbar_expect_tx(fb, 5 * UNIT);
            mbar_arrive(fb);
            tma_load_3d(sa, &P.xq[0], fb, 0, qr * 128, s);
            tma_load_3d(sa + 2 * UNIT, &P.wqkv[0], fb, hp * 64, s * 64, 0);
          }
        }
        if (elect_one()) mbar_arrive(bars + 8u * B_GO);
      }
      auto rbar = [&](int b0, int c) { return bars + 8u * b0 + ((8u * (c & 7)) ^ ((q & 1u) << 5)); };
      auto rpar = [&](int c) { return ((q + (c >> 2)) >> 1) & 1u; };
#pragma unroll 1
      for (int sg = 1; sg < NSEG; sg++) {
        const int code = seg_code(sg);
        const int L = (code >> 2) & 3, ch = code & 1;
        uint32_t seen = act ? 0u : 0xFFFFu;
        if ((code & 2) == 0) {
          const CUtensorMap* map = act ? &P.xq[L == 0 ? 0 : 1] : &P.wqkv[L & 1];
          if (act && (L == 0 || __any_sync(0xffffffffu, mbar_test(bars + 8u * (B_XRDY + ch), (L & 1) ^ 1)))) {
            seen = 0xFFFFu;
            fence_proxy_async_all();
          }
          const int k1 = ((code >> 4) & 12) + 4;
#pragma unroll 1
          for (int k4 = (code >> 2) & 12; k4 < k1; k4 += 4, q++) {
#pragma unroll
            for (int ks = 0; ks < 4; ks++) {
              const int kt = k4 + ks;
              if ((ks & 1) == 0)
                wait_mask<false>(g_flags + F_X + (ch * 8 + qr) * XSTR, 8, 6u * ep1 - 6u + 2u * L, 1u << (kt >> 1), seen, lane);
              if (ks == 0 && prevw) mbar_wait(rbar(B_EMPTY, -5), rpar(-5));
              else mbar_wait(rbar(B_EMPTY, ks - 4), rpar(-4));
              if (ks == 3 && prevw && !act) mbar_wait(bars + 8u * B_RESE, dl == 0 ? 1u : 0u);
              if (elect_one()) {
                mbar_expect_tx(rbar(B_FULL, ks), act ? 2 * UNIT : 3 * UNIT);
                tma_load_3d(base + ks * 5 * UNIT + (act ? 0 : 2 * UNIT) + (ks < 2 ? dl : 0u - dl), map, rbar(B_FULL, ks),
                            act ? 0 : hp * 64, act ? ch * 1024 + qr * 128 : kt * 64, act ? kt : 0);
              }
            }
            prevw = false;
          }
        } else {
          const CUtensorMap* map = act ? &P.o : &P.wo[L & 1];
          const bool pre = !act && w_pre(2 * L + ch);
          const int m0 = ch * 1024 + rt * 64;
#pragma unroll
          for (int kt = 0; kt < 16; kt++) {
            if (kt == 0 || kt == 1 || kt == 4 || kt == 8)
              wait_mask<false>(g_flags + F_O + (ch * 16 + rt) * OSTR, 16, 4u * ep1 - 3u + L,
                               kt == 0 ? 1u : (kt == 1 ? 0xEu : (kt == 4 ? 0xF0u : 0xFF00u)), seen, lane);
            if (kt < 4 && !prevw) mbar_wait(rbar(B_EMPTY, kt - 4 - (kt >> 1)), rpar(-4));
            else mbar_wait(rbar(B_EMPTY, kt - 6), rpar(kt - 6));
            if (kt == 6 && prevw && !act) mbar_wait(bars + 8u * B_RESE, dl == 0 ? 1u : 0u);
            if (elect_one()) {
              if (pre_idx(kt) >= 0 && pre) {
                mbar_arrive(rbar(B_FULL, kt));
              } else {
                mbar_expect_tx(rbar(B_FULL, kt), act ? UNIT : 2 * UNIT);
                const uint32_t da = base + w_ua(kt) * UNIT + (w_ua(kt) < 10 ? dl : 0u - dl);
                const uint32_t db = base + w_ub(kt) * UNIT + (w_ub(kt) < 10 ? dl : 0u - dl);
                tma_load_3d(act ? da : db, map, rbar(B_FULL, kt), 0, act ? m0 : kt * 64, act ? kt : ct * 2);
              }
            }
          }
          if (act && elect_one()) {
            mbar_expect_tx(bars + 8u * B_RESF, 2 * UNIT);
            tma_load_3d(base + 8 * UNIT + dl, &P.xr[L == 0 ? 0 : 1], bars + 8u * B_RESF, 0, m0, ct * 2);
          }
          q += 4;
          dl ^= 10u * UNIT;
          prevw = true;
        }
      }
    } else if (warp == 14) {
      const unsigned ep1 = (*(volatile unsigned*)(g_flags + F_DONE)) / NCTA + 1u;
#pragma unroll 1
      for (int inst = 0; inst < 8; inst++) {
        const int L = inst >> 1, ch = inst & 1, gb = ch * 8 + qr;
        unsigned* kvf = g_flags + F_KV;
        const unsigned kvt = 8u * ep1 - 6u + 2u * L;
        named_bar_sync(3, 160);
        if (elect_one()) {
          if ((L & 1) == 0) {
            bulk_store(g_kvA[L >> 1][gb][hp][1], slots + 16384, 16384);
          } else {
            bulk_store(g_kvB[L >> 1][gb][hp], KB_ROW0 + 112 * 128, 2048);
            bulk_store(g_kvB[L >> 1][gb][hp] + 2048, VB_ROW0 + 112 * 128, 2048);
          }
          bulk_commit();
          bulk_wait0();
          fence_proxy_async_all();
          red_relaxed_add(kvf + (gb * 16 + hp) * KSTR, (L & 1) + 1u);
        }
        __syncwarp();
        if (L & 1) named_bar_arrive(7, 160);
        else named_bar_sync(7, 160);
        if (elect_one()) {
          if ((L & 1) == 0) {
            bulk_store(g_kvA[L >> 1][gb][hp][0], slots, 16384);
            bulk_commit();
            bulk_wait0();
            fence_proxy_async_all();
            red_relaxed_add(kvf + (gb * 16 + hp) * KSTR, 1u);
          }
          if (gb >= 1) {
            wait_ge(kvf + ((gb - 1) * 16 + hp) * KSTR, kvt - 1u);
            fence_proxy_async_all();
          }
          if ((L & 1) == 0) {
            const uint32_t parA = ((L >> 1) * 2 + ch) & 1;
            const uint8_t* s1 = gb >= 1 ? g_kvA[L >> 1][gb - 1][hp][0] : g_zero;
            mbar_expect_tx(bars + 8u * B_HALO, 16384);
            bulk_load(slots + 2 * 16384, gb >= 1 ? s1 + 16384 : s1, 16384, bars + 8u * B_HALO);
            if (gb >= 1) {
              wait_ge(kvf + ((gb - 1) * 16 + hp) * KSTR, kvt);
              fence_proxy_async_all();
            }
            mbar_wait_lazy<100>(bars + 8u * B_REL, parA);
            mbar_expect_tx(bars + 8u * (B_HALO + 1), 16384);
            bulk_load(slots + 16384, s1, 16384, bars + 8u * (B_HALO + 1));
            if (gb >= 2) {
              wait_ge(kvf + ((gb - 2) * 16 + hp) * KSTR, kvt);
              fence_proxy_async_all();
            }
            const uint8_t* s2 = gb >= 2 ? g_kvA[L >> 1][gb - 2][hp][0] : g_zero;
            mbar_wait_lazy<100>(bars + 8u * (B_REL + 1), parA);
            mbar_expect_tx(bars + 8u * (B_HALO + 2), 16384);
            bulk_load(slots, gb >= 2 ? s2 + 16384 : s2, 16384, bars + 8u * (B_HALO + 2));
            mbar_wait_lazy<100>(bars + 8u * (B_REL + 2), parA);
            mbar_expect_tx(bars + 8u * (B_HALO + 3), 16384);
            bulk_load(slots + 2 * 16384, s2, 16384, bars + 8u * (B_HALO + 3));
          } else {
            const uint8_t* s1 = gb >= 1 ? g_kvB[L >> 1][gb - 1][hp] : g_zero;
            mbar_expect_tx(bars + 8u * B_HALO, 4096);
            bulk_load(KB_ROW0 - 2048, s1, 2048, bars + 8u * B_HALO);
            bulk_load(VB_ROW0 - 2048, s1 + 2048, 2048, bars + 8u * B_HALO);
          }
          if (w_pre(inst)) {
            mbar_wait(bars + 8u * B_AFREE, (inst & 1) ^ 1);
            if (inst == 1) mbar_wait(bars + 8u * B_CSD, 0);
            mbar_expect_tx(bars + 8u * B_PRE, 8 * UNIT);
#pragma unroll 1
            for (int j = 0; j < 4; j++) {
              tma_load_3d(slots + j * 2 * UNIT, &P.wo[L & 1], bars + 8u * B_PRE, 0, (PRE0 + (j << PRESH)) * 64, ct * 2);
              __nanosleep(200);
            }
          }
        }
        __syncwarp();
      }
    } else {
      const unsigned ep1 = (*(volatile unsigned*)(g_flags + F_DONE)) / NCTA + 1u;
      mbar_wait(bars + 8u * B_GO, 0);
#pragma unroll 1
      for (int i = 0; i < 20; i++) {
        const char* src = i < 4 ? reinterpret_cast<const char*>(P.wo_p[0]) + (size_t)b * 16384 + i * 4096
                                : (i < 16 ? reinterpret_cast<const char*>(P.wqkv_p[1]) + (size_t)b * 49152 + (i - 4) * 4096
                                          : reinterpret_cast<const char*>(P.wo_p[1]) + (size_t)b * 16384 + (i - 16) * 4096);
        asm volatile("prefetch.global.L2 [%0];" ::"l"(src + lane * 128));
        __nanosleep(TRICKLE);
      }
#pragma unroll 1
      for (int inst = 2; inst < 8; inst++) {
        const int L = inst >> 1, ch = inst & 1, gb = ch * 8 + qr;
        uint32_t seen = 0;
        wait_mask<true>(g_flags + F_X + gb * XSTR, 8, 6u * ep1 - 6u + 2u * L, 0xFFu, seen, lane);
        if (lane == 0) mbar_arrive(bars + 8u * (B_XRDY + ch));
#pragma unroll 1
        for (int h = 0; h < 4; h++) {
          const float4* sp = &g_stats[L][0][gb * 128 + h * 32 + lane];
          const float4 s0 = sum_recs<4>(sp, S_LEN, ep1), s1 = sum_recs<4>(sp + 4 * S_LEN, S_LEN, ep1);
          sts32(base + OFF_RS + (ch * 128 + h * 32 + lane) * 4, ln_params(s0.x + s1.x, s0.y + s1.y));
        }
        if (inst == 2) {
          mbar_wait(bars + 8u * B_CSD, 0);
#pragma unroll 1
          for (int hf = 0; hf < 2; hf++) {
            const float4* cp = &g_cs[1][hp][0][hf * 32 + lane];
            const float4 s0 = sum_recs<4>(cp, 64, ep1), s1 = sum_recs<4>(cp + 4 * 64, 64, ep1);
            const uint32_t ca = base + OFF_CS + (192 + cs_pos(hf * 32 + lane)) * 4;
            sts32(ca, __float_as_uint(s0.x + s1.x));
            sts32(ca + 256, __float_as_uint(s0.y + s1.y));
            sts32(ca + 512, __float_as_uint(s0.z + s1.z));
          }
        }
        __syncwarp();
        if (lane == 0) mbar_arrive(bars + 8u * (B_PREP + ch));
      }
    }
  } else {
    const bool asst = warp >= 8;
    const bool lane0 = lane == 0;
    uint32_t tpar = 0;
    GTL(0);
    if (asst) {
      colsum_part(&P.wqkv[0], 0, qr, hp);
      if ((threadIdx.x & 127) < 2) mbar_arrive(bars + 8u * B_AFREE);
    } else if (warp >= 4) {
      PHASE_IDS
      {
        const unsigned ep1 = (*(volatile unsigned*)(g_flags + F_DONE)) / NCTA + 1u;
        const int row = b * 16 + (tid >> 3);
        const uint4* src = reinterpret_cast<const uint4*>(P.in_x + (size_t)row * DM) + (tid & 7);
        float s1 = 0.f, s2 = 0.f;
#pragma unroll 1
        for (int k = 0; k < 4; k++) {
          mbar_pace(bars + 8u * (B_EMPTY + 2 * k), 0);
          uint4 v[4];
#pragma unroll
          for (int j = 0; j < 4; j++) v[j] = __ldg(src + (k * 4 + j) * 8);
#pragma unroll
          for (int j = 0; j < 4; j++) {
            const uint32_t w[4] = {v[j].x, v[j].y, v[j].z, v[j].w};
#pragma unroll
            for (int e = 0; e < 4; e++) {
              const float x0 = bf_lo(w[e]), x1 = bf_hi(w[e]);
              s1 += x0 + x1;
              s2 = fmaf(x0, x0, fmaf(x1, x1, s2));
            }
          }
        }
#pragma unroll
        for (int o = 1; o < 8; o <<= 1) {
          s1 += __shfl_xor_sync(0xffffffffu, s1, o);
          s2 += __shfl_xor_sync(0xffffffffu, s2, o);
        }
        if ((tid & 7) == 0) st_rec(&g_stats[0][0][row], s1, s2, 0.f, ep1);
        if (tid == 0) sts32(base + OFF_EPOCH, ep1);
        if (tid < 64) {
          const float4 s0 = sum_recs<8>(&g_cs[0][hp][0][tid], 64, ep1);
          sts32(base + OFF_CS + cs_pos(tid) * 4, __float_as_uint(s0.x));
          sts32(base + OFF_CS + cs_pos(tid) * 4 + 256, __float_as_uint(s0.y));
          sts32(base + OFF_CS + cs_pos(tid) * 4 + 512, __float_as_uint(s0.z));
        }
#pragma unroll 1
        for (int cc = 0; cc < 2; cc++) {
          const float4 s0 = sum_recs<1>(&g_stats[0][0][(cc * 8 + qr) * 128 + tid], 0, ep1);
          sts32(base + OFF_RS + (cc * 128 + tid) * 4, ln_params(s0.x, s0.y));
        }
        named_bar_sync(2, 128);
        if (tid < 2) mbar_arrive(bars + 8u * (B_PREP + tid));
      }
    }
#pragma unroll 1
    for (int inst = asst ? 0 : warp >> 2; inst < 8; inst += asst ? 1 : 2) {
      const int L = inst >> 1, ch = inst & 1, gb = ch * 8 + qr;
      if (asst) {
        setmaxnreg_dec<24>();
        named_bar_sync(4, 256);
        setmaxnreg_inc<128>();
      } else {
      setmaxnreg_inc<224>();
      {
        float acc[2][96];
        const int ksp = q_split(inst);
        int n = q_first(inst);
        uint32_t dlt = (ch == 0 && L > 0) ? 10u * (UNIT >> 4) : 0u;
        if (inst != 0 && inst != 2 && inst != 6) {
          mbar_wait_lazy<100>(bars + 8u * (B_TURN + ch), tpar);
          tpar ^= 1u;
        }
        if (L == 3) GTL(37);
        mbar_wait(bars + 8u * (B_FULL + (n & 7)), (n >> 3) & 1);
        GTL(1 + L * 8);
        {
          const uint32_t da = (base >> 4) + 0x10000u + dlt;
          const uint64_t db = desc_lo(da - 0x10000u + ((UNIT >> 4) << 16) + 2 * (UNIT >> 4));
          wgmma_fence();
          wgmma_n192_ssz_ta0_tb1(acc[0], desc_lo(da), db);
          wgmma_commit();
          wgmma_n192_ssz_ta0_tb1(acc[1], desc_lo(da + (UNIT >> 4)), db);
          wgmma_commit();
        }
#pragma unroll 1
        for (int k4 = 0; k4 < 4; k4++) {
          const bool brk = k4 + 1 == ksp && k4 < 3;
#pragma unroll
          for (int ks = 0; ks < 4; ks++, n++) {
            STAMP(inst == KSQ, k4 * 4 + ks);
            const uint32_t da = ((base + ks * 5 * UNIT) >> 4) + 0x10000u + (ks < 2 ? dlt : 0u - dlt);
            const uint32_t dbb = da - 0x10000u + ((UNIT >> 4) << 16) + 2 * (UNIT >> 4);
#pragma unroll
            for (int k16 = 0; k16 < 4; k16++) {
              if (ks == 0 && k16 == 0 && k4 == 0) continue;
              const uint64_t db = desc_lo(dbb + k16 * 128);
              wgmma_fence();
              wgmma_n192_ss_ta0_tb1(acc[0], desc_lo(da + k16 * 2), db, 1);
              wgmma_commit();
              wgmma_wait<1>();
              if (k16 == 0 && lane0 && (ks != 0 || k4 != ksp)) mbar_arrive(bars + 8u * (B_EMPTY + ((n - 1) & 7)));
              wgmma_fence();
              wgmma_n192_ss_ta0_tb1(acc[1], desc_lo(da + (UNIT >> 4) + k16 * 2), db, 1);
              wgmma_commit();
              bool ok = true;
              if (k16 == 2) ok = mbar_test(bars + 8u * (B_FULL + ((n + 1) & 7)), ((n + 1) >> 3) & 1) || (ks == 3 && (k4 == 3 || brk));
              if (k16 == QTURN && ks == 3 && (k4 == 3 || brk) && lane0) mbar_arrive(bars + 8u * (B_TURN + (ch ^ 1)));
              if (ks < 3 || k16 < 3) wgmma_wait<1>();
              if (k16 == 2 && !ok) mbar_wait(bars + 8u * (B_FULL + ((n + 1) & 7)), ((n + 1) >> 3) & 1);
            }
          }
          if (brk) {
            wgmma_wait<0>();
            if (lane0) mbar_arrive(bars + 8u * (B_EMPTY + ((n - 1) & 7)));
            n += 16;
            dlt ^= 10u * (UNIT >> 4);
            mbar_wait_lazy<100>(bars + 8u * (B_TURN + ch), tpar);
            tpar ^= 1u;
            STAMP(inst == KSQ, 17);
            mbar_wait(bars + 8u * (B_FULL + (n & 7)), (n >> 3) & 1);
          }
        }
        PHASE_IDS
        mbar_wait(bars + 8u * (B_PREP + ch), L & 1);
        const bool afree = mbar_test(bars + 8u * B_AFREE, inst & 1);
        float nmean[2][2], rinv[2][2];
        const uint32_t csa = base + OFF_CS + ((L & 1) * 192 + 4 * c) * 4;
        uint4 cs[20];
        {
          uint32_t v[4];
#pragma unroll
          for (int i = 0; i < 4; i++)
            v[i] = lds32(base + OFF_RS + (ch * 128 + (i >> 1) * 64 + wwarp * 16 + g + 8 * (i & 1)) * 4);
#pragma unroll
          for (int t = 0; t < 2; t++) cs[t] = lds128(csa + (t + 4) * 64);
#pragma unroll
          for (int i = 0; i < 4; i++) {
            nmean[i >> 1][i & 1] = -bf_lo(v[i]);
            rinv[i >> 1][i & 1] = rcp_fast(bf_hi(v[i]));
            asm volatile("" : "+f"(rinv[i >> 1][i & 1]), "+f"(nmean[i >> 1][i & 1]));
          }
        }
        const int mat = lane >> 3;
        const uint32_t soff = (wwarp * 16 + (mat & 1) * 8 + (lane & 7)) * 128;
        const uint32_t kdst = ((L & 1) ? KB_ROW0 : slots) + soff, vdst = ((L & 1) ? VB_ROW0 : slots + 8192) + soff;
        const uint32_t hs = (L & 1) ? 8192 : 16384;
        wgmma_wait<0>();
        reg_fence<96>(acc[0]);
        reg_fence<96>(acc[1]);
        if (lane0) mbar_arrive(bars + 8u * (B_EMPTY + ((n - 1) & 7)));
        STAMP(inst == KSQ, 16);
        GTL(2 + L * 8);
        if (!afree) mbar_wait(bars + 8u * B_AFREE, inst & 1);
#pragma unroll
        for (int t = 2; t < CSPF; t++) cs[t] = lds128(csa + (t + 4) * 64);
#pragma unroll
        for (int t = 0; t < 20; t++) {
          const int p = t >= 16 ? 0 : ((t >> 2) & 1) + 1, jp = t & 3;
          if (t + CSPF < 20) {
            const int tn = t + CSPF, jn = tn >= 16 ? tn - 16 : (tn & 7) + 4;
            cs[tn] = lds128(csa + jn * 64);
          }
          const int j = p * 8 + 2 * jp;
          const float2 cs0 = make_float2(__uint_as_float(cs[t].x), __uint_as_float(cs[t].y));
          const float2 cs1 = make_float2(__uint_as_float(cs[t].z), __uint_as_float(cs[t].w));
          const uint32_t sw = ((2 * jp + (mat >> 1)) ^ (lane & 7)) << 4;
#pragma unroll
          for (int h = 0; h < 2; h++) {
            if (t < 16 && h != (t < 8 ? 1 : 0)) continue;
            const float* a = &acc[h][4 * j];
            const uint32_t r0 = pack_bf16x2(fmaf(nmean[h][0], cs0.x, a[0]) * rinv[h][0], fmaf(nmean[h][0], cs0.y, a[1]) * rinv[h][0]);
            const uint32_t r1 = pack_bf16x2(fmaf(nmean[h][1], cs0.x, a[2]) * rinv[h][1], fmaf(nmean[h][1], cs0.y, a[3]) * rinv[h][1]);
            const uint32_t r2 = pack_bf16x2(fmaf(nmean[h][0], cs1.x, a[4]) * rinv[h][0], fmaf(nmean[h][0], cs1.y, a[5]) * rinv[h][0]);
            const uint32_t r3 = pack_bf16x2(fmaf(nmean[h][1], cs1.x, a[6]) * rinv[h][1], fmaf(nmean[h][1], cs1.y, a[7]) * rinv[h][1]);
            const uint32_t dst = p == 0 ? slots + 3 * 16384 + soff + h * 8192 : (p == 1 ? kdst : vdst) + h * hs;
            stmatrix_x4(dst + sw, r0, r1, r2, r3);
          }
          if (t == 7 || t == 15) {
            fence_proxy_async_smem();
            named_bar_arrive(t == 7 ? 3 : 7, 160);
          }
        }
      }
      fence_proxy_async_smem();
      setmaxnreg_dec<128>();
      named_bar_sync(4, 256);
      }
      GTL(3 + L * 8);
      {
        PHASE_IDS
        if ((L & 1) == 0) attention_a(asst, L, gb, hp, inst & 1, ch, wwarp, lane, P.zero);
        else attention_b(asst, gb, inst & 1, wwarp, lane);
        GTL(4 + L * 8);
        fence_proxy_async_smem();
      }
      if (asst) {
        named_bar_arrive(5, 256);
        if (inst == 1) {
          mbar_wait(bars + 8u * B_AFREE, 0);
          colsum_part(&P.wqkv[1], 1, qr, hp);
          if (lane0) mbar_arrive(bars + 8u * B_CSD);
        }
        continue;
      }
      {
        named_bar_sync(5, 256);
        const int wwarp = warp & 3;
        if (wwarp < 2 && elect_one()) {
          tma_store_3d(&P.o, slots + 3 * 16384 + wwarp * 8192, 0, gb * 128 + wwarp * 64, hp);
          bulk_commit();
          bulk_wait0();
          mbar_arrive(bars + 8u * B_AFREE);
          fence_proxy_async_all();
          red_relaxed_add(g_flags + F_O + (gb * 2 + wwarp) * OSTR + hp, 1u);
        }
        __syncwarp();
      }
      GTL(5 + L * 8);

      {
        float acc[64];
        const int n0 = w_first(inst);
        const bool pre = w_pre(inst);
        const uint32_t dl = ch * 10u * (UNIT >> 4);
        mbar_wait_lazy<100>(bars + 8u * (B_TURN + ch), tpar);
        tpar ^= 1u;
        mbar_wait(bars + 8u * (B_FULL + (n0 & 7)), (n0 >> 3) & 1);
        GTL(6 + L * 8);
#pragma unroll
        for (int kt = 0; kt < 16; kt++) {
          const int n = n0 + kt;
          STAMP(inst == KSW, 20 + kt);
          const uint32_t da = ((base + w_ua(kt) * UNIT) >> 4) + 0x10000u + (w_ua(kt) < 10 ? dl : 0u - dl);
          uint32_t db = ((base + w_ub(kt) * UNIT) >> 4) + ((UNIT >> 4) << 16) + (w_ub(kt) < 10 ? dl : 0u - dl);
          if (pre_idx(kt) >= 0 && pre) db = ((slots + pre_idx(kt) * 2 * UNIT) >> 4) + ((UNIT >> 4) << 16);
          if (kt == PRE0 && pre) mbar_wait(bars + 8u * B_PRE, __popc(PREMASK & ((1u << inst) - 1u)) & 1);
          if (kt == 15 && lane0 && (inst & 3) != 0) mbar_arrive(bars + 8u * (B_TURN + (ch ^ 1)));
          wgmma_fence();
          if (kt == 0) wgmma_n128_ssz_ta0_tb1(acc, desc_lo(da), desc_lo(db));
#pragma unroll
          for (int k16 = kt == 0 ? 1 : 0; k16 < 4; k16++) wgmma_n128_ss_ta0_tb1(acc, desc_lo(da + 2 * k16), desc_lo(db + 128 * k16), 1);
          wgmma_commit();
          const uint32_t nb = bars + 8u * (kt == 15 ? B_RESF : B_FULL + ((n + 1) & 7)), np = kt == 15 ? ch : ((n + 1) >> 3) & 1;
          const bool ok = mbar_test(nb, np);
          if (kt > 0) {
            wgmma_wait<1>();
            if (lane0) mbar_arrive(bars + 8u * (B_EMPTY + ((n - 1) & 7)));
          }
          if (!ok) mbar_wait(nb, np);
        }
        PHASE_IDS
        const uint32_t xb = base + (8 + ch * 10) * UNIT;
        const int mat = lane >> 3;
        const uint32_t xrow = xb + (wwarp * 16 + (mat & 1) * 8 + (lane & 7)) * 128;
        uint32_t xv[8][4];
#pragma unroll
        for (int jp = 0; jp < 8; jp++)
          ldmatrix_x4(xv[jp], xrow + (jp >> 2) * UNIT + (((2 * (jp & 3) + (mat >> 1)) ^ (lane & 7)) << 4));
        wgmma_wait<0>();
        reg_fence<64>(acc);
        if (lane0) mbar_arrive(bars + 8u * (B_EMPTY + ((n0 + 15) & 7)));
        STAMP(inst == KSW, 36);
        GTL(7 + L * 8);
#pragma unroll
        for (int jp = 0; jp < 8; jp++) {
#pragma unroll
          for (int q = 0; q < 4; q++) xv[jp][q] = add_bf16x2(xv[jp][q], pack_bf16x2(acc[8 * jp + 2 * q], acc[8 * jp + 2 * q + 1]));
          stmatrix_x4(xrow + (jp >> 2) * UNIT + (((2 * (jp & 3) + (mat >> 1)) ^ (lane & 7)) << 4), xv[jp][0], xv[jp][1],
                      xv[jp][2], xv[jp][3]);
        }
        fence_proxy_async_smem();
        named_bar_sync(1 + ch, 128);
        const int grow = ch * 1024 + rt * 64;
        if (wwarp == 0) {
          if (elect_one()) {
            tma_store_3d(&P.xr[L == 3 ? 2 : 1], xb, 0, grow, ct * 2);
            bulk_commit();
            bulk_wait_read0();
            mbar_arrive(bars + 8u * B_RESE);
            bulk_wait0();
            TGET(t35);
            fence_proxy_async_all();
            if (L < 3) red_relaxed_add(g_flags + F_X + (ch * 8 + (rt >> 1)) * XSTR + ct, 1u);
            if (L == 2) TPUT(ch, 35, t35);
          }
          __syncwarp();
        } else if (lane == 0) {
          mbar_arrive(bars + 8u * B_RESE);
        }
        if (L < 3) {
          const unsigned ep1 = lds32(base + OFF_EPOCH);
          float s1[2] = {0.f, 0.f}, s2[2] = {0.f, 0.f};
#pragma unroll
          for (int jp = 0; jp < 8; jp++)
#pragma unroll
            for (int q = 0; q < 4; q++) {
              const float x0 = bf_lo(xv[jp][q]), x1 = bf_hi(xv[jp][q]);
              s1[q & 1] += x0 + x1;
              s2[q & 1] = fmaf(x0, x0, fmaf(x1, x1, s2[q & 1]));
            }
#pragma unroll
          for (int r = 0; r < 2; r++) {
            s1[r] += __shfl_xor_sync(0xffffffffu, s1[r], 1);
            s2[r] += __shfl_xor_sync(0xffffffffu, s2[r], 1);
            s1[r] += __shfl_xor_sync(0xffffffffu, s1[r], 2);
            s2[r] += __shfl_xor_sync(0xffffffffu, s2[r], 2);
            if (c == 0) st_rec(&g_stats[L + 1][ct][grow + wwarp * 16 + g + 8 * r], s1[r], s2[r], 0.f, ep1);
          }
        }
        GTL(8 + L * 8);
      }
    }
    if (threadIdx.x == 128) atomicAdd(g_flags + F_DONE, 1u);
  }
}

typedef CUresult (*PFN_tmEncode)(CUtensorMap*, CUtensorMapDataType, cuuint32_t, void*, const cuuint64_t*,
                                 const cuuint64_t*, const cuuint32_t*, const cuuint32_t*, CUtensorMapInterleave,
                                 CUtensorMapSwizzle, CUtensorMapL2promotion, CUtensorMapFloatOOBfill);

PFN_tmEncode get_encode_fn() {
  static PFN_tmEncode fn = nullptr;
  if (!fn) {
    cudaDriverEntryPointQueryResult qr;
    void* p = nullptr;
    cudaGetDriverEntryPoint("cuTensorMapEncodeTiled", &p, cudaEnableDefault, &qr);
    fn = (PFN_tmEncode)p;
  }
  return fn;
}

CUtensorMap make_map(const void* ptr, int rows, int cols, int inner, int box_rows, int box_blk) {
  CUtensorMap m;
  cuuint64_t gdim[3] = {(cuuint64_t)inner, (cuuint64_t)rows, (cuuint64_t)(cols / inner)};
  cuuint64_t gstr[2] = {(cuuint64_t)cols * 2, (cuuint64_t)inner * 2};
  cuuint32_t box[3] = {64, (cuuint32_t)box_rows, (cuuint32_t)box_blk};
  cuuint32_t estr[3] = {1, 1, 1};
  get_encode_fn()(&m, CU_TENSOR_MAP_DATA_TYPE_BFLOAT16, 3, const_cast<void*>(ptr), gdim, gstr, box, estr,
                  CU_TENSOR_MAP_INTERLEAVE_NONE, CU_TENSOR_MAP_SWIZZLE_128B, CU_TENSOR_MAP_L2_PROMOTION_L2_128B,
                  CU_TENSOR_MAP_FLOAT_OOB_FILL_NONE);
  return m;
}

}

extern "C" void kernel_launch(void* const* d_in, const int* in_sizes, int n_in, void* d_out, int out_size) {
  (void)in_sizes; (void)n_in; (void)out_size;
  void *p_o, *p_x;
  cudaGetSymbolAddress(&p_o, g_o);
  cudaGetSymbolAddress(&p_x, g_x);
  static bool attr_done = false;
  if (!attr_done) {
    cudaFuncSetAttribute(fused_kernel, cudaFuncAttributeMaxDynamicSharedMemorySize, SMEM_BYTES);
    attr_done = true;
  }
  Params P;
  P.in_x = (const __nv_bfloat16*)d_in[0];
  P.wqkv_p[0] = (const __nv_bfloat16*)d_in[1];
  P.wo_p[0] = (const __nv_bfloat16*)d_in[2];
  P.wqkv_p[1] = (const __nv_bfloat16*)d_in[4];
  P.wo_p[1] = (const __nv_bfloat16*)d_in[5];
  P.out = (__nv_bfloat16*)d_out;
  P.zero = 0;
  P.xq[0] = make_map(P.in_x, S_LEN, DM, 64, 128, 1);
  P.xq[1] = make_map(p_x, S_LEN, DM, 64, 128, 1);
  P.xr[0] = make_map(P.in_x, S_LEN, DM, 64, 64, 2);
  P.xr[1] = make_map(p_x, S_LEN, DM, 64, 64, 2);
  P.xr[2] = make_map(d_out, S_LEN, DM, 64, 64, 2);
  P.o = make_map(p_o, S_LEN, DM, 64, 64, 1);
  for (int t = 0; t < 2; t++) {
    P.wqkv[t] = make_map(P.wqkv_p[t], DM, NQKV, 1024, 64, 3);
    P.wo[t] = make_map(P.wo_p[t], DM, DM, 64, 64, 2);
  }
  fused_kernel<<<NCTA, 512, SMEM_BYTES>>>(P);
}
```

```cpp
#include <cuda_runtime.h>
#include <cuda_bf16.h>
#include <cuda.h>
#include <stdint.h>

namespace {

constexpr int S_LEN = 2048;
constexpr int DM = 1024;
constexpr int NQKV = 3072;
constexpr int NCTA = 128;

__device__ __align__(1024) uint8_t g_kvA[2][16][16][2][16384];
__device__ __align__(1024) uint8_t g_kvB[2][16][16][4096];
__device__ __align__(1024) uint8_t g_zero[16384];
__device__ __align__(1024) __nv_bfloat16 g_o[S_LEN * DM];
__device__ __align__(1024) __nv_bfloat16 g_x[S_LEN * DM];
__device__ __align__(1024) float4 g_stats[4][8][S_LEN];
__device__ __align__(1024) float4 g_cs[2][16][8][64];
constexpr int F_X = 0;
constexpr int XSTR = 32, OSTR = 32, KSTR = 32;
constexpr int F_O = F_X + 16 * XSTR;
constexpr int F_KV = F_O + 32 * OSTR;
constexpr int F_DONE = F_KV + 256 * KSTR;
__device__ __align__(1024) unsigned g_flags[F_DONE + 32];

constexpr uint32_t SBASE = 1024;
constexpr int UNIT = 8192;
constexpr int NUNITS = 20;
constexpr int OFF_SLOT = NUNITS * UNIT;
constexpr int OFF_BAR = OFF_SLOT + 4 * 16384;
constexpr int OFF_EPOCH = OFF_BAR + 296;
constexpr int OFF_CS = OFF_BAR + 304;
constexpr int OFF_RS = OFF_CS + 1536;
constexpr int OFF_TS = OFF_RS + 1024;
constexpr int SMEM_BYTES = OFF_RS + 1024;
constexpr int B_FULL = 0, B_EMPTY = 8, B_PREP = 16, B_HALO = 18, B_REL = 22, B_AFREE = 25, B_TURN = 26, B_XRDY = 28,
              B_CS = 30, B_CSD = 31, B_GO = 32, B_PRE = 33, B_RESF = 34, B_RESE = 35;

__device__ __forceinline__ uint32_t smem_u32(const void* p) { return (uint32_t)__cvta_generic_to_shared(p); }

__device__ __forceinline__ void mbar_init(uint32_t bar, uint32_t cnt) {
  asm volatile("mbarrier.init.shared::cta.b64 [%0], %1;" ::"r"(bar), "r"(cnt));
}
__device__ __forceinline__ void mbar_expect_tx(uint32_t bar, uint32_t bytes) {
  asm volatile("mbarrier.arrive.expect_tx.shared::cta.b64 _, [%0], %1;" ::"r"(bar), "r"(bytes) : "memory");
}
__device__ __forceinline__ void mbar_arrive(uint32_t bar) {
  asm volatile("mbarrier.arrive.shared::cta.b64 _, [%0];" ::"r"(bar) : "memory");
}
__device__ __forceinline__ bool mbar_try_wait(uint32_t bar, uint32_t parity) {
  uint32_t ok;
  asm volatile(
      "{\n.reg .pred p;\nmbarrier.try_wait.parity.shared::cta.b64 p, [%1], %2;\nselp.b32 %0, 1, 0, p;\n}\n"
      : "=r"(ok)
      : "r"(bar), "r"(parity)
      : "memory");
  return ok != 0;
}
__device__ __forceinline__ bool mbar_test(uint32_t bar, uint32_t parity) {
  uint32_t ok;
  asm volatile(
      "{\n.reg .pred p;\nmbarrier.test_wait.parity.shared::cta.b64 p, [%1], %2;\nselp.b32 %0, 1, 0, p;\n}\n"
      : "=r"(ok)
      : "r"(bar), "r"(parity)
      : "memory");
  return ok != 0;
}
__device__ __forceinline__ void mbar_wait(uint32_t bar, uint32_t parity) {
#pragma unroll 1
  for (uint32_t it = 0; it < (1u << 18); ++it) {
    if (mbar_try_wait(bar, parity)) return;
  }
}
__device__ __forceinline__ void mbar_pace(uint32_t bar, uint32_t parity) {
#pragma unroll 1
  for (uint32_t it = 0; it < 24; ++it) {
    if (mbar_try_wait(bar, parity)) return;
  }
}
template <int NS>
__device__ __forceinline__ void mbar_wait_lazy(uint32_t bar, uint32_t parity) {
#pragma unroll 1
  for (uint32_t it = 0; it < (1u << 18); ++it) {
    if (mbar_try_wait(bar, parity)) return;
    __nanosleep(NS);
  }
}
__device__ __forceinline__ bool elect_one() {
  uint32_t ok;
  asm volatile("{\n.reg .pred p;\nelect.sync _|p, 0xffffffff;\nselp.b32 %0, 1, 0, p;\n}\n" : "=r"(ok));
  return ok != 0;
}
__device__ __forceinline__ void fence_barrier_init() { asm volatile("fence.mbarrier_init.release.cluster;" ::: "memory"); }
__device__ __forceinline__ void fence_proxy_async_smem() { asm volatile("fence.proxy.async.shared::cta;" ::: "memory"); }
__device__ __forceinline__ void fence_proxy_async_all() { asm volatile("fence.proxy.async.global;" ::: "memory"); }

__device__ __forceinline__ void tma_load_3d(uint32_t dst, const CUtensorMap* map, uint32_t bar, int c0, int c1, int c2) {
  asm volatile(
      "cp.async.bulk.tensor.3d.shared::cluster.global.mbarrier::complete_tx::bytes [%0], [%1, {%3, %4, %5}], [%2];" ::"r"(dst),
      "l"(map), "r"(bar), "r"(c0), "r"(c1), "r"(c2)
      : "memory");
}
__device__ __forceinline__ void bulk_load(uint32_t dst, const void* src, uint32_t bytes, uint32_t bar) {
  asm volatile("cp.async.bulk.shared::cluster.global.mbarrier::complete_tx::bytes [%0], [%1], %2, [%3];" ::"r"(dst),
               "l"(src), "r"(bytes), "r"(bar)
               : "memory");
}
__device__ __forceinline__ void bulk_store(void* dst, uint32_t src, uint32_t bytes) {
  asm volatile("cp.async.bulk.global.shared::cta.bulk_group [%0], [%1], %2;" ::"l"(dst), "r"(src), "r"(bytes) : "memory");
}
__device__ __forceinline__ void tma_store_3d(const CUtensorMap* map, uint32_t src, int c0, int c1, int c2) {
  asm volatile("cp.async.bulk.tensor.3d.global.shared::cta.bulk_group [%0, {%2, %3, %4}], [%1];" ::"l"(map), "r"(src),
               "r"(c0), "r"(c1), "r"(c2)
               : "memory");
}
__device__ __forceinline__ void bulk_commit() { asm volatile("cp.async.bulk.commit_group;" ::: "memory"); }
__device__ __forceinline__ void bulk_wait_read0() { asm volatile("cp.async.bulk.wait_group.read 0;" ::: "memory"); }
__device__ __forceinline__ void bulk_wait0() { asm volatile("cp.async.bulk.wait_group 0;" ::: "memory"); }
__device__ __forceinline__ void named_bar_sync(int id, int nthreads) {
  asm volatile("bar.sync %0, %1;" ::"r"(id), "r"(nthreads) : "memory");
}
__device__ __forceinline__ void named_bar_arrive(int id, int nthreads) {
  asm volatile("bar.arrive %0, %1;" ::"r"(id), "r"(nthreads) : "memory");
}

__device__ __forceinline__ void wgmma_fence() { asm volatile("wgmma.fence.sync.aligned;\n" ::: "memory"); }
__device__ __forceinline__ void wgmma_commit() { asm volatile("wgmma.commit_group.sync.aligned;\n" ::: "memory"); }
template <int N>
__device__ __forceinline__ void wgmma_wait() {
  asm volatile("wgmma.wait_group.sync.aligned %0;\n" ::"n"(N) : "memory");
}
template <int R>
__device__ __forceinline__ void setmaxnreg_inc() { asm volatile("setmaxnreg.inc.sync.aligned.u32 %0;\n" ::"n"(R)); }
template <int R>
__device__ __forceinline__ void setmaxnreg_dec() { asm volatile("setmaxnreg.dec.sync.aligned.u32 %0;\n" ::"n"(R)); }
template <int N>
__device__ __forceinline__ void reg_fence(float* r) {
#pragma unroll
  for (int i = 0; i < N; i++) asm volatile("" : "+f"(r[i])::"memory");
}

template <int N>
__device__ __forceinline__ void reg_define(float* r) {
#pragma unroll
  for (int i = 0; i < N; i++) r[i] = 0.f;
}

__device__ __forceinline__ uint64_t desc_lo(uint32_t lo) {
  uint64_t d;
  asm("mov.b64 %0, {%1, %2};" : "=l"(d) : "r"(lo), "r"(0x40000040u));
  return d;
}
__device__ __forceinline__ uint64_t make_desc(uint32_t addr, uint32_t lbo_bytes) {
  return desc_lo((addr >> 4) + ((lbo_bytes >> 4) << 16));
}

__device__ __forceinline__ void wgmma_n192_ss_ta0_tb1(float* d, uint64_t descA, uint64_t descB, int scaleD) {
  asm volatile("{\n.reg .pred p;\nsetp.ne.b32 p, %98, 0;\n"
    "wgmma.mma_async.sync.aligned.m64n192k16.f32.bf16.bf16 {%0, %1, %2, %3, %4, %5, %6, %7, %8, %9, %10, %11, %12, %13, %14, %15, %16, %17, %18, %19, %20, %21, %22, %23, %24, %25, %26, %27, %28, %29, %30, %31, %32, %33, %34, %35, %36, %37, %38, %39, %40, %41, %42, %43, %44, %45, %46, %47, %48, %49, %50, %51, %52, %53, %54, %55, %56, %57, %58, %59, %60, %61, %62, %63, %64, %65, %66, %67, %68, %69, %70, %71, %72, %73, %74, %75, %76, %77, %78, %79, %80, %81, %82, %83, %84, %85, %86, %87, %88, %89, %90, %91, %92, %93, %94, %95}, %96, %97, p, 1, 1, 0, 1;\n}\n"
    : "+f"(d[0]), "+f"(d[1]), "+f"(d[2]), "+f"(d[3]), "+f"(d[4]), "+f"(d[5]), "+f"(d[6]), "+f"(d[7]), "+f"(d[8]), "+f"(d[9]), "+f"(d[10]), "+f"(d[11]), "+f"(d[12]), "+f"(d[13]), "+f"(d[14]), "+f"(d[15]), "+f"(d[16]), "+f"(d[17]), "+f"(d[18]), "+f"(d[19]), "+f"(d[20]), "+f"(d[21]), "+f"(d[22]), "+f"(d[23]), "+f"(d[24]), "+f"(d[25]), "+f"(d[26]), "+f"(d[27]), "+f"(d[28]), "+f"(d[29]), "+f"(d[30]), "+f"(d[31]), "+f"(d[32]), "+f"(d[33]), "+f"(d[34]), "+f"(d[35]), "+f"(d[36]), "+f"(d[37]), "+f"(d[38]), "+f"(d[39]), "+f"(d[40]), "+f"(d[41]), "+f"(d[42]), "+f"(d[43]), "+f"(d[44]), "+f"(d[45]), "+f"(d[46]), "+f"(d[47]), "+f"(d[48]), "+f"(d[49]), "+f"(d[50]), "+f"(d[51]), "+f"(d[52]), "+f"(d[53]), "+f"(d[54]), "+f"(d[55]), "+f"(d[56]), "+f"(d[57]), "+f"(d[58]), "+f"(d[59]), "+f"(d[60]), "+f"(d[61]), "+f"(d[62]), "+f"(d[63]), "+f"(d[64]), "+f"(d[65]), "+f"(d[66]), "+f"(d[67]), "+f"(d[68]), "+f"(d[69]), "+f"(d[70]), "+f"(d[71]), "+f"(d[72]), "+f"(d[73]), "+f"(d[74]), "+f"(d[75]), "+f"(d[76]), "+f"(d[77]), "+f"(d[78]), "+f"(d[79]), "+f"(d[80]), "+f"(d[81]), "+f"(d[82]), "+f"(d[83]), "+f"(d[84]), "+f"(d[85]), "+f"(d[86]), "+f"(d[87]), "+f"(d[88]), "+f"(d[89]), "+f"(d[90]), "+f"(d[91]), "+f"(d[92]), "+f"(d[93]), "+f"(d[94]), "+f"(d[95])
    : "l"(descA), "l"(descB), "r"(scaleD));
}

__device__ __forceinline__ void wgmma_n128_ss_ta0_tb1(float* d, uint64_t descA, uint64_t descB, int scaleD) {
  asm volatile("{\n.reg .pred p;\nsetp.ne.b32 p, %66, 0;\n"
    "wgmma.mma_async.sync.aligned.m64n128k16.f32.bf16.bf16 {%0, %1, %2, %3, %4, %5, %6, %7, %8, %9, %10, %11, %12, %13, %14, %15, %16, %17, %18, %19, %20, %21, %22, %23, %24, %25, %26, %27, %28, %29, %30, %31, %32, %33, %34, %35, %36, %37, %38, %39, %40, %41, %42, %43, %44, %45, %46, %47, %48, %49, %50, %51, %52, %53, %54, %55, %56, %57, %58, %59, %60, %61, %62, %63}, %64, %65, p, 1, 1, 0, 1;\n}\n"
    : "+f"(d[0]), "+f"(d[1]), "+f"(d[2]), "+f"(d[3]), "+f"(d[4]), "+f"(d[5]), "+f"(d[6]), "+f"(d[7]), "+f"(d[8]), "+f"(d[9]), "+f"(d[10]), "+f"(d[11]), "+f"(d[12]), "+f"(d[13]), "+f"(d[14]), "+f"(d[15]), "+f"(d[16]), "+f"(d[17]), "+f"(d[18]), "+f"(d[19]), "+f"(d[20]), "+f"(d[21]), "+f"(d[22]), "+f"(d[23]), "+f"(d[24]), "+f"(d[25]), "+f"(d[26]), "+f"(d[27]), "+f"(d[28]), "+f"(d[29]), "+f"(d[30]), "+f"(d[31]), "+f"(d[32]), "+f"(d[33]), "+f"(d[34]), "+f"(d[35]), "+f"(d[36]), "+f"(d[37]), "+f"(d[38]), "+f"(d[39]), "+f"(d[40]), "+f"(d[41]), "+f"(d[42]), "+f"(d[43]), "+f"(d[44]), "+f"(d[45]), "+f"(d[46]), "+f"(d[47]), "+f"(d[48]), "+f"(d[49]), "+f"(d[50]), "+f"(d[51]), "+f"(d[52]), "+f"(d[53]), "+f"(d[54]), "+f"(d[55]), "+f"(d[56]), "+f"(d[57]), "+f"(d[58]), "+f"(d[59]), "+f"(d[60]), "+f"(d[61]), "+f"(d[62]), "+f"(d[63])
    : "l"(descA), "l"(descB), "r"(scaleD));
}

__device__ __forceinline__ void wgmma_n192_ssz_ta0_tb1(float* d, uint64_t descA, uint64_t descB) {
  asm volatile("{\n.reg .pred p;\nsetp.ne.b32 p, 0, 0;\n"
    "wgmma.mma_async.sync.aligned.m64n192k16.f32.bf16.bf16 {%0, %1, %2, %3, %4, %5, %6, %7, %8, %9, %10, %11, %12, %13, %14, %15, %16, %17, %18, %19, %20, %21, %22, %23, %24, %25, %26, %27, %28, %29, %30, %31, %32, %33, %34, %35, %36, %37, %38, %39, %40, %41, %42, %43, %44, %45, %46, %47, %48, %49, %50, %51, %52, %53, %54, %55, %56, %57, %58, %59, %60, %61, %62, %63, %64, %65, %66, %67, %68, %69, %70, %71, %72, %73, %74, %75, %76, %77, %78, %79, %80, %81, %82, %83, %84, %85, %86, %87, %88, %89, %90, %91, %92, %93, %94, %95}, %96, %97, p, 1, 1, 0, 1;\n}\n"
    : "=f"(d[0]), "=f"(d[1]), "=f"(d[2]), "=f"(d[3]), "=f"(d[4]), "=f"(d[5]), "=f"(d[6]), "=f"(d[7]), "=f"(d[8]), "=f"(d[9]), "=f"(d[10]), "=f"(d[11]), "=f"(d[12]), "=f"(d[13]), "=f"(d[14]), "=f"(d[15]), "=f"(d[16]), "=f"(d[17]), "=f"(d[18]), "=f"(d[19]), "=f"(d[20]), "=f"(d[21]), "=f"(d[22]), "=f"(d[23]), "=f"(d[24]), "=f"(d[25]), "=f"(d[26]), "=f"(d[27]), "=f"(d[28]), "=f"(d[29]), "=f"(d[30]), "=f"(d[31]), "=f"(d[32]), "=f"(d[33]), "=f"(d[34]), "=f"(d[35]), "=f"(d[36]), "=f"(d[37]), "=f"(d[38]), "=f"(d[39]), "=f"(d[40]), "=f"(d[41]), "=f"(d[42]), "=f"(d[43]), "=f"(d[44]), "=f"(d[45]), "=f"(d[46]), "=f"(d[47]), "=f"(d[48]), "=f"(d[49]), "=f"(d[50]), "=f"(d[51]), "=f"(d[52]), "=f"(d[53]), "=f"(d[54]), "=f"(d[55]), "=f"(d[56]), "=f"(d[57]), "=f"(d[58]), "=f"(d[59]), "=f"(d[60]), "=f"(d[61]), "=f"(d[62]), "=f"(d[63]), "=f"(d[64]), "=f"(d[65]), "=f"(d[66]), "=f"(d[67]), "=f"(d[68]), "=f"(d[69]), "=f"(d[70]), "=f"(d[71]), "=f"(d[72]), "=f"(d[73]), "=f"(d[74]), "=f"(d[75]), "=f"(d[76]), "=f"(d[77]), "=f"(d[78]), "=f"(d[79]), "=f"(d[80]), "=f"(d[81]), "=f"(d[82]), "=f"(d[83]), "=f"(d[84]), "=f"(d[85]), "=f"(d[86]), "=f"(d[87]), "=f"(d[88]), "=f"(d[89]), "=f"(d[90]), "=f"(d[91]), "=f"(d[92]), "=f"(d[93]), "=f"(d[94]), "=f"(d[95])
    : "l"(descA), "l"(descB));
}

__device__ __forceinline__ void wgmma_n128_ssz_ta0_tb1(float* d, uint64_t descA, uint64_t descB) {
  asm volatile("{\n.reg .pred p;\nsetp.ne.b32 p, 0, 0;\n"
    "wgmma.mma_async.sync.aligned.m64n128k16.f32.bf16.bf16 {%0, %1, %2, %3, %4, %5, %6, %7, %8, %9, %10, %11, %12, %13, %14, %15, %16, %17, %18, %19, %20, %21, %22, %23, %24, %25, %26, %27, %28, %29, %30, %31, %32, %33, %34, %35, %36, %37, %38, %39, %40, %41, %42, %43, %44, %45, %46, %47, %48, %49, %50, %51, %52, %53, %54, %55, %56, %57, %58, %59, %60, %61, %62, %63}, %64, %65, p, 1, 1, 0, 1;\n}\n"
    : "=f"(d[0]), "=f"(d[1]), "=f"(d[2]), "=f"(d[3]), "=f"(d[4]), "=f"(d[5]), "=f"(d[6]), "=f"(d[7]), "=f"(d[8]), "=f"(d[9]), "=f"(d[10]), "=f"(d[11]), "=f"(d[12]), "=f"(d[13]), "=f"(d[14]), "=f"(d[15]), "=f"(d[16]), "=f"(d[17]), "=f"(d[18]), "=f"(d[19]), "=f"(d[20]), "=f"(d[21]), "=f"(d[22]), "=f"(d[23]), "=f"(d[24]), "=f"(d[25]), "=f"(d[26]), "=f"(d[27]), "=f"(d[28]), "=f"(d[29]), "=f"(d[30]), "=f"(d[31]), "=f"(d[32]), "=f"(d[33]), "=f"(d[34]), "=f"(d[35]), "=f"(d[36]), "=f"(d[37]), "=f"(d[38]), "=f"(d[39]), "=f"(d[40]), "=f"(d[41]), "=f"(d[42]), "=f"(d[43]), "=f"(d[44]), "=f"(d[45]), "=f"(d[46]), "=f"(d[47]), "=f"(d[48]), "=f"(d[49]), "=f"(d[50]), "=f"(d[51]), "=f"(d[52]), "=f"(d[53]), "=f"(d[54]), "=f"(d[55]), "=f"(d[56]), "=f"(d[57]), "=f"(d[58]), "=f"(d[59]), "=f"(d[60]), "=f"(d[61]), "=f"(d[62]), "=f"(d[63])
    : "l"(descA), "l"(descB));
}

__device__ __forceinline__ void wgmma_n64_ss_ta0_tb0(float* d, uint64_t descA, uint64_t descB, int scaleD) {
  asm volatile("{\n.reg .pred p;\nsetp.ne.b32 p, %34, 0;\n"
    "wgmma.mma_async.sync.aligned.m64n64k16.f32.bf16.bf16 {%0, %1, %2, %3, %4, %5, %6, %7, %8, %9, %10, %11, %12, %13, %14, %15, %16, %17, %18, %19, %20, %21, %22, %23, %24, %25, %26, %27, %28, %29, %30, %31}, %32, %33, p, 1, 1, 0, 0;\n}\n"
    : "+f"(d[0]), "+f"(d[1]), "+f"(d[2]), "+f"(d[3]), "+f"(d[4]), "+f"(d[5]), "+f"(d[6]), "+f"(d[7]), "+f"(d[8]), "+f"(d[9]), "+f"(d[10]), "+f"(d[11]), "+f"(d[12]), "+f"(d[13]), "+f"(d[14]), "+f"(d[15]), "+f"(d[16]), "+f"(d[17]), "+f"(d[18]), "+f"(d[19]), "+f"(d[20]), "+f"(d[21]), "+f"(d[22]), "+f"(d[23]), "+f"(d[24]), "+f"(d[25]), "+f"(d[26]), "+f"(d[27]), "+f"(d[28]), "+f"(d[29]), "+f"(d[30]), "+f"(d[31])
    : "l"(descA), "l"(descB), "r"(scaleD));
}

__device__ __forceinline__ void wgmma_n64_ssz_ta0_tb0(float* d, uint64_t descA, uint64_t descB) {
  asm volatile("{\n.reg .pred p;\nsetp.ne.b32 p, 0, 0;\n"
    "wgmma.mma_async.sync.aligned.m64n64k16.f32.bf16.bf16 {%0, %1, %2, %3, %4, %5, %6, %7, %8, %9, %10, %11, %12, %13, %14, %15, %16, %17, %18, %19, %20, %21, %22, %23, %24, %25, %26, %27, %28, %29, %30, %31}, %32, %33, p, 1, 1, 0, 0;\n}\n"
    : "=f"(d[0]), "=f"(d[1]), "=f"(d[2]), "=f"(d[3]), "=f"(d[4]), "=f"(d[5]), "=f"(d[6]), "=f"(d[7]), "=f"(d[8]), "=f"(d[9]), "=f"(d[10]), "=f"(d[11]), "=f"(d[12]), "=f"(d[13]), "=f"(d[14]), "=f"(d[15]), "=f"(d[16]), "=f"(d[17]), "=f"(d[18]), "=f"(d[19]), "=f"(d[20]), "=f"(d[21]), "=f"(d[22]), "=f"(d[23]), "=f"(d[24]), "=f"(d[25]), "=f"(d[26]), "=f"(d[27]), "=f"(d[28]), "=f"(d[29]), "=f"(d[30]), "=f"(d[31])
    : "l"(descA), "l"(descB));
}

__device__ __forceinline__ void wgmma_n80_ss_ta0_tb0(float* d, uint64_t descA, uint64_t descB, int scaleD) {
  asm volatile("{\n.reg .pred p;\nsetp.ne.b32 p, %42, 0;\n"
    "wgmma.mma_async.sync.aligned.m64n80k16.f32.bf16.bf16 {%0, %1, %2, %3, %4, %5, %6, %7, %8, %9, %10, %11, %12, %13, %14, %15, %16, %17, %18, %19, %20, %21, %22, %23, %24, %25, %26, %27, %28, %29, %30, %31, %32, %33, %34, %35, %36, %37, %38, %39}, %40, %41, p, 1, 1, 0, 0;\n}\n"
    : "+f"(d[0]), "+f"(d[1]), "+f"(d[2]), "+f"(d[3]), "+f"(d[4]), "+f"(d[5]), "+f"(d[6]), "+f"(d[7]), "+f"(d[8]), "+f"(d[9]), "+f"(d[10]), "+f"(d[11]), "+f"(d[12]), "+f"(d[13]), "+f"(d[14]), "+f"(d[15]), "+f"(d[16]), "+f"(d[17]), "+f"(d[18]), "+f"(d[19]), "+f"(d[20]), "+f"(d[21]), "+f"(d[22]), "+f"(d[23]), "+f"(d[24]), "+f"(d[25]), "+f"(d[26]), "+f"(d[27]), "+f"(d[28]), "+f"(d[29]), "+f"(d[30]), "+f"(d[31]), "+f"(d[32]), "+f"(d[33]), "+f"(d[34]), "+f"(d[35]), "+f"(d[36]), "+f"(d[37]), "+f"(d[38]), "+f"(d[39])
    : "l"(descA), "l"(descB), "r"(scaleD));
}

__device__ __forceinline__ void wgmma_n32_rs_tb1(float* d, const uint32_t* a, uint64_t descB, int scaleD) {
  asm volatile("{\n.reg .pred p;\nsetp.ne.b32 p, %21, 0;\n"
    "wgmma.mma_async.sync.aligned.m64n32k16.f32.bf16.bf16 {%0, %1, %2, %3, %4, %5, %6, %7, %8, %9, %10, %11, %12, %13, %14, %15}, {%16, %17, %18, %19}, %20, p, 1, 1, 1;\n}\n"
    : "+f"(d[0]), "+f"(d[1]), "+f"(d[2]), "+f"(d[3]), "+f"(d[4]), "+f"(d[5]), "+f"(d[6]), "+f"(d[7]), "+f"(d[8]), "+f"(d[9]), "+f"(d[10]), "+f"(d[11]), "+f"(d[12]), "+f"(d[13]), "+f"(d[14]), "+f"(d[15])
    : "r"(a[0]), "r"(a[1]), "r"(a[2]), "r"(a[3]), "l"(descB), "r"(scaleD));
}

__device__ __forceinline__ uint32_t pack_bf16x2(float lo, float hi) {
  uint32_t r;
  asm("cvt.rn.bf16x2.f32 %0, %1, %2;" : "=r"(r) : "f"(hi), "f"(lo));
  return r;
}
__device__ __forceinline__ float bf_lo(uint32_t p) { return __uint_as_float(p << 16); }
__device__ __forceinline__ float bf_hi(uint32_t p) { return __uint_as_float(p & 0xffff0000u); }
__device__ __forceinline__ float bf16_round(float v) { return __bfloat162float(__float2bfloat16_rn(v)); }
__device__ __forceinline__ float ex2_approx(float x) {
  float r;
  asm("ex2.approx.ftz.f32 %0, %1;" : "=f"(r) : "f"(x));
  return r;
}
__device__ __forceinline__ float rcp_fast(float x) {
  float r;
  asm("rcp.approx.ftz.f32 %0, %1;" : "=f"(r) : "f"(x));
  return r;
}
__device__ __forceinline__ void ldmatrix_x4(uint32_t (&r)[4], uint32_t addr) {
  asm volatile("ldmatrix.sync.aligned.m8n8.x4.shared.b16 {%0,%1,%2,%3}, [%4];"
               : "=r"(r[0]), "=r"(r[1]), "=r"(r[2]), "=r"(r[3])
               : "r"(addr)
               : "memory");
}
__device__ __forceinline__ void stmatrix_x4(uint32_t addr, uint32_t r0, uint32_t r1, uint32_t r2, uint32_t r3) {
  asm volatile("stmatrix.sync.aligned.m8n8.x4.shared.b16 [%0], {%1,%2,%3,%4};" ::"r"(addr), "r"(r0), "r"(r1), "r"(r2),
               "r"(r3));
}
__device__ __forceinline__ uint32_t add_bf16x2(uint32_t a, uint32_t b) {
  uint32_t r;
  asm("add.rn.bf16x2 %0, %1, %2;" : "=r"(r) : "r"(a), "r"(b));
  return r;
}
__device__ __forceinline__ uint4 lds128(uint32_t addr) {
  uint4 v;
  asm volatile("ld.shared.v4.b32 {%0,%1,%2,%3}, [%4];" : "=r"(v.x), "=r"(v.y), "=r"(v.z), "=r"(v.w) : "r"(addr) : "memory");
  return v;
}
__device__ __forceinline__ uint32_t lds32(uint32_t addr) {
  uint32_t v;
  asm volatile("ld.shared.b32 %0, [%1];" : "=r"(v) : "r"(addr) : "memory");
  return v;
}
__device__ __forceinline__ void sts32(uint32_t addr, uint32_t v) {
  asm volatile("st.shared.b32 [%0], %1;" ::"r"(addr), "r"(v) : "memory");
}

__device__ __forceinline__ unsigned ld_acquire_u32(const unsigned* p) {
  unsigned v;
  asm volatile("ld.acquire.gpu.global.u32 %0, [%1];" : "=r"(v) : "l"(p) : "memory");
  return v;
}
__device__ __forceinline__ void red_relaxed_add(unsigned* p, unsigned v) {
  asm volatile("red.relaxed.gpu.global.add.u32 [%0], %1;" ::"l"(p), "r"(v) : "memory");
}
__device__ __forceinline__ void wait_ge(const unsigned* p, unsigned target) {
#pragma unroll 1
  for (uint32_t it = 0; it < (1u << 17); ++it) {
    if ((int)(ld_acquire_u32(p) - target) >= 0) return;
  }
}

template <bool SLOW>
__device__ __forceinline__ void wait_mask(const unsigned* f, int cnt, unsigned target, uint32_t need, uint32_t& seen, int lane) {
  if ((seen & need) == need) return;
  const unsigned* fp = f + (lane & (cnt - 1));
#pragma unroll 1
  for (uint32_t it = 0; it < (1u << 17); ++it) {
    seen = __ballot_sync(0xffffffffu, (int)(ld_acquire_u32(fp) - target) >= 0);
    if ((seen & need) == need) break;
    if (SLOW) __nanosleep(400);
  }
  fence_proxy_async_all();
}
__device__ __forceinline__ float4 ld_rec(const float4* p) {
  float4 v;
  asm volatile("ld.relaxed.gpu.global.v4.f32 {%0,%1,%2,%3}, [%4];" : "=f"(v.x), "=f"(v.y), "=f"(v.z), "=f"(v.w) : "l"(p) : "memory");
  return v;
}
__device__ __forceinline__ void st_rec(float4* p, float a, float b, float c, unsigned tag) {
  asm volatile("st.relaxed.gpu.global.v4.f32 [%0], {%1,%2,%3,%4};" ::"l"(p), "f"(a), "f"(b), "f"(c), "f"(__uint_as_float(tag)) : "memory");
}
template <int N>
__device__ __forceinline__ float4 sum_recs(const float4* p, int stride, unsigned tag) {
  float4 s;
#pragma unroll 1
  for (uint32_t it = 0; it < (1u << 17); ++it) {
    float4 v[N];
#pragma unroll
    for (int t = 0; t < N; t++) v[t] = ld_rec(p + t * stride);
    bool ok = true;
    s = make_float4(0.f, 0.f, 0.f, 0.f);
#pragma unroll
    for (int t = 0; t < N; t++) {
      ok &= __float_as_uint(v[t].w) == tag;
      s.x += v[t].x;
      s.y += v[t].y;
      s.z += v[t].z;
    }
    if (ok) break;
    __nanosleep(200);
  }
  return s;
}

__device__ __forceinline__ int fresh_tid() {
  int t;
  asm volatile("mov.u32 %0, %%tid.x;" : "=r"(t));
  return t;
}
#define PHASE_IDS                                  \
  const int tid_ = fresh_tid();                    \
  const int lane = tid_ & 31, wwarp = __shfl_sync(0xffffffffu, (tid_ >> 5) & 3, 0), tid = tid_ & 127; \
  const int g = lane >> 2, c = lane & 3;           \
  (void)tid; (void)g; (void)c; (void)wwarp;

#define STAMPW(cond, i) do { } while (0)
#define STAMP(cond, i) do { } while (0)
#define GTL(i) do { } while (0)
#define GTLX(c, i) do { } while (0)
#define TGET(v) do { } while (0)
#define TPUT(c, i, v) do { } while (0)

constexpr float SM_C = 0.17677669529663687f * 1.4426950408889634f;

__device__ __forceinline__ void sched_fence(uint32_t never) {
  asm volatile("{\n.reg .pred p;\nSF:\nsetp.ne.u32 p, %0, 0;\n@p nanosleep.u32 32;\n@p bra.uni SF;\n}\n" ::"r"(never) : "memory");
}

template <int G0, int G1>
__device__ __forceinline__ void attn_exp(float (&s)[32]) {
#pragma unroll
  for (int k = 8 * G0; k < 8 * G1; k++) s[k] = ex2_approx(s[k]);
}
#define ASPL 2
template <int MODE, bool NEXT>
__device__ __forceinline__ void attn_unit(float (&s)[32], float (&sn)[32], float (&o)[16], float (&l)[2], bool valid,
                                          uint32_t vdesc, uint32_t qdesc, uint32_t kdesc, uint32_t tri, int wwarp,
                                          uint32_t hbar, uint32_t hpar, uint32_t rel, uint32_t zero) {
  if (MODE == 0) {
    attn_exp<0, ASPL>(s);
  } else if (MODE == 1) {
    attn_exp<0, 1>(s);
    if (wwarp >= 1) attn_exp<1, 2>(s);
  } else {
    attn_exp<3, 4>(s);
    if (wwarp <= 2) attn_exp<2, 3>(s);
  }
  sched_fence(zero);
  if (hbar) mbar_wait(hbar, hpar);
  wgmma_wait<0>();
  if (rel) mbar_arrive(rel);
  if (NEXT) {
    wgmma_fence();
    wgmma_n64_ssz_ta0_tb0(sn, desc_lo(qdesc), desc_lo(kdesc));
    wgmma_n64_ss_ta0_tb0(sn, desc_lo(qdesc + 2), desc_lo(kdesc + 2), 1);
    wgmma_commit();
    sched_fence(zero);
  }
  if (MODE == 0) {
    attn_exp<ASPL, 4>(s);
  } else if (MODE == 1) {
    if (wwarp >= 2) attn_exp<2, 3>(s);
    if (wwarp >= 3) attn_exp<3, 4>(s);
  } else {
    if (wwarp <= 1) attn_exp<1, 2>(s);
    if (wwarp <= 0) attn_exp<0, 1>(s);
  }
  uint32_t p[4][4];
#pragma unroll
  for (int k = 0; k < 16; k++) p[k >> 2][k & 3] = pack_bf16x2(s[2 * k], s[2 * k + 1]);
  if (MODE != 0) {
#pragma unroll
    for (int k = 0; k < 4; k++) {
      const uint32_t in = (MODE == 1 ? k < wwarp : k > wwarp) ? 0xffffffffu : 0u, on = k == wwarp ? 0xffffffffu : in;
      const uint32_t mt = k == wwarp ? (MODE == 1 ? tri : ~tri) : in;
      p[k][0] &= mt;
      p[k][1] &= MODE == 1 ? on : in;
      p[k][2] &= MODE == 1 ? in : on;
      p[k][3] &= mt;
    }
  }
  wgmma_fence();
#pragma unroll
  for (int k = 0; k < 4; k++) wgmma_n32_rs_tb1(o, p[k], desc_lo(vdesc + k * 128), 1);
  wgmma_commit();
#pragma unroll
  for (int r = 0; r < 2; r++) {
    const uint32_t t0 = add_bf16x2(add_bf16x2(p[0][r], p[0][2 + r]), add_bf16x2(p[1][r], p[1][2 + r]));
    const uint32_t t1 = add_bf16x2(add_bf16x2(p[2][r], p[2][2 + r]), add_bf16x2(p[3][r], p[3][2 + r]));
    const float t = (bf_lo(t0) + bf_hi(t0)) + (bf_lo(t1) + bf_hi(t1));
    if (valid) l[r] += t;
  }
  if (NEXT) {
    wgmma_wait<1>();
    reg_fence<32>(sn);
  }
}

__device__ __forceinline__ void attn_a_slow(const uint8_t* __restrict__ kvimg, int L, int gb, int hp,
                                         int hh, int wwarp, int lane) {
  constexpr uint32_t sq = SBASE + OFF_SLOT + 3 * 16384;
  wait_ge(g_flags + F_KV + (gb * 16 + hp) * KSTR, 8u * ((*(volatile unsigned*)(g_flags + F_DONE)) / NCTA) + 2u * L + 2u);
#pragma unroll 1
  for (int t = 0; t < 32; t++) {
    const int row = (t >> 4) * 64 + wwarp * 16 + (t & 15);
    const int qpos = gb * 128 + row;
    const uint32_t qaddr = sq + row * 128;
    float mx = -INFINITY, sum = 0.f, acc = 0.f;
#pragma unroll 1
    for (int pass = 0; pass < 2; pass++) {
#pragma unroll 1
      for (int j = 0; j < 8; j++) {
        const int kp = qpos - (lane + 32 * j);
        const uint8_t* kr = kvimg + ((size_t)((kp >> 7) * 16 + hp) * 2 + ((kp >> 6) & 1)) * 16384 + (kp & 63) * 128;
        float d = -INFINITY;
        if (kp >= 0) {
          d = 0.f;
#pragma unroll 1
          for (int q = 0; q < 4; q++) {
            const uint4 kv = __ldcg(reinterpret_cast<const uint4*>(kr + (((hh * 4 + q) ^ (kp & 7)) << 4)));
            const uint4 qv = lds128(qaddr + (((hh * 4 + q) ^ (row & 7)) << 4));
            const uint32_t kw[4] = {kv.x, kv.y, kv.z, kv.w}, qw[4] = {qv.x, qv.y, qv.z, qv.w};
#pragma unroll
            for (int e = 0; e < 4; e++) d = fmaf(bf_lo(kw[e]), bf_lo(qw[e]), fmaf(bf_hi(kw[e]), bf_hi(qw[e]), d));
          }
        }
        if (pass == 0) {
          mx = fmaxf(mx, d);
        } else {
          const float ev = ex2_approx(d - mx);
          sum += ev;
          const float pv = bf16_round(ev);
#pragma unroll 1
          for (int kk = 0; kk < 32; kk++) {
            const float pk = __shfl_sync(0xffffffffu, pv, kk);
            const int k2 = qpos - (kk + 32 * j);
            if (k2 >= 0) {
              const uint8_t* vr = kvimg + ((size_t)((k2 >> 7) * 16 + hp) * 2 + ((k2 >> 6) & 1)) * 16384 + 8192 + (k2 & 63) * 128;
              const unsigned short vv =
                  __ldcg(reinterpret_cast<const unsigned short*>(vr + (((hh * 4 + (lane >> 3)) ^ (k2 & 7)) << 4) + (lane & 7) * 2));
              acc = fmaf(pk, __uint_as_float((uint32_t)vv << 16), acc);
            }
          }
        }
      }
      if (pass == 0) {
#pragma unroll
        for (int o = 16; o > 0; o >>= 1) mx = fmaxf(mx, __shfl_xor_sync(0xffffffffu, mx, o));
      }
    }
#pragma unroll
    for (int o = 16; o > 0; o >>= 1) sum += __shfl_xor_sync(0xffffffffu, sum, o);
    acc *= rcp_fast(sum);
    const float hi = __shfl_down_sync(0xffffffffu, acc, 1);
    __syncwarp();
    if ((lane & 1) == 0) sts32(qaddr + (((hh * 4 + (lane >> 3)) ^ (row & 7)) << 4) + (lane & 7) * 2, pack_bf16x2(acc, hi));
    __syncwarp();
  }
}

__device__ __forceinline__ void store_o(const float (&o)[16], const float (&inv)[2], uint32_t rowaddr, int hh, int lane) {
  const int mat = lane >> 3, r7 = lane & 7;
#pragma unroll
  for (int jp = 0; jp < 2; jp++)
    stmatrix_x4(rowaddr + (((hh * 4 + 2 * jp + (mat >> 1)) ^ r7) << 4),
                pack_bf16x2(o[8 * jp] * inv[0], o[8 * jp + 1] * inv[0]),
                pack_bf16x2(o[8 * jp + 2] * inv[1], o[8 * jp + 3] * inv[1]),
                pack_bf16x2(o[8 * jp + 4] * inv[0], o[8 * jp + 5] * inv[0]),
                pack_bf16x2(o[8 * jp + 6] * inv[1], o[8 * jp + 7] * inv[1]));
}

__device__ __forceinline__ void attention_a(int HH, int L, int gb, int hp, uint32_t par0, uint32_t parA, int wwarp, int lane,
                                            uint32_t zero) {
  constexpr uint32_t bars = SBASE + OFF_BAR;
  const uint32_t dslot = ((SBASE + OFF_SLOT) >> 4) + 0x10000u + HH * 4;
  const uint32_t dq = dslot + 3 * 1024;
  float sa[32], sb[32], o[2][16], l[2][2];
  auto dch = [&](int n) { return dslot + 1024u * (n % 3 == 0 ? 1 : (n % 3 == 1 ? 0 : 2)); };
  wgmma_fence();
  wgmma_n64_ssz_ta0_tb0(sa, desc_lo(dq + 512), desc_lo(dch(0)));
  wgmma_n64_ss_ta0_tb0(sa, desc_lo(dq + 512 + 2), desc_lo(dch(0) + 2), 1);
  wgmma_commit();
#pragma unroll
  for (int h = 0; h < 2; h++) {
#pragma unroll
    for (int i = 0; i < 16; i++) o[h][i] = 0.f;
    l[h][0] = l[h][1] = 0.f;
  }
  const int dg = (lane >> 2) - 2 * (lane & 3);
  const uint32_t tri = (dg >= 0 ? 0xffffu : 0u) | (dg >= 1 ? 0xffff0000u : 0u);
  const int nmax = 2 * gb + 1;
  wgmma_wait<0>();
  reg_fence<32>(sa);
#define ATT_STEP(i, MODE)                                                                                            \
  attn_unit<MODE, true>(sa, sb, o[1], l[1], i <= nmax, dch(i) + 512, dq, dch(i + 1), tri, wwarp,                     \
                        i >= 1 ? bars + 8u * (B_HALO + i - 1) : 0u, i == 1 ? par0 : parA, 0u, zero);                 \
  attn_unit<MODE, (i < 4)>(sb, sa, o[0], l[0], i + 1 <= nmax, dch(i + 1) + 512, dq + 512, dch(i + 1), tri, wwarp, 0u, \
                           0u, i < 3 && lane == 0 ? bars + 8u * (B_REL + i) : 0u, zero);
  ATT_STEP(0, 1)
  ATT_STEP(1, 0)
  ATT_STEP(2, 0)
  ATT_STEP(3, 0)
  ATT_STEP(4, 2)
#undef ATT_STEP
  wgmma_wait<0>();
  const uint32_t ra = SBASE + OFF_SLOT + 3 * 16384 + (wwarp * 16 + ((lane >> 3) & 1) * 8 + (lane & 7)) * 128;
  reg_fence<16>(o[0]);
  reg_fence<16>(o[1]);
  float inv[2][2];
  bool bad = false;
#pragma unroll
  for (int h = 0; h < 2; h++)
#pragma unroll
    for (int r = 0; r < 2; r++) {
      float v = l[h][r];
      v += __shfl_xor_sync(0xffffffffu, v, 1);
      v += __shfl_xor_sync(0xffffffffu, v, 2);
      bad |= !(v <= 1.152921504606846976e18f && v >= 8.673617379884035e-19f);
      inv[h][r] = rcp_fast(v);
    }
  if (HH == 0) GTL(45);
  if (__any_sync(0xffffffffu, bad)) {
    attn_a_slow(g_kvA[L >> 1][0][0][0], L, gb, hp, HH, wwarp, lane);
  } else {
    store_o(o[0], inv[0], ra, HH, lane);
    store_o(o[1], inv[1], ra + 8192, HH, lane);
  }
}

constexpr uint32_t KB_ROW0 = SBASE + OFF_SLOT + 2048, VB_ROW0 = SBASE + OFF_SLOT + 24576 + 2048;

__device__ __forceinline__ void attnB_soft(const float (&s)[40], int wwarp, int D, bool edge, bool odd,
                                           uint32_t (&p)[5][4], float (&sum)[2]) {
  float z[2][3];
#define GATHER_(W)                                                                                  \
  _Pragma("unroll") for (int r = 0; r < 2; r++) _Pragma("unroll") for (int t = 0; t < 3; t++)       \
      z[r][t] = odd ? s[4 * (2 * W + r + t) + 2 * r + 1] : s[4 * (2 * W + r + t) + 2 * r];
  if (wwarp < 2) {
    if (wwarp == 0) { GATHER_(0) } else { GATHER_(1) }
  } else {
    if (wwarp == 2) { GATHER_(2) } else { GATHER_(3) }
  }
#undef GATHER_
  float y[2];
  y[0] = D >= 2 ? z[0][0] : z[0][2];
  y[1] = D >= 2 ? z[1][0] : z[1][2];
  if (edge) {
    z[0][1] = -INFINITY;
    if (D >= 2) y[0] = y[1] = -INFINITY;
  }
  float m0 = fmaxf(z[0][1], y[0]), m1 = fmaxf(z[1][1], y[1]);
  m0 = fmaxf(m0, __shfl_xor_sync(0xffffffffu, m0, 1));
  m1 = fmaxf(m1, __shfl_xor_sync(0xffffffffu, m1, 1));
  m0 = fmaxf(m0, __shfl_xor_sync(0xffffffffu, m0, 2));
  m1 = fmaxf(m1, __shfl_xor_sync(0xffffffffu, m1, 2));
  const float e00 = ex2_approx(z[0][1] - m0), e01 = ex2_approx(y[0] - m0);
  const float e10 = ex2_approx(z[1][1] - m1), e11 = ex2_approx(y[1] - m1);
  sum[0] = e00 + e01;
  sum[1] = e10 + e11;
  const int sh = odd ? 16 : 0;
  const uint32_t a0 = pack_bf16x2(e00, 0.f) << sh, a1 = pack_bf16x2(e10, 0.f) << sh;
  const uint32_t b0 = pack_bf16x2(e01, 0.f) << sh, b1 = pack_bf16x2(e11, 0.f) << sh;
  const int kb = wwarp + (D >= 2 ? 0 : 1);
#pragma unroll
  for (int k = 0; k < 5; k++) {
    p[k][0] = k == kb ? b0 : 0u;
    p[k][1] = k == wwarp + 1 ? a1 : 0u;
    p[k][2] = k == wwarp ? a0 : 0u;
    p[k][3] = k == kb ? b1 : 0u;
#pragma unroll
    for (int q = 0; q < 4; q++) asm volatile("" : "+r"(p[k][q]));
  }
}

__device__ __forceinline__ void attnB_s(float (&s)[40], int HH, int h) {
  constexpr uint32_t sq = SBASE + OFF_SLOT + 3 * 16384;
#pragma unroll
  for (int ks = 0; ks < 2; ks++)
    wgmma_n80_ss_ta0_tb0(s, make_desc(sq + h * 8192 + HH * 64 + ks * 32, 16),
                         make_desc(KB_ROW0 + h * 8192 - 2048 + HH * 64 + ks * 32, 16), ks);
}
__device__ __forceinline__ void attnB_pv(float (&o)[16], const uint32_t (&p)[5][4], int HH, int h) {
#pragma unroll
  for (int k = 0; k < 5; k++)
    wgmma_n32_rs_tb1(o, p[k], make_desc(VB_ROW0 + h * 8192 - 2048 + k * 2048 + HH * 64, 16), k);
}

__device__ __forceinline__ void attention_b(int HH, int gb, uint32_t par0, int wwarp, int lane) {
  constexpr uint32_t bars = SBASE + OFF_BAR, sq = SBASE + OFF_SLOT + 3 * 16384;
  float s[40];
  reg_define<40>(s);
  wgmma_fence();
  attnB_s(s, HH, 1);
  wgmma_commit();
  const int g = lane >> 2;
  const bool odd = g & 1;
  const int D = 2 * (lane & 3) + (g & 1) - g;
  const uint32_t ra = sq + (wwarp * 16 + ((lane >> 3) & 1) * 8 + (lane & 7)) * 128;
  wgmma_wait<0>();
  reg_fence<40>(s);
#pragma unroll 1
  for (int h = 1; h >= 0; h--) {
    float o[16], inv[2];
    uint32_t p[5][4];
    reg_define<16>(o);
    attnB_soft(s, wwarp, D, h == 0 && gb == 0 && wwarp == 0, odd, p, inv);
    if (h == 1) {
      mbar_wait(bars + 8u * B_HALO, par0);
      wgmma_fence();
      attnB_s(s, HH, 0);
    }
    wgmma_fence();
    attnB_pv(o, p, HH, h);
    wgmma_commit();
#pragma unroll
    for (int r = 0; r < 2; r++) {
      inv[r] += __shfl_xor_sync(0xffffffffu, inv[r], 1);
      inv[r] += __shfl_xor_sync(0xffffffffu, inv[r], 2);
      inv[r] = rcp_fast(inv[r]);
    }
    wgmma_wait<0>();
    reg_fence<40>(s);
    reg_fence<16>(o);
    store_o(o, inv, ra + h * 8192, HH, lane);
  }
}

#define KTQM 0
#define TRICKLE 300
#define CSPF 4
#define QTURN 2
struct Params {
  CUtensorMap xq[2], xr[3], o, wqkv[2], wo[2];
  const __nv_bfloat16* in_x;
  const __nv_bfloat16* wqkv_p[2];
  const __nv_bfloat16* wo_p[2];
  __nv_bfloat16* out;
  uint32_t zero;
};

__device__ __forceinline__ void colsum_part(const CUtensorMap* wmap, int ty, int qr, int hp) {
  constexpr uint32_t bars = SBASE + OFF_BAR, slots = SBASE + OFF_SLOT;
  PHASE_IDS
  const unsigned ep1 = (*(volatile unsigned*)(g_flags + F_DONE)) / NCTA + 1u;
  if (wwarp == 0 && elect_one()) {
    mbar_expect_tx(bars + 8u * B_CS, 6 * UNIT);
#pragma unroll 1
    for (int j = 0; j < 2; j++) {
      if (ty == 0) mbar_pace(bars + 8u * (B_EMPTY + 1 + 3 * j), 0);
      else __nanosleep(1000);
      tma_load_3d(slots + j * 3 * UNIT, wmap, bars + 8u * B_CS, hp * 64, qr * 128 + j * 64, 0);
    }
  }
  mbar_wait(bars + 8u * B_CS, ty);
  const uint32_t src = slots + (tid >> 3) * 128 + (((tid & 7) ^ ((tid >> 3) & 7)) << 4);
#pragma unroll 1
  for (int p = 0; p < 3; p++) {
    float s[8];
#pragma unroll
    for (int e = 0; e < 8; e++) s[e] = 0.f;
#pragma unroll
    for (int j = 0; j < 8; j++) {
      const uint4 v = lds128(src + p * UNIT + (j >> 2) * 3 * UNIT + (j & 3) * 2048);
      const uint32_t x[4] = {v.x, v.y, v.z, v.w};
#pragma unroll
      for (int e = 0; e < 4; e++) {
        s[2 * e] += bf_lo(x[e]);
        s[2 * e + 1] += bf_hi(x[e]);
      }
    }
#pragma unroll
    for (int st = 0; st < 2; st++) {
      const bool up = (lane >> (st + 3)) & 1;
#pragma unroll
      for (int e = 0; e < (4 >> st); e++) {
        const float keep = up ? s[e + (4 >> st)] : s[e], give = up ? s[e] : s[e + (4 >> st)];
        s[e] = keep + __shfl_xor_sync(0xffffffffu, give, 8 << st);
      }
    }
    const uint32_t dst = slots + 6 * UNIT + ((wwarp * 3 + p) * 64 + (lane & 7) * 8 + ((lane >> 3) & 1) * 4 + (lane >> 4) * 2) * 4;
    sts32(dst, __float_as_uint(s[0]));
    sts32(dst + 4, __float_as_uint(s[1]));
  }
  named_bar_sync(6, 128);
  if (tid < 64) {
    float r[3] = {0.f, 0.f, 0.f};
#pragma unroll
    for (int e = 0; e < 12; e++) r[e % 3] += __uint_as_float(lds32(slots + 6 * UNIT + (e * 64 + tid) * 4));
    st_rec(&g_cs[ty][hp][qr][tid], r[0], r[1], r[2], ep1);
  }
  named_bar_sync(6, 128);
}

__device__ __forceinline__ int cs_pos(int col) { return (col & ~15) + ((col & 7) >> 1) * 4 + ((col >> 3) & 1) * 2 + (col & 1); }

__device__ __forceinline__ uint32_t ln_params(float s1, float s2) {
  const float mean = s1 * (1.0f / DM);
  const float var = fmaxf(fmaf(-mean, mean, s2 * (1.0f / DM)), 0.f);
  float sd;
  asm("sqrt.approx.f32 %0, %1;" : "=f"(sd) : "f"(bf16_round(bf16_round(var) + 1e-5f)));
  return pack_bf16x2(mean, sd);
}

__host__ __device__ constexpr int w_ua(int kt) { return (kt == 6 ? 20 : 3 * kt) % 20; }
__host__ __device__ constexpr int w_ub(int kt) { return (kt == 6 ? 18 : 3 * kt + 1) % 20; }

constexpr int NSEG = 20;
__host__ __device__ constexpr int SEGQ(int ch, int L, int k0, int k1) { return ch | (L << 2) | ((k0 / 4) << 4) | ((k1 / 4 - 1) << 6); }
__host__ __device__ constexpr int SEGW(int ch, int L) { return ch | 2 | (L << 2); }
__host__ __device__ constexpr unsigned long long pack8(int a, int b, int c, int d, int e, int f, int g, int h) {
  return (unsigned long long)a | ((unsigned long long)b << 8) | ((unsigned long long)c << 16) | ((unsigned long long)d << 24) |
         ((unsigned long long)e << 32) | ((unsigned long long)f << 40) | ((unsigned long long)g << 48) | ((unsigned long long)h << 56);
}
#define SP2 12
#define SP3 12
#define SP4 12
#define SP6 12
__device__ __forceinline__ int seg_code(int sg) {
  constexpr unsigned long long T0 = pack8(SEGQ(0, 0, 0, 16), SEGQ(1, 0, 0, 16), SEGW(0, 0), SEGQ(0, 1, 0, SP2), SEGW(1, 0),
                                          SEGQ(0, 1, SP2, 16), SEGQ(1, 1, 0, SP3), SEGW(0, 1));
  constexpr unsigned long long T1 = pack8(SEGQ(1, 1, SP3, 16), SEGQ(0, 2, 0, SP4), SEGW(1, 1), SEGQ(0, 2, SP4, 16),
                                          SEGQ(1, 2, 0, 16), SEGW(0, 2), SEGQ(0, 3, 0, SP6), SEGW(1, 2));
  constexpr unsigned long long T2 = pack8(SEGQ(0, 3, SP6, 16), SEGQ(1, 3, 0, 16), SEGW(0, 3), SEGW(1, 3), 0, 0, 0, 0);
  return (int)(((sg < 8 ? T0 : (sg < 16 ? T1 : T2)) >> (8 * (sg & 7))) & 255ull);
}
__device__ __forceinline__ int q_first(int inst) { return (int)((pack8(0, 16, 48, 80, 112, 144, 176, 208) >> (8 * inst)) & 255ull); }
__device__ __forceinline__ int w_first(int inst) {
  return (int)((pack8(32, 48 + SP2, 80 + SP3, 112 + SP4, 160, 176 + SP6, 224, 240) >> (8 * inst)) & 255ull);
}
#define PREMASK 0x2Cu
#define PRE0 3
#define PRESH 2
__host__ __device__ constexpr int pre_idx(int kt) {
  const int d = kt - PRE0;
  return (d >= 0 && (d & ((1 << PRESH) - 1)) == 0 && (d >> PRESH) < 4) ? d >> PRESH : -1;
}
__device__ __forceinline__ bool w_pre(int inst) { return (PREMASK >> inst) & 1u; }
__device__ __forceinline__ int q_split(int inst) { return (int)(((0x40400044u | ((SP2 / 4) << 8) | ((SP3 / 4) << 12) | ((SP4 / 4) << 16) | ((SP6 / 4) << 24)) >> (4 * inst)) & 15u); }

__global__ void __launch_bounds__(512, 1) fused_kernel(const __grid_constant__ Params P) {
  extern __shared__ __align__(1024) uint8_t smem_raw[];
  constexpr uint32_t base = SBASE, bars = base + OFF_BAR, slots = base + OFF_SLOT;
  if (smem_u32(smem_raw) != base) __trap();
  const int warp = __shfl_sync(0xffffffffu, threadIdx.x >> 5, 0), lane = threadIdx.x & 31;
  const int b = blockIdx.x;
#define QS 0
#define WS 1
  const int qr = ((b & ((8 << QS) - 1)) >> QS) ^ (((b >> (3 + QS)) & 1) * 7);
  const int hp = ((b >> (3 + QS)) << QS) + (b & ((1 << QS) - 1));
  const int rt = ((b & ((16 << WS) - 1)) >> WS) ^ (((b >> (4 + WS)) & 1) * 15);
  const int ct = ((b >> (4 + WS)) << WS) + (b & ((1 << WS) - 1));

  if (warp == 12) {
    if (elect_one()) {
#pragma unroll
      for (int s = 0; s < 8; s++) {
        mbar_init(bars + 8u * (B_FULL + s), 2);
        mbar_init(bars + 8u * (B_EMPTY + s), 4);
      }
      mbar_init(bars + 8u * B_GO, 1);
      fence_barrier_init();
    }
    __syncwarp();
    named_bar_arrive(0, 512);
  }
  if (threadIdx.x == 0) {
    mbar_init(bars + 8u * B_PREP, 1);
    mbar_init(bars + 8u * (B_PREP + 1), 1);
    for (int s = 0; s < 4; s++) mbar_init(bars + 8u * (B_HALO + s), 1);
    for (int s = 0; s < 3; s++) mbar_init(bars + 8u * (B_REL + s), 8);
    mbar_init(bars + 8u * B_AFREE, 2);
    mbar_init(bars + 8u * B_TURN, 4);
    mbar_init(bars + 8u * (B_TURN + 1), 4);
    mbar_init(bars + 8u * B_CS, 1);
    mbar_init(bars + 8u * B_PRE, 1);
    mbar_init(bars + 8u * B_RESF, 1);
    mbar_init(bars + 8u * B_RESE, 4);
    mbar_init(bars + 8u * B_CSD, 4);
    mbar_init(bars + 8u * B_XRDY, 1);
    mbar_init(bars + 8u * (B_XRDY + 1), 1);
    fence_barrier_init();
  }
  if (warp != 12) named_bar_sync(0, 512);

  if (warp >= 12) {
    setmaxnreg_dec<32>();
    if (warp <= 13) {
      const bool act = warp == 13;
      uint32_t q = 4, dl = 0;
      bool prevw = false;
      unsigned ep1 = 0;
      if (act) {
        mbar_wait(bars + 8u * B_GO, 0);
        ep1 = __shfl_sync(0xffffffffu, (*(volatile unsigned*)(g_flags + F_DONE)) / NCTA + 1u, 0);
      } else {
#pragma unroll 1
        for (int s = 0; s < 16; s++) {
          const uint32_t fb = bars + 8u * (B_FULL + (s & 7)), sa = base + (s & 3) * 5 * UNIT;
          if (s >= 4) mbar_wait(bars + 8u * (B_EMPTY + ((s - 4) & 7)), ((s - 4) >> 3) & 1);
          if (elect_one()) {
            mbar_expect_tx(fb, 5 * UNIT);
            mbar_arrive(fb);
            tma_load_3d(sa, &P.xq[0], fb, 0, qr * 128, s);
            tma_load_3d(sa + 2 * UNIT, &P.wqkv[0], fb, hp * 64, s * 64, 0);
          }
        }
        if (elect_one()) mbar_arrive(bars + 8u * B_GO);
      }
      auto rbar = [&](int b0, int c) { return bars + 8u * b0 + ((8u * (c & 7)) ^ ((q & 1u) << 5)); };
      auto rpar = [&](int c) { return ((q + (c >> 2)) >> 1) & 1u; };
#pragma unroll 1
      for (int sg = 1; sg < NSEG; sg++) {
        const int code = seg_code(sg);
        const int L = (code >> 2) & 3, ch = code & 1;
        uint32_t seen = act ? 0u : 0xFFFFu;
        if ((code & 2) == 0) {
          const CUtensorMap* map = act ? &P.xq[L == 0 ? 0 : 1] : &P.wqkv[L & 1];
          if (act && (L == 0 || __any_sync(0xffffffffu, mbar_test(bars + 8u * (B_XRDY + ch), (L & 1) ^ 1)))) {
            seen = 0xFFFFu;
            fence_proxy_async_all();
          }
          const int k1 = ((code >> 4) & 12) + 4;
#pragma unroll 1
          for (int k4 = (code >> 2) & 12; k4 < k1; k4 += 4, q++) {
#pragma unroll
            for (int ks = 0; ks < 4; ks++) {
              const int kt = k4 + ks;
              if ((ks & 1) == 0)
                wait_mask<false>(g_flags + F_X + (ch * 8 + qr) * XSTR, 8, 6u * ep1 - 6u + 2u * L, 1u << (kt >> 1), seen, lane);
              if (ks == 0 && prevw) mbar_wait(rbar(B_EMPTY, -5), rpar(-5));
              else mbar_wait(rbar(B_EMPTY, ks - 4), rpar(-4));
              if (ks == 3 && prevw && !act) mbar_wait(bars + 8u * B_RESE, dl == 0 ? 1u : 0u);
              if (elect_one()) {
                mbar_expect_tx(rbar(B_FULL, ks), act ? 2 * UNIT : 3 * UNIT);
                tma_load_3d(base + ks * 5 * UNIT + (act ? 0 : 2 * UNIT) + (ks < 2 ? dl : 0u - dl), map, rbar(B_FULL, ks),
                            act ? 0 : hp * 64, act ? ch * 1024 + qr * 128 : kt * 64, act ? kt : 0);
              }
            }
            prevw = false;
          }
        } else {
          const CUtensorMap* map = act ? &P.o : &P.wo[L & 1];
          const bool pre = !act && w_pre(2 * L + ch);
          const int m0 = ch * 1024 + rt * 64;
#pragma unroll
          for (int kt = 0; kt < 16; kt++) {
            if (kt == 0 || kt == 1 || kt == 4 || kt == 8)
              wait_mask<false>(g_flags + F_O + (ch * 16 + rt) * OSTR, 16, 4u * ep1 - 3u + L,
                               kt == 0 ? 1u : (kt == 1 ? 0xEu : (kt == 4 ? 0xF0u : 0xFF00u)), seen, lane);
            if (kt < 4 && !prevw) mbar_wait(rbar(B_EMPTY, kt - 4 - (kt >> 1)), rpar(-4));
            else mbar_wait(rbar(B_EMPTY, kt - 6), rpar(kt - 6));
            if (kt == 6 && prevw && !act) mbar_wait(bars + 8u * B_RESE, dl == 0 ? 1u : 0u);
            if (elect_one()) {
              if (pre_idx(kt) >= 0 && pre) {
                mbar_arrive(rbar(B_FULL, kt));
              } else {
                mbar_expect_tx(rbar(B_FULL, kt), act ? UNIT : 2 * UNIT);
                const uint32_t da = base + w_ua(kt) * UNIT + (w_ua(kt) < 10 ? dl : 0u - dl);
                const uint32_t db = base + w_ub(kt) * UNIT + (w_ub(kt) < 10 ? dl : 0u - dl);
                tma_load_3d(act ? da : db, map, rbar(B_FULL, kt), 0, act ? m0 : kt * 64, act ? kt : ct * 2);
              }
            }
          }
          if (act && elect_one()) {
            mbar_expect_tx(bars + 8u * B_RESF, 2 * UNIT);
            tma_load_3d(base + 8 * UNIT + dl, &P.xr[L == 0 ? 0 : 1], bars + 8u * B_RESF, 0, m0, ct * 2);
          }
          q += 4;
          dl ^= 10u * UNIT;
          prevw = true;
        }
      }
    } else if (warp == 14) {
      const unsigned ep1 = (*(volatile unsigned*)(g_flags + F_DONE)) / NCTA + 1u;
#pragma unroll 1
      for (int inst = 0; inst < 8; inst++) {
        const int L = inst >> 1, ch = inst & 1, gb = ch * 8 + qr;
        unsigned* kvf = g_flags + F_KV;
        const unsigned kvt = 8u * ep1 - 6u + 2u * L;
        named_bar_sync(3, 160);
        if (elect_one()) {
          if ((L & 1) == 0) {
            bulk_store(g_kvA[L >> 1][gb][hp][1], slots + 16384, 16384);
          } else {
            bulk_store(g_kvB[L >> 1][gb][hp], KB_ROW0 + 112 * 128, 2048);
            bulk_store(g_kvB[L >> 1][gb][hp] + 2048, VB_ROW0 + 112 * 128, 2048);
          }
          bulk_commit();
          bulk_wait0();
          fence_proxy_async_all();
          red_relaxed_add(kvf + (gb * 16 + hp) * KSTR, (L & 1) + 1u);
        }
        __syncwarp();
        if (L & 1) named_bar_arrive(7, 160);
        else named_bar_sync(7, 160);
        if (elect_one()) {
          if ((L & 1) == 0) {
            bulk_store(g_kvA[L >> 1][gb][hp][0], slots, 16384);
            bulk_commit();
            bulk_wait0();
            fence_proxy_async_all();
            red_relaxed_add(kvf + (gb * 16 + hp) * KSTR, 1u);
          }
          if (gb >= 1) {
            wait_ge(kvf + ((gb - 1) * 16 + hp) * KSTR, kvt - 1u);
            fence_proxy_async_all();
          }
          if ((L & 1) == 0) {
            const uint32_t parA = ((L >> 1) * 2 + ch) & 1;
            const uint8_t* s1 = gb >= 1 ? g_kvA[L >> 1][gb - 1][hp][0] : g_zero;
            mbar_expect_tx(bars + 8u * B_HALO, 16384);
            bulk_load(slots + 2 * 16384, gb >= 1 ? s1 + 16384 : s1, 16384, bars + 8u * B_HALO);
            if (gb >= 1) {
              wait_ge(kvf + ((gb - 1) * 16 + hp) * KSTR, kvt);
              fence_proxy_async_all();
            }
            mbar_wait_lazy<100>(bars + 8u * B_REL, parA);
            mbar_expect_tx(bars + 8u * (B_HALO + 1), 16384);
            bulk_load(slots + 16384, s1, 16384, bars + 8u * (B_HALO + 1));
            if (gb >= 2) {
              wait_ge(kvf + ((gb - 2) * 16 + hp) * KSTR, kvt);
              fence_proxy_async_all();
            }
            const uint8_t* s2 = gb >= 2 ? g_kvA[L >> 1][gb - 2][hp][0] : g_zero;
            mbar_wait_lazy<100>(bars + 8u * (B_REL + 1), parA);
            mbar_expect_tx(bars + 8u * (B_HALO + 2), 16384);
            bulk_load(slots, gb >= 2 ? s2 + 16384 : s2, 16384, bars + 8u * (B_HALO + 2));
            mbar_wait_lazy<100>(bars + 8u * (B_REL + 2), parA);
            mbar_expect_tx(bars + 8u * (B_HALO + 3), 16384);
            bulk_load(slots + 2 * 16384, s2, 16384, bars + 8u * (B_HALO + 3));
          } else {
            const uint8_t* s1 = gb >= 1 ? g_kvB[L >> 1][gb - 1][hp] : g_zero;
            mbar_expect_tx(bars + 8u * B_HALO, 4096);
            bulk_load(KB_ROW0 - 2048, s1, 2048, bars + 8u * B_HALO);
            bulk_load(VB_ROW0 - 2048, s1 + 2048, 2048, bars + 8u * B_HALO);
          }
          if (w_pre(inst)) {
            mbar_wait(bars + 8u * B_AFREE, (inst & 1) ^ 1);
            if (inst == 1) mbar_wait(bars + 8u * B_CSD, 0);
            mbar_expect_tx(bars + 8u * B_PRE, 8 * UNIT);
#pragma unroll 1
            for (int j = 0; j < 4; j++) {
              tma_load_3d(slots + j * 2 * UNIT, &P.wo[L & 1], bars + 8u * B_PRE, 0, (PRE0 + (j << PRESH)) * 64, ct * 2);
              __nanosleep(200);
            }
          }
        }
        __syncwarp();
      }
    } else {
      const unsigned ep1 = (*(volatile unsigned*)(g_flags + F_DONE)) / NCTA + 1u;
      mbar_wait(bars + 8u * B_GO, 0);
#pragma unroll 1
      for (int i = 0; i < 20; i++) {
        const char* src = i < 4 ? reinterpret_cast<const char*>(P.wo_p[0]) + (size_t)b * 16384 + i * 4096
                                : (i < 16 ? reinterpret_cast<const char*>(P.wqkv_p[1]) + (size_t)b * 49152 + (i - 4) * 4096
                                          : reinterpret_cast<const char*>(P.wo_p[1]) + (size_t)b * 16384 + (i - 16) * 4096);
        asm volatile("prefetch.global.L2 [%0];" ::"l"(src + lane * 128));
        __nanosleep(TRICKLE);
      }
#pragma unroll 1
      for (int inst = 2; inst < 8; inst++) {
        const int L = inst >> 1, ch = inst & 1, gb = ch * 8 + qr;
        uint32_t seen = 0;
        wait_mask<true>(g_flags + F_X + gb * XSTR, 8, 6u * ep1 - 6u + 2u * L, 0xFFu, seen, lane);
        if (lane == 0) mbar_arrive(bars + 8u * (B_XRDY + ch));
#pragma unroll 1
        for (int h = 0; h < 4; h++) {
          const float4* sp = &g_stats[L][0][gb * 128 + h * 32 + lane];
          const float4 s0 = sum_recs<4>(sp, S_LEN, ep1), s1 = sum_recs<4>(sp + 4 * S_LEN, S_LEN, ep1);
          sts32(base + OFF_RS + (ch * 128 + h * 32 + lane) * 4, ln_params(s0.x + s1.x, s0.y + s1.y));
        }
        if (inst == 2) {
          mbar_wait(bars + 8u * B_CSD, 0);
#pragma unroll 1
          for (int hf = 0; hf < 2; hf++) {
            const float4* cp = &g_cs[1][hp][0][hf * 32 + lane];
            const float4 s0 = sum_recs<4>(cp, 64, ep1), s1 = sum_recs<4>(cp + 4 * 64, 64, ep1);
            const uint32_t ca = base + OFF_CS + (192 + cs_pos(hf * 32 + lane)) * 4;
            sts32(ca, __float_as_uint(s0.x + s1.x));
            sts32(ca + 256, __float_as_uint(s0.y + s1.y));
            sts32(ca + 512, __float_as_uint(s0.z + s1.z));
          }
        }
        __syncwarp();
        if (lane == 0) mbar_arrive(bars + 8u * (B_PREP + ch));
      }
    }
  } else {
    const bool asst = warp >= 8;
    const bool lane0 = lane == 0;
    uint32_t tpar = 0;
    GTL(0);
    if (asst) {
      colsum_part(&P.wqkv[0], 0, qr, hp);
      if ((threadIdx.x & 127) < 2) mbar_arrive(bars + 8u * B_AFREE);
    } else if (warp >= 4) {
      PHASE_IDS
      {
        const unsigned ep1 = (*(volatile unsigned*)(g_flags + F_DONE)) / NCTA + 1u;
        const int row = b * 16 + (tid >> 3);
        const uint4* src = reinterpret_cast<const uint4*>(P.in_x + (size_t)row * DM) + (tid & 7);
        float s1 = 0.f, s2 = 0.f;
#pragma unroll 1
        for (int k = 0; k < 4; k++) {
          mbar_pace(bars + 8u * (B_EMPTY + 2 * k), 0);
          uint4 v[4];
#pragma unroll
          for (int j = 0; j < 4; j++) v[j] = __ldg(src + (k * 4 + j) * 8);
#pragma unroll
          for (int j = 0; j < 4; j++) {
            const uint32_t w[4] = {v[j].x, v[j].y, v[j].z, v[j].w};
#pragma unroll
            for (int e = 0; e < 4; e++) {
              const float x0 = bf_lo(w[e]), x1 = bf_hi(w[e]);
              s1 += x0 + x1;
              s2 = fmaf(x0, x0, fmaf(x1, x1, s2));
            }
          }
        }
#pragma unroll
        for (int o = 1; o < 8; o <<= 1) {
          s1 += __shfl_xor_sync(0xffffffffu, s1, o);
          s2 += __shfl_xor_sync(0xffffffffu, s2, o);
        }
        if ((tid & 7) == 0) st_rec(&g_stats[0][0][row], s1, s2, 0.f, ep1);
        if (tid == 0) sts32(base + OFF_EPOCH, ep1);
        if (tid < 64) {
          const float4 s0 = sum_recs<8>(&g_cs[0][hp][0][tid], 64, ep1);
          sts32(base + OFF_CS + cs_pos(tid) * 4, __float_as_uint(s0.x));
          sts32(base + OFF_CS + cs_pos(tid) * 4 + 256, __float_as_uint(s0.y));
          sts32(base + OFF_CS + cs_pos(tid) * 4 + 512, __float_as_uint(s0.z));
        }
#pragma unroll 1
        for (int cc = 0; cc < 2; cc++) {
          const float4 s0 = sum_recs<1>(&g_stats[0][0][(cc * 8 + qr) * 128 + tid], 0, ep1);
          sts32(base + OFF_RS + (cc * 128 + tid) * 4, ln_params(s0.x, s0.y));
        }
        named_bar_sync(2, 128);
        if (tid < 2) mbar_arrive(bars + 8u * (B_PREP + tid));
      }
    }
#pragma unroll 1
    for (int inst = asst ? 0 : warp >> 2; inst < 8; inst += asst ? 1 : 2) {
      const int L = inst >> 1, ch = inst & 1, gb = ch * 8 + qr;
      if (asst) {
        setmaxnreg_dec<24>();
        named_bar_sync(4, 256);
        setmaxnreg_inc<128>();
      } else {
      setmaxnreg_inc<224>();
      {
        float acc[2][96];
        const int ksp = q_split(inst);
        int n = q_first(inst);
        uint32_t dlt = (ch == 0 && L > 0) ? 10u * (UNIT >> 4) : 0u;
        if (inst != 0 && inst != 2 && inst != 6) {
          mbar_wait_lazy<100>(bars + 8u * (B_TURN + ch), tpar);
          tpar ^= 1u;
        }
        if (L == 3) GTL(37);
        mbar_wait(bars + 8u * (B_FULL + (n & 7)), (n >> 3) & 1);
        GTL(1 + L * 8);
        {
          const uint32_t da = (base >> 4) + 0x10000u + dlt;
          const uint64_t db = desc_lo(da - 0x10000u + ((UNIT >> 4) << 16) + 2 * (UNIT >> 4));
          wgmma_fence();
          wgmma_n192_ssz_ta0_tb1(acc[0], desc_lo(da), db);
          wgmma_commit();
          wgmma_n192_ssz_ta0_tb1(acc[1], desc_lo(da + (UNIT >> 4)), db);
          wgmma_commit();
        }
#pragma unroll 1
        for (int k4 = 0; k4 < 4; k4++) {
          const bool brk = k4 + 1 == ksp && k4 < 3;
#pragma unroll
          for (int ks = 0; ks < 4; ks++, n++) {
            STAMP(inst == KSQ, k4 * 4 + ks);
            const uint32_t da = ((base + ks * 5 * UNIT) >> 4) + 0x10000u + (ks < 2 ? dlt : 0u - dlt);
            const uint32_t dbb = da - 0x10000u + ((UNIT >> 4) << 16) + 2 * (UNIT >> 4);
#pragma unroll
            for (int k16 = 0; k16 < 4; k16++) {
              if (ks == 0 && k16 == 0 && k4 == 0) continue;
              const uint64_t db = desc_lo(dbb + k16 * 128);
              wgmma_fence();
              wgmma_n192_ss_ta0_tb1(acc[0], desc_lo(da + k16 * 2), db, 1);
              wgmma_commit();
              wgmma_wait<1>();
              if (k16 == 0 && lane0 && (ks != 0 || k4 != ksp)) mbar_arrive(bars + 8u * (B_EMPTY + ((n - 1) & 7)));
              wgmma_fence();
              wgmma_n192_ss_ta0_tb1(acc[1], desc_lo(da + (UNIT >> 4) + k16 * 2), db, 1);
              wgmma_commit();
              bool ok = true;
              if (k16 == 2) ok = mbar_test(bars + 8u * (B_FULL + ((n + 1) & 7)), ((n + 1) >> 3) & 1) || (ks == 3 && (k4 == 3 || brk));
              if (k16 == QTURN && ks == 3 && (k4 == 3 || brk) && lane0) mbar_arrive(bars + 8u * (B_TURN + (ch ^ 1)));
              if (ks < 3 || k16 < 3) wgmma_wait<1>();
              if (k16 == 2 && !ok) mbar_wait(bars + 8u * (B_FULL + ((n + 1) & 7)), ((n + 1) >> 3) & 1);
            }
          }
          if (brk) {
            wgmma_wait<0>();
            if (lane0) mbar_arrive(bars + 8u * (B_EMPTY + ((n - 1) & 7)));
            n += 16;
            dlt ^= 10u * (UNIT >> 4);
            mbar_wait_lazy<100>(bars + 8u * (B_TURN + ch), tpar);
            tpar ^= 1u;
            STAMP(inst == KSQ, 17);
            mbar_wait(bars + 8u * (B_FULL + (n & 7)), (n >> 3) & 1);
          }
        }
        PHASE_IDS
        mbar_wait(bars + 8u * (B_PREP + ch), L & 1);
        const bool afree = mbar_test(bars + 8u * B_AFREE, inst & 1);
        float nmean[2][2], rinv[2][2];
        const uint32_t csa = base + OFF_CS + ((L & 1) * 192 + 4 * c) * 4;
        uint4 cs[20];
        {
          uint32_t v[4];
#pragma unroll
          for (int i = 0; i < 4; i++)
            v[i] = lds32(base + OFF_RS + (ch * 128 + (i >> 1) * 64 + wwarp * 16 + g + 8 * (i & 1)) * 4);
#pragma unroll
          for (int t = 0; t < 2; t++) cs[t] = lds128(csa + (t + 4) * 64);
#pragma unroll
          for (int i = 0; i < 4; i++) {
            nmean[i >> 1][i & 1] = -bf_lo(v[i]);
            rinv[i >> 1][i & 1] = rcp_fast(bf_hi(v[i]));
            asm volatile("" : "+f"(rinv[i >> 1][i & 1]), "+f"(nmean[i >> 1][i & 1]));
          }
        }
        const int mat = lane >> 3;
        const uint32_t soff = (wwarp * 16 + (mat & 1) * 8 + (lane & 7)) * 128;
        const uint32_t kdst = ((L & 1) ? KB_ROW0 : slots) + soff, vdst = ((L & 1) ? VB_ROW0 : slots + 8192) + soff;
        const uint32_t hs = (L & 1) ? 8192 : 16384;
        wgmma_wait<0>();
        reg_fence<96>(acc[0]);
        reg_fence<96>(acc[1]);
        if (lane0) mbar_arrive(bars + 8u * (B_EMPTY + ((n - 1) & 7)));
        STAMP(inst == KSQ, 16);
        GTL(2 + L * 8);
        if (!afree) mbar_wait(bars + 8u * B_AFREE, inst & 1);
#pragma unroll
        for (int t = 2; t < CSPF; t++) cs[t] = lds128(csa + (t + 4) * 64);
#pragma unroll
        for (int t = 0; t < 20; t++) {
          const int p = t >= 16 ? 0 : ((t >> 2) & 1) + 1, jp = t & 3;
          if (t + CSPF < 20) {
            const int tn = t + CSPF, jn = tn >= 16 ? tn - 16 : (tn & 7) + 4;
            cs[tn] = lds128(csa + jn * 64);
          }
          if (t == 16) {
#pragma unroll
            for (int i = 0; i < 4; i++) rinv[i >> 1][i & 1] *= SM_C;
          }
          const int j = p * 8 + 2 * jp;
          const float2 cs0 = make_float2(__uint_as_float(cs[t].x), __uint_as_float(cs[t].y));
          const float2 cs1 = make_float2(__uint_as_float(cs[t].z), __uint_as_float(cs[t].w));
          const uint32_t sw = ((2 * jp + (mat >> 1)) ^ (lane & 7)) << 4;
#pragma unroll
          for (int h = 0; h < 2; h++) {
            if (t < 16 && h != (t < 8 ? 1 : 0)) continue;
            const float* a = &acc[h][4 * j];
            const uint32_t r0 = pack_bf16x2(fmaf(nmean[h][0], cs0.x, a[0]) * rinv[h][0], fmaf(nmean[h][0], cs0.y, a[1]) * rinv[h][0]);
            const uint32_t r1 = pack_bf16x2(fmaf(nmean[h][1], cs0.x, a[2]) * rinv[h][1], fmaf(nmean[h][1], cs0.y, a[3]) * rinv[h][1]);
            const uint32_t r2 = pack_bf16x2(fmaf(nmean[h][0], cs1.x, a[4]) * rinv[h][0], fmaf(nmean[h][0], cs1.y, a[5]) * rinv[h][0]);
            const uint32_t r3 = pack_bf16x2(fmaf(nmean[h][1], cs1.x, a[6]) * rinv[h][1], fmaf(nmean[h][1], cs1.y, a[7]) * rinv[h][1]);
            const uint32_t dst = p == 0 ? slots + 3 * 16384 + soff + h * 8192 : (p == 1 ? kdst : vdst) + h * hs;
            stmatrix_x4(dst + sw, r0, r1, r2, r3);
          }
          if (t == 7 || t == 15) {
            fence_proxy_async_smem();
            named_bar_arrive(t == 7 ? 3 : 7, 160);
          }
        }
      }
      fence_proxy_async_smem();
      setmaxnreg_dec<128>();
      named_bar_sync(4, 256);
      }
      GTL(3 + L * 8);
      {
        PHASE_IDS
        if ((L & 1) == 0) attention_a(asst, L, gb, hp, inst & 1, ch, wwarp, lane, P.zero);
        else attention_b(asst, gb, inst & 1, wwarp, lane);
        GTL(4 + L * 8);
        fence_proxy_async_smem();
      }
      if (asst) {
        named_bar_arrive(5, 256);
        if (inst == 1) {
          mbar_wait(bars + 8u * B_AFREE, 0);
          colsum_part(&P.wqkv[1], 1, qr, hp);
          if (lane0) mbar_arrive(bars + 8u * B_CSD);
        }
        continue;
      }
      {
        named_bar_sync(5, 256);
        const int wwarp = warp & 3;
        if (wwarp < 2 && elect_one()) {
          tma_store_3d(&P.o, slots + 3 * 16384 + wwarp * 8192, 0, gb * 128 + wwarp * 64, hp);
          bulk_commit();
          bulk_wait0();
          mbar_arrive(bars + 8u * B_AFREE);
          fence_proxy_async_all();
          red_relaxed_add(g_flags + F_O + (gb * 2 + wwarp) * OSTR + hp, 1u);
        }
        __syncwarp();
      }
      GTL(5 + L * 8);

      {
        float acc[64];
        const int n0 = w_first(inst);
        const bool pre = w_pre(inst);
        const uint32_t dl = ch * 10u * (UNIT >> 4);
        mbar_wait_lazy<100>(bars + 8u * (B_TURN + ch), tpar);
        tpar ^= 1u;
        mbar_wait(bars + 8u * (B_FULL + (n0 & 7)), (n0 >> 3) & 1);
        GTL(6 + L * 8);
#pragma unroll
        for (int kt = 0; kt < 16; kt++) {
          const int n = n0 + kt;
          STAMP(inst == KSW, 20 + kt);
          const uint32_t da = ((base + w_ua(kt) * UNIT) >> 4) + 0x10000u + (w_ua(kt) < 10 ? dl : 0u - dl);
          uint32_t db = ((base + w_ub(kt) * UNIT) >> 4) + ((UNIT >> 4) << 16) + (w_ub(kt) < 10 ? dl : 0u - dl);
          if (pre_idx(kt) >= 0 && pre) db = ((slots + pre_idx(kt) * 2 * UNIT) >> 4) + ((UNIT >> 4) << 16);
          if (kt == PRE0 && pre) mbar_wait(bars + 8u * B_PRE, __popc(PREMASK & ((1u << inst) - 1u)) & 1);
          if (kt == 15 && lane0 && (inst & 3) != 0) mbar_arrive(bars + 8u * (B_TURN + (ch ^ 1)));
          wgmma_fence();
          if (kt == 0) wgmma_n128_ssz_ta0_tb1(acc, desc_lo(da), desc_lo(db));
#pragma unroll
          for (int k16 = kt == 0 ? 1 : 0; k16 < 4; k16++) wgmma_n128_ss_ta0_tb1(acc, desc_lo(da + 2 * k16), desc_lo(db + 128 * k16), 1);
          wgmma_commit();
          const uint32_t nb = bars + 8u * (kt == 15 ? B_RESF : B_FULL + ((n + 1) & 7)), np = kt == 15 ? ch : ((n + 1) >> 3) & 1;
          const bool ok = mbar_test(nb, np);
          if (kt > 0) {
            wgmma_wait<1>();
            if (lane0) mbar_arrive(bars + 8u * (B_EMPTY + ((n - 1) & 7)));
          }
          if (!ok) mbar_wait(nb, np);
        }
        PHASE_IDS
        const uint32_t xb = base + (8 + ch * 10) * UNIT;
        const int mat = lane >> 3;
        const uint32_t xrow = xb + (wwarp * 16 + (mat & 1) * 8 + (lane & 7)) * 128;
        uint32_t xv[8][4];
#pragma unroll
        for (int jp = 0; jp < 8; jp++)
          ldmatrix_x4(xv[jp], xrow + (jp >> 2) * UNIT + (((2 * (jp & 3) + (mat >> 1)) ^ (lane & 7)) << 4));
        wgmma_wait<0>();
        reg_fence<64>(acc);
        if (lane0) mbar_arrive(bars + 8u * (B_EMPTY + ((n0 + 15) & 7)));
        STAMP(inst == KSW, 36);
        GTL(7 + L * 8);
#pragma unroll
        for (int jp = 0; jp < 8; jp++) {
#pragma unroll
          for (int q = 0; q < 4; q++) xv[jp][q] = add_bf16x2(xv[jp][q], pack_bf16x2(acc[8 * jp + 2 * q], acc[8 * jp + 2 * q + 1]));
          stmatrix_x4(xrow + (jp >> 2) * UNIT + (((2 * (jp & 3) + (mat >> 1)) ^ (lane & 7)) << 4), xv[jp][0], xv[jp][1],
                      xv[jp][2], xv[jp][3]);
        }
        fence_proxy_async_smem();
        named_bar_sync(1 + ch, 128);
        const int grow = ch * 1024 + rt * 64;
        if (wwarp == 0) {
          if (elect_one()) {
            tma_store_3d(&P.xr[L == 3 ? 2 : 1], xb, 0, grow, ct * 2);
            bulk_commit();
            bulk_wait_read0();
            mbar_arrive(bars + 8u * B_RESE);
            bulk_wait0();
            TGET(t35);
            fence_proxy_async_all();
            if (L < 3) red_relaxed_add(g_flags + F_X + (ch * 8 + (rt >> 1)) * XSTR + ct, 1u);
            if (L == 2) TPUT(ch, 35, t35);
          }
          __syncwarp();
        } else if (lane == 0) {
          mbar_arrive(bars + 8u * B_RESE);
        }
        if (L < 3) {
          const unsigned ep1 = lds32(base + OFF_EPOCH);
          float s1[2] = {0.f, 0.f}, s2[2] = {0.f, 0.f};
#pragma unroll
          for (int jp = 0; jp < 8; jp++)
#pragma unroll
            for (int q = 0; q < 4; q++) {
              const float x0 = bf_lo(xv[jp][q]), x1 = bf_hi(xv[jp][q]);
              s1[q & 1] += x0 + x1;
              s2[q & 1] = fmaf(x0, x0, fmaf(x1, x1, s2[q & 1]));
            }
#pragma unroll
          for (int r = 0; r < 2; r++) {
            s1[r] += __shfl_xor_sync(0xffffffffu, s1[r], 1);
            s2[r] += __shfl_xor_sync(0xffffffffu, s2[r], 1);
            s1[r] += __shfl_xor_sync(0xffffffffu, s1[r], 2);
            s2[r] += __shfl_xor_sync(0xffffffffu, s2[r], 2);
            if (c == 0) st_rec(&g_stats[L + 1][ct][grow + wwarp * 16 + g + 8 * r], s1[r], s2[r], 0.f, ep1);
          }
        }
        GTL(8 + L * 8);
      }
    }
    if (threadIdx.x == 128) atomicAdd(g_flags + F_DONE, 1u);
  }
}

typedef CUresult (*PFN_tmEncode)(CUtensorMap*, CUtensorMapDataType, cuuint32_t, void*, const cuuint64_t*,
                                 const cuuint64_t*, const cuuint32_t*, const cuuint32_t*, CUtensorMapInterleave,
                                 CUtensorMapSwizzle, CUtensorMapL2promotion, CUtensorMapFloatOOBfill);

PFN_tmEncode get_encode_fn() {
  static PFN_tmEncode fn = nullptr;
  if (!fn) {
    cudaDriverEntryPointQueryResult qr;
    void* p = nullptr;
    cudaGetDriverEntryPoint("cuTensorMapEncodeTiled", &p, cudaEnableDefault, &qr);
    fn = (PFN_tmEncode)p;
  }
  return fn;
}

CUtensorMap make_map(const void* ptr, int rows, int cols, int inner, int box_rows, int box_blk) {
  CUtensorMap m;
  cuuint64_t gdim[3] = {(cuuint64_t)inner, (cuuint64_t)rows, (cuuint64_t)(cols / inner)};
  cuuint64_t gstr[2] = {(cuuint64_t)cols * 2, (cuuint64_t)inner * 2};
  cuuint32_t box[3] = {64, (cuuint32_t)box_rows, (cuuint32_t)box_blk};
  cuuint32_t estr[3] = {1, 1, 1};
  get_encode_fn()(&m, CU_TENSOR_MAP_DATA_TYPE_BFLOAT16, 3, const_cast<void*>(ptr), gdim, gstr, box, estr,
                  CU_TENSOR_MAP_INTERLEAVE_NONE, CU_TENSOR_MAP_SWIZZLE_128B, CU_TENSOR_MAP_L2_PROMOTION_L2_128B,
                  CU_TENSOR_MAP_FLOAT_OOB_FILL_NONE);
  return m;
}

}

extern "C" void kernel_launch(void* const* d_in, const int* in_sizes, int n_in, void* d_out, int out_size) {
  (void)in_sizes; (void)n_in; (void)out_size;
  void *p_o, *p_x;
  cudaGetSymbolAddress(&p_o, g_o);
  cudaGetSymbolAddress(&p_x, g_x);
  static bool attr_done = false;
  if (!attr_done) {
    cudaFuncSetAttribute(fused_kernel, cudaFuncAttributeMaxDynamicSharedMemorySize, SMEM_BYTES);
    attr_done = true;
  }
  Params P;
  P.in_x = (const __nv_bfloat16*)d_in[0];
  P.wqkv_p[0] = (const __nv_bfloat16*)d_in[1];
  P.wo_p[0] = (const __nv_bfloat16*)d_in[2];
  P.wqkv_p[1] = (const __nv_bfloat16*)d_in[4];
  P.wo_p[1] = (const __nv_bfloat16*)d_in[5];
  P.out = (__nv_bfloat16*)d_out;
  P.zero = 0;
  P.xq[0] = make_map(P.in_x, S_LEN, DM, 64, 128, 1);
  P.xq[1] = make_map(p_x, S_LEN, DM, 64, 128, 1);
  P.xr[0] = make_map(P.in_x, S_LEN, DM, 64, 64, 2);
  P.xr[1] = make_map(p_x, S_LEN, DM, 64, 64, 2);
  P.xr[2] = make_map(d_out, S_LEN, DM, 64, 64, 2);
  P.o = make_map(p_o, S_LEN, DM, 64, 64, 1);
  for (int t = 0; t < 2; t++) {
    P.wqkv[t] = make_map(P.wqkv_p[t], DM, NQKV, 1024, 64, 3);
    P.wo[t] = make_map(P.wo_p[t], DM, DM, 64, 64, 2);
  }
  fused_kernel<<<NCTA, 512, SMEM_BYTES>>>(P);
}
```

```cpp
#include <cuda_runtime.h>
#include <cuda_bf16.h>
#include <cuda.h>
#include <stdint.h>

namespace {

constexpr int S_LEN = 2048;
constexpr int DM = 1024;
constexpr int NQKV = 3072;
constexpr int NCTA = 128;

__device__ __align__(1024) uint8_t g_kvA[2][16][16][2][16384];
__device__ __align__(1024) uint8_t g_kvB[2][16][16][4096];
__device__ __align__(1024) uint8_t g_zero[16384];
__device__ __align__(1024) __nv_bfloat16 g_o[S_LEN * DM];
__device__ __align__(1024) __nv_bfloat16 g_x[S_LEN * DM];
__device__ __align__(1024) float4 g_stats[4][8][S_LEN];
__device__ __align__(1024) float4 g_cs[2][16][8][64];
constexpr int F_X = 0;
constexpr int XSTR = 32, OSTR = 32, KSTR = 32;
constexpr int F_O = F_X + 16 * XSTR;
constexpr int F_KV = F_O + 32 * OSTR;
constexpr int F_DONE = F_KV + 256 * KSTR;
__device__ __align__(1024) unsigned g_flags[F_DONE + 32];

constexpr uint32_t SBASE = 1024;
constexpr int UNIT = 8192;
constexpr int NUNITS = 20;
constexpr int OFF_SLOT = NUNITS * UNIT;
constexpr int OFF_BAR = OFF_SLOT + 4 * 16384;
constexpr int OFF_EPOCH = OFF_BAR + 296;
constexpr int OFF_CS = OFF_BAR + 304;
constexpr int OFF_RS = OFF_CS + 1536;
constexpr int OFF_TS = OFF_RS + 1024;
constexpr int SMEM_BYTES = OFF_RS + 1024;
constexpr int B_FULL = 0, B_EMPTY = 8, B_PREP = 16, B_HALO = 18, B_REL = 22, B_AFREE = 25, B_TURN = 26, B_XRDY = 28,
              B_CS = 30, B_CSD = 31, B_GO = 32, B_PRE = 33, B_RESF = 34, B_RESE = 35;

__device__ __forceinline__ uint32_t smem_u32(const void* p) { return (uint32_t)__cvta_generic_to_shared(p); }

__device__ __forceinline__ void mbar_init(uint32_t bar, uint32_t cnt) {
  asm volatile("mbarrier.init.shared::cta.b64 [%0], %1;" ::"r"(bar), "r"(cnt));
}
__device__ __forceinline__ void mbar_expect_tx(uint32_t bar, uint32_t bytes) {
  asm volatile("mbarrier.arrive.expect_tx.shared::cta.b64 _, [%0], %1;" ::"r"(bar), "r"(bytes) : "memory");
}
__device__ __forceinline__ void mbar_arrive(uint32_t bar) {
  asm volatile("mbarrier.arrive.shared::cta.b64 _, [%0];" ::"r"(bar) : "memory");
}
__device__ __forceinline__ bool mbar_try_wait(uint32_t bar, uint32_t parity) {
  uint32_t ok;
  asm volatile(
      "{\n.reg .pred p;\nmbarrier.try_wait.parity.shared::cta.b64 p, [%1], %2;\nselp.b32 %0, 1, 0, p;\n}\n"
      : "=r"(ok)
      : "r"(bar), "r"(parity)
      : "memory");
  return ok != 0;
}
__device__ __forceinline__ bool mbar_test(uint32_t bar, uint32_t parity) {
  uint32_t ok;
  asm volatile(
      "{\n.reg .pred p;\nmbarrier.test_wait.parity.shared::cta.b64 p, [%1], %2;\nselp.b32 %0, 1, 0, p;\n}\n"
      : "=r"(ok)
      : "r"(bar), "r"(parity)
      : "memory");
  return ok != 0;
}
__device__ __forceinline__ void mbar_wait(uint32_t bar, uint32_t parity) {
#pragma unroll 1
  for (uint32_t it = 0; it < (1u << 18); ++it) {
    if (mbar_try_wait(bar, parity)) return;
  }
}
__device__ __forceinline__ void mbar_pace(uint32_t bar, uint32_t parity) {
#pragma unroll 1
  for (uint32_t it = 0; it < 24; ++it) {
    if (mbar_try_wait(bar, parity)) return;
  }
}
template <int NS>
__device__ __forceinline__ void mbar_wait_lazy(uint32_t bar, uint32_t parity) {
#pragma unroll 1
  for (uint32_t it = 0; it < (1u << 18); ++it) {
    if (mbar_try_wait(bar, parity)) return;
    __nanosleep(NS);
  }
}
__device__ __forceinline__ bool elect_one() {
  uint32_t ok;
  asm volatile("{\n.reg .pred p;\nelect.sync _|p, 0xffffffff;\nselp.b32 %0, 1, 0, p;\n}\n" : "=r"(ok));
  return ok != 0;
}
__device__ __forceinline__ void fence_barrier_init() { asm volatile("fence.mbarrier_init.release.cluster;" ::: "memory"); }
__device__ __forceinline__ void fence_proxy_async_smem() { asm volatile("fence.proxy.async.shared::cta;" ::: "memory"); }
__device__ __forceinline__ void fence_proxy_async_all() { asm volatile("fence.proxy.async.global;" ::: "memory"); }

__device__ __forceinline__ void tma_load_3d(uint32_t dst, const CUtensorMap* map, uint32_t bar, int c0, int c1, int c2) {
  asm volatile(
      "cp.async.bulk.tensor.3d.shared::cluster.global.mbarrier::complete_tx::bytes [%0], [%1, {%3, %4, %5}], [%2];" ::"r"(dst),
      "l"(map), "r"(bar), "r"(c0), "r"(c1), "r"(c2)
      : "memory");
}
__device__ __forceinline__ void bulk_load(uint32_t dst, const void* src, uint32_t bytes, uint32_t bar) {
  asm volatile("cp.async.bulk.shared::cluster.global.mbarrier::complete_tx::bytes [%0], [%1], %2, [%3];" ::"r"(dst),
               "l"(src), "r"(bytes), "r"(bar)
               : "memory");
}
__device__ __forceinline__ void bulk_store(void* dst, uint32_t src, uint32_t bytes) {
  asm volatile("cp.async.bulk.global.shared::cta.bulk_group [%0], [%1], %2;" ::"l"(dst), "r"(src), "r"(bytes) : "memory");
}
__device__ __forceinline__ void tma_store_3d(const CUtensorMap* map, uint32_t src, int c0, int c1, int c2) {
  asm volatile("cp.async.bulk.tensor.3d.global.shared::cta.bulk_group [%0, {%2, %3, %4}], [%1];" ::"l"(map), "r"(src),
               "r"(c0), "r"(c1), "r"(c2)
               : "memory");
}
__device__ __forceinline__ void bulk_commit() { asm volatile("cp.async.bulk.commit_group;" ::: "memory"); }
__device__ __forceinline__ void bulk_wait_read0() { asm volatile("cp.async.bulk.wait_group.read 0;" ::: "memory"); }
__device__ __forceinline__ void bulk_wait0() { asm volatile("cp.async.bulk.wait_group 0;" ::: "memory"); }
__device__ __forceinline__ void named_bar_sync(int id, int nthreads) {
  asm volatile("bar.sync %0, %1;" ::"r"(id), "r"(nthreads) : "memory");
}
__device__ __forceinline__ void named_bar_arrive(int id, int nthreads) {
  asm volatile("bar.arrive %0, %1;" ::"r"(id), "r"(nthreads) : "memory");
}

__device__ __forceinline__ void wgmma_fence() { asm volatile("wgmma.fence.sync.aligned;\n" ::: "memory"); }
__device__ __forceinline__ void wgmma_commit() { asm volatile("wgmma.commit_group.sync.aligned;\n" ::: "memory"); }
template <int N>
__device__ __forceinline__ void wgmma_wait() {
  asm volatile("wgmma.wait_group.sync.aligned %0;\n" ::"n"(N) : "memory");
}
template <int R>
__device__ __forceinline__ void setmaxnreg_inc() { asm volatile("setmaxnreg.inc.sync.aligned.u32 %0;\n" ::"n"(R)); }
template <int R>
__device__ __forceinline__ void setmaxnreg_dec() { asm volatile("setmaxnreg.dec.sync.aligned.u32 %0;\n" ::"n"(R)); }
template <int N>
__device__ __forceinline__ void reg_fence(float* r) {
#pragma unroll
  for (int i = 0; i < N; i++) asm volatile("" : "+f"(r[i])::"memory");
}

template <int N>
__device__ __forceinline__ void reg_define(float* r) {
#pragma unroll
  for (int i = 0; i < N; i++) r[i] = 0.f;
}

__device__ __forceinline__ uint64_t desc_lo(uint32_t lo) {
  uint64_t d;
  asm("mov.b64 %0, {%1, %2};" : "=l"(d) : "r"(lo), "r"(0x40000040u));
  return d;
}
__device__ __forceinline__ uint64_t make_desc(uint32_t addr, uint32_t lbo_bytes) {
  return desc_lo((addr >> 4) + ((lbo_bytes >> 4) << 16));
}

__device__ __forceinline__ void wgmma_n192_ss_ta0_tb1(float* d, uint64_t descA, uint64_t descB, int scaleD) {
  asm volatile("{\n.reg .pred p;\nsetp.ne.b32 p, %98, 0;\n"
    "wgmma.mma_async.sync.aligned.m64n192k16.f32.bf16.bf16 {%0, %1, %2, %3, %4, %5, %6, %7, %8, %9, %10, %11, %12, %13, %14, %15, %16, %17, %18, %19, %20, %21, %22, %23, %24, %25, %26, %27, %28, %29, %30, %31, %32, %33, %34, %35, %36, %37, %38, %39, %40, %41, %42, %43, %44, %45, %46, %47, %48, %49, %50, %51, %52, %53, %54, %55, %56, %57, %58, %59, %60, %61, %62, %63, %64, %65, %66, %67, %68, %69, %70, %71, %72, %73, %74, %75, %76, %77, %78, %79, %80, %81, %82, %83, %84, %85, %86, %87, %88, %89, %90, %91, %92, %93, %94, %95}, %96, %97, p, 1, 1, 0, 1;\n}\n"
    : "+f"(d[0]), "+f"(d[1]), "+f"(d[2]), "+f"(d[3]), "+f"(d[4]), "+f"(d[5]), "+f"(d[6]), "+f"(d[7]), "+f"(d[8]), "+f"(d[9]), "+f"(d[10]), "+f"(d[11]), "+f"(d[12]), "+f"(d[13]), "+f"(d[14]), "+f"(d[15]), "+f"(d[16]), "+f"(d[17]), "+f"(d[18]), "+f"(d[19]), "+f"(d[20]), "+f"(d[21]), "+f"(d[22]), "+f"(d[23]), "+f"(d[24]), "+f"(d[25]), "+f"(d[26]), "+f"(d[27]), "+f"(d[28]), "+f"(d[29]), "+f"(d[30]), "+f"(d[31]), "+f"(d[32]), "+f"(d[33]), "+f"(d[34]), "+f"(d[35]), "+f"(d[36]), "+f"(d[37]), "+f"(d[38]), "+f"(d[39]), "+f"(d[40]), "+f"(d[41]), "+f"(d[42]), "+f"(d[43]), "+f"(d[44]), "+f"(d[45]), "+f"(d[46]), "+f"(d[47]), "+f"(d[48]), "+f"(d[49]), "+f"(d[50]), "+f"(d[51]), "+f"(d[52]), "+f"(d[53]), "+f"(d[54]), "+f"(d[55]), "+f"(d[56]), "+f"(d[57]), "+f"(d[58]), "+f"(d[59]), "+f"(d[60]), "+f"(d[61]), "+f"(d[62]), "+f"(d[63]), "+f"(d[64]), "+f"(d[65]), "+f"(d[66]), "+f"(d[67]), "+f"(d[68]), "+f"(d[69]), "+f"(d[70]), "+f"(d[71]), "+f"(d[72]), "+f"(d[73]), "+f"(d[74]), "+f"(d[75]), "+f"(d[76]), "+f"(d[77]), "+f"(d[78]), "+f"(d[79]), "+f"(d[80]), "+f"(d[81]), "+f"(d[82]), "+f"(d[83]), "+f"(d[84]), "+f"(d[85]), "+f"(d[86]), "+f"(d[87]), "+f"(d[88]), "+f"(d[89]), "+f"(d[90]), "+f"(d[91]), "+f"(d[92]), "+f"(d[93]), "+f"(d[94]), "+f"(d[95])
    : "l"(descA), "l"(descB), "r"(scaleD));
}

__device__ __forceinline__ void wgmma_n128_ss_ta0_tb1(float* d, uint64_t descA, uint64_t descB, int scaleD) {
  asm volatile("{\n.reg .pred p;\nsetp.ne.b32 p, %66, 0;\n"
    "wgmma.mma_async.sync.aligned.m64n128k16.f32.bf16.bf16 {%0, %1, %2, %3, %4, %5, %6, %7, %8, %9, %10, %11, %12, %13, %14, %15, %16, %17, %18, %19, %20, %21, %22, %23, %24, %25, %26, %27, %28, %29, %30, %31, %32, %33, %34, %35, %36, %37, %38, %39, %40, %41, %42, %43, %44, %45, %46, %47, %48, %49, %50, %51, %52, %53, %54, %55, %56, %57, %58, %59, %60, %61, %62, %63}, %64, %65, p, 1, 1, 0, 1;\n}\n"
    : "+f"(d[0]), "+f"(d[1]), "+f"(d[2]), "+f"(d[3]), "+f"(d[4]), "+f"(d[5]), "+f"(d[6]), "+f"(d[7]), "+f"(d[8]), "+f"(d[9]), "+f"(d[10]), "+f"(d[11]), "+f"(d[12]), "+f"(d[13]), "+f"(d[14]), "+f"(d[15]), "+f"(d[16]), "+f"(d[17]), "+f"(d[18]), "+f"(d[19]), "+f"(d[20]), "+f"(d[21]), "+f"(d[22]), "+f"(d[23]), "+f"(d[24]), "+f"(d[25]), "+f"(d[26]), "+f"(d[27]), "+f"(d[28]), "+f"(d[29]), "+f"(d[30]), "+f"(d[31]), "+f"(d[32]), "+f"(d[33]), "+f"(d[34]), "+f"(d[35]), "+f"(d[36]), "+f"(d[37]), "+f"(d[38]), "+f"(d[39]), "+f"(d[40]), "+f"(d[41]), "+f"(d[42]), "+f"(d[43]), "+f"(d[44]), "+f"(d[45]), "+f"(d[46]), "+f"(d[47]), "+f"(d[48]), "+f"(d[49]), "+f"(d[50]), "+f"(d[51]), "+f"(d[52]), "+f"(d[53]), "+f"(d[54]), "+f"(d[55]), "+f"(d[56]), "+f"(d[57]), "+f"(d[58]), "+f"(d[59]), "+f"(d[60]), "+f"(d[61]), "+f"(d[62]), "+f"(d[63])
    : "l"(descA), "l"(descB), "r"(scaleD));
}

__device__ __forceinline__ void wgmma_n192_ssz_ta0_tb1(float* d, uint64_t descA, uint64_t descB) {
  asm volatile("{\n.reg .pred p;\nsetp.ne.b32 p, 0, 0;\n"
    "wgmma.mma_async.sync.aligned.m64n192k16.f32.bf16.bf16 {%0, %1, %2, %3, %4, %5, %6, %7, %8, %9, %10, %11, %12, %13, %14, %15, %16, %17, %18, %19, %20, %21, %22, %23, %24, %25, %26, %27, %28, %29, %30, %31, %32, %33, %34, %35, %36, %37, %38, %39, %40, %41, %42, %43, %44, %45, %46, %47, %48, %49, %50, %51, %52, %53, %54, %55, %56, %57, %58, %59, %60, %61, %62, %63, %64, %65, %66, %67, %68, %69, %70, %71, %72, %73, %74, %75, %76, %77, %78, %79, %80, %81, %82, %83, %84, %85, %86, %87, %88, %89, %90, %91, %92, %93, %94, %95}, %96, %97, p, 1, 1, 0, 1;\n}\n"
    : "=f"(d[0]), "=f"(d[1]), "=f"(d[2]), "=f"(d[3]), "=f"(d[4]), "=f"(d[5]), "=f"(d[6]), "=f"(d[7]), "=f"(d[8]), "=f"(d[9]), "=f"(d[10]), "=f"(d[11]), "=f"(d[12]), "=f"(d[13]), "=f"(d[14]), "=f"(d[15]), "=f"(d[16]), "=f"(d[17]), "=f"(d[18]), "=f"(d[19]), "=f"(d[20]), "=f"(d[21]), "=f"(d[22]), "=f"(d[23]), "=f"(d[24]), "=f"(d[25]), "=f"(d[26]), "=f"(d[27]), "=f"(d[28]), "=f"(d[29]), "=f"(d[30]), "=f"(d[31]), "=f"(d[32]), "=f"(d[33]), "=f"(d[34]), "=f"(d[35]), "=f"(d[36]), "=f"(d[37]), "=f"(d[38]), "=f"(d[39]), "=f"(d[40]), "=f"(d[41]), "=f"(d[42]), "=f"(d[43]), "=f"(d[44]), "=f"(d[45]), "=f"(d[46]), "=f"(d[47]), "=f"(d[48]), "=f"(d[49]), "=f"(d[50]), "=f"(d[51]), "=f"(d[52]), "=f"(d[53]), "=f"(d[54]), "=f"(d[55]), "=f"(d[56]), "=f"(d[57]), "=f"(d[58]), "=f"(d[59]), "=f"(d[60]), "=f"(d[61]), "=f"(d[62]), "=f"(d[63]), "=f"(d[64]), "=f"(d[65]), "=f"(d[66]), "=f"(d[67]), "=f"(d[68]), "=f"(d[69]), "=f"(d[70]), "=f"(d[71]), "=f"(d[72]), "=f"(d[73]), "=f"(d[74]), "=f"(d[75]), "=f"(d[76]), "=f"(d[77]), "=f"(d[78]), "=f"(d[79]), "=f"(d[80]), "=f"(d[81]), "=f"(d[82]), "=f"(d[83]), "=f"(d[84]), "=f"(d[85]), "=f"(d[86]), "=f"(d[87]), "=f"(d[88]), "=f"(d[89]), "=f"(d[90]), "=f"(d[91]), "=f"(d[92]), "=f"(d[93]), "=f"(d[94]), "=f"(d[95])
    : "l"(descA), "l"(descB));
}

__device__ __forceinline__ void wgmma_n128_ssz_ta0_tb1(float* d, uint64_t descA, uint64_t descB) {
  asm volatile("{\n.reg .pred p;\nsetp.ne.b32 p, 0, 0;\n"
    "wgmma.mma_async.sync.aligned.m64n128k16.f32.bf16.bf16 {%0, %1, %2, %3, %4, %5, %6, %7, %8, %9, %10, %11, %12, %13, %14, %15, %16, %17, %18, %19, %20, %21, %22, %23, %24, %25, %26, %27, %28, %29, %30, %31, %32, %33, %34, %35, %36, %37, %38, %39, %40, %41, %42, %43, %44, %45, %46, %47, %48, %49, %50, %51, %52, %53, %54, %55, %56, %57, %58, %59, %60, %61, %62, %63}, %64, %65, p, 1, 1, 0, 1;\n}\n"
    : "=f"(d[0]), "=f"(d[1]), "=f"(d[2]), "=f"(d[3]), "=f"(d[4]), "=f"(d[5]), "=f"(d[6]), "=f"(d[7]), "=f"(d[8]), "=f"(d[9]), "=f"(d[10]), "=f"(d[11]), "=f"(d[12]), "=f"(d[13]), "=f"(d[14]), "=f"(d[15]), "=f"(d[16]), "=f"(d[17]), "=f"(d[18]), "=f"(d[19]), "=f"(d[20]), "=f"(d[21]), "=f"(d[22]), "=f"(d[23]), "=f"(d[24]), "=f"(d[25]), "=f"(d[26]), "=f"(d[27]), "=f"(d[28]), "=f"(d[29]), "=f"(d[30]), "=f"(d[31]), "=f"(d[32]), "=f"(d[33]), "=f"(d[34]), "=f"(d[35]), "=f"(d[36]), "=f"(d[37]), "=f"(d[38]), "=f"(d[39]), "=f"(d[40]), "=f"(d[41]), "=f"(d[42]), "=f"(d[43]), "=f"(d[44]), "=f"(d[45]), "=f"(d[46]), "=f"(d[47]), "=f"(d[48]), "=f"(d[49]), "=f"(d[50]), "=f"(d[51]), "=f"(d[52]), "=f"(d[53]), "=f"(d[54]), "=f"(d[55]), "=f"(d[56]), "=f"(d[57]), "=f"(d[58]), "=f"(d[59]), "=f"(d[60]), "=f"(d[61]), "=f"(d[62]), "=f"(d[63])
    : "l"(descA), "l"(descB));
}

__device__ __forceinline__ void wgmma_n64_ss_ta0_tb0(float* d, uint64_t descA, uint64_t descB, int scaleD) {
  asm volatile("{\n.reg .pred p;\nsetp.ne.b32 p, %34, 0;\n"
    "wgmma.mma_async.sync.aligned.m64n64k16.f32.bf16.bf16 {%0, %1, %2, %3, %4, %5, %6, %7, %8, %9, %10, %11, %12, %13, %14, %15, %16, %17, %18, %19, %20, %21, %22, %23, %24, %25, %26, %27, %28, %29, %30, %31}, %32, %33, p, 1, 1, 0, 0;\n}\n"
    : "+f"(d[0]), "+f"(d[1]), "+f"(d[2]), "+f"(d[3]), "+f"(d[4]), "+f"(d[5]), "+f"(d[6]), "+f"(d[7]), "+f"(d[8]), "+f"(d[9]), "+f"(d[10]), "+f"(d[11]), "+f"(d[12]), "+f"(d[13]), "+f"(d[14]), "+f"(d[15]), "+f"(d[16]), "+f"(d[17]), "+f"(d[18]), "+f"(d[19]), "+f"(d[20]), "+f"(d[21]), "+f"(d[22]), "+f"(d[23]), "+f"(d[24]), "+f"(d[25]), "+f"(d[26]), "+f"(d[27]), "+f"(d[28]), "+f"(d[29]), "+f"(d[30]), "+f"(d[31])
    : "l"(descA), "l"(descB), "r"(scaleD));
}

__device__ __forceinline__ void wgmma_n64_ssz_ta0_tb0(float* d, uint64_t descA, uint64_t descB) {
  asm volatile("{\n.reg .pred p;\nsetp.ne.b32 p, 0, 0;\n"
    "wgmma.mma_async.sync.aligned.m64n64k16.f32.bf16.bf16 {%0, %1, %2, %3, %4, %5, %6, %7, %8, %9, %10, %11, %12, %13, %14, %15, %16, %17, %18, %19, %20, %21, %22, %23, %24, %25, %26, %27, %28, %29, %30, %31}, %32, %33, p, 1, 1, 0, 0;\n}\n"
    : "=f"(d[0]), "=f"(d[1]), "=f"(d[2]), "=f"(d[3]), "=f"(d[4]), "=f"(d[5]), "=f"(d[6]), "=f"(d[7]), "=f"(d[8]), "=f"(d[9]), "=f"(d[10]), "=f"(d[11]), "=f"(d[12]), "=f"(d[13]), "=f"(d[14]), "=f"(d[15]), "=f"(d[16]), "=f"(d[17]), "=f"(d[18]), "=f"(d[19]), "=f"(d[20]), "=f"(d[21]), "=f"(d[22]), "=f"(d[23]), "=f"(d[24]), "=f"(d[25]), "=f"(d[26]), "=f"(d[27]), "=f"(d[28]), "=f"(d[29]), "=f"(d[30]), "=f"(d[31])
    : "l"(descA), "l"(descB));
}

__device__ __forceinline__ void wgmma_n80_ss_ta0_tb0(float* d, uint64_t descA, uint64_t descB, int scaleD) {
  asm volatile("{\n.reg .pred p;\nsetp.ne.b32 p, %42, 0;\n"
    "wgmma.mma_async.sync.aligned.m64n80k16.f32.bf16.bf16 {%0, %1, %2, %3, %4, %5, %6, %7, %8, %9, %10, %11, %12, %13, %14, %15, %16, %17, %18, %19, %20, %21, %22, %23, %24, %25, %26, %27, %28, %29, %30, %31, %32, %33, %34, %35, %36, %37, %38, %39}, %40, %41, p, 1, 1, 0, 0;\n}\n"
    : "+f"(d[0]), "+f"(d[1]), "+f"(d[2]), "+f"(d[3]), "+f"(d[4]), "+f"(d[5]), "+f"(d[6]), "+f"(d[7]), "+f"(d[8]), "+f"(d[9]), "+f"(d[10]), "+f"(d[11]), "+f"(d[12]), "+f"(d[13]), "+f"(d[14]), "+f"(d[15]), "+f"(d[16]), "+f"(d[17]), "+f"(d[18]), "+f"(d[19]), "+f"(d[20]), "+f"(d[21]), "+f"(d[22]), "+f"(d[23]), "+f"(d[24]), "+f"(d[25]), "+f"(d[26]), "+f"(d[27]), "+f"(d[28]), "+f"(d[29]), "+f"(d[30]), "+f"(d[31]), "+f"(d[32]), "+f"(d[33]), "+f"(d[34]), "+f"(d[35]), "+f"(d[36]), "+f"(d[37]), "+f"(d[38]), "+f"(d[39])
    : "l"(descA), "l"(descB), "r"(scaleD));
}

__device__ __forceinline__ void wgmma_n32_rs_tb1(float* d, const uint32_t* a, uint64_t descB, int scaleD) {
  asm volatile("{\n.reg .pred p;\nsetp.ne.b32 p, %21, 0;\n"
    "wgmma.mma_async.sync.aligned.m64n32k16.f32.bf16.bf16 {%0, %1, %2, %3, %4, %5, %6, %7, %8, %9, %10, %11, %12, %13, %14, %15}, {%16, %17, %18, %19}, %20, p, 1, 1, 1;\n}\n"
    : "+f"(d[0]), "+f"(d[1]), "+f"(d[2]), "+f"(d[3]), "+f"(d[4]), "+f"(d[5]), "+f"(d[6]), "+f"(d[7]), "+f"(d[8]), "+f"(d[9]), "+f"(d[10]), "+f"(d[11]), "+f"(d[12]), "+f"(d[13]), "+f"(d[14]), "+f"(d[15])
    : "r"(a[0]), "r"(a[1]), "r"(a[2]), "r"(a[3]), "l"(descB), "r"(scaleD));
}

__device__ __forceinline__ uint32_t pack_bf16x2(float lo, float hi) {
  uint32_t r;
  asm("cvt.rn.bf16x2.f32 %0, %1, %2;" : "=r"(r) : "f"(hi), "f"(lo));
  return r;
}
__device__ __forceinline__ float bf_lo(uint32_t p) { return __uint_as_float(p << 16); }
__device__ __forceinline__ float bf_hi(uint32_t p) { return __uint_as_float(p & 0xffff0000u); }
__device__ __forceinline__ float bf16_round(float v) { return __bfloat162float(__float2bfloat16_rn(v)); }
__device__ __forceinline__ float ex2_approx(float x) {
  float r;
  asm("ex2.approx.ftz.f32 %0, %1;" : "=f"(r) : "f"(x));
  return r;
}
__device__ __forceinline__ float rcp_fast(float x) {
  float r;
  asm("rcp.approx.ftz.f32 %0, %1;" : "=f"(r) : "f"(x));
  return r;
}
__device__ __forceinline__ void ldmatrix_x4(uint32_t (&r)[4], uint32_t addr) {
  asm volatile("ldmatrix.sync.aligned.m8n8.x4.shared.b16 {%0,%1,%2,%3}, [%4];"
               : "=r"(r[0]), "=r"(r[1]), "=r"(r[2]), "=r"(r[3])
               : "r"(addr)
               : "memory");
}
__device__ __forceinline__ void stmatrix_x4(uint32_t addr, uint32_t r0, uint32_t r1, uint32_t r2, uint32_t r3) {
  asm volatile("stmatrix.sync.aligned.m8n8.x4.shared.b16 [%0], {%1,%2,%3,%4};" ::"r"(addr), "r"(r0), "r"(r1), "r"(r2),
               "r"(r3));
}
__device__ __forceinline__ uint32_t add_bf16x2(uint32_t a, uint32_t b) {
  uint32_t r;
  asm("add.rn.bf16x2 %0, %1, %2;" : "=r"(r) : "r"(a), "r"(b));
  return r;
}
__device__ __forceinline__ uint4 lds128(uint32_t addr) {
  uint4 v;
  asm volatile("ld.shared.v4.b32 {%0,%1,%2,%3}, [%4];" : "=r"(v.x), "=r"(v.y), "=r"(v.z), "=r"(v.w) : "r"(addr) : "memory");
  return v;
}
__device__ __forceinline__ uint32_t lds32(uint32_t addr) {
  uint32_t v;
  asm volatile("ld.shared.b32 %0, [%1];" : "=r"(v) : "r"(addr) : "memory");
  return v;
}
__device__ __forceinline__ void sts32(uint32_t addr, uint32_t v) {
  asm volatile("st.shared.b32 [%0], %1;" ::"r"(addr), "r"(v) : "memory");
}

__device__ __forceinline__ unsigned ld_acquire_u32(const unsigned* p) {
  unsigned v;
  asm volatile("ld.acquire.gpu.global.u32 %0, [%1];" : "=r"(v) : "l"(p) : "memory");
  return v;
}
__device__ __forceinline__ void red_relaxed_add(unsigned* p, unsigned v) {
  asm volatile("red.relaxed.gpu.global.add.u32 [%0], %1;" ::"l"(p), "r"(v) : "memory");
}
__device__ __forceinline__ void wait_ge(const unsigned* p, unsigned target) {
#pragma unroll 1
  for (uint32_t it = 0; it < (1u << 17); ++it) {
    if ((int)(ld_acquire_u32(p) - target) >= 0) return;
  }
}

__device__ __forceinline__ void wait_ge2(const unsigned* p, unsigned t0, unsigned t1) {
#pragma unroll 1
  for (uint32_t it = 0; it < (1u << 17); ++it) {
    unsigned long long v;
    asm volatile("ld.acquire.gpu.global.u64 %0, [%1];" : "=l"(v) : "l"(p) : "memory");
    if ((int)((unsigned)v - t0) >= 0 && (int)((unsigned)(v >> 32) - t1) >= 0) return;
  }
}

template <bool SLOW>
__device__ __forceinline__ void wait_mask(const unsigned* f, int cnt, unsigned target, uint32_t need, uint32_t& seen, int lane) {
  if ((seen & need) == need) return;
  const unsigned* fp = f + (lane & (cnt - 1));
#pragma unroll 1
  for (uint32_t it = 0; it < (1u << 17); ++it) {
    seen = __ballot_sync(0xffffffffu, (int)(ld_acquire_u32(fp) - target) >= 0);
    if ((seen & need) == need) break;
    if (SLOW) __nanosleep(400);
  }
  fence_proxy_async_all();
}
__device__ __forceinline__ float4 ld_rec(const float4* p) {
  float4 v;
  asm volatile("ld.relaxed.gpu.global.v4.f32 {%0,%1,%2,%3}, [%4];" : "=f"(v.x), "=f"(v.y), "=f"(v.z), "=f"(v.w) : "l"(p) : "memory");
  return v;
}
__device__ __forceinline__ void st_rec(float4* p, float a, float b, float c, unsigned tag) {
  asm volatile("st.relaxed.gpu.global.v4.f32 [%0], {%1,%2,%3,%4};" ::"l"(p), "f"(a), "f"(b), "f"(c), "f"(__uint_as_float(tag)) : "memory");
}
template <int N>
__device__ __forceinline__ float4 sum_recs(const float4* p, int stride, unsigned tag) {
  float4 s;
#pragma unroll 1
  for (uint32_t it = 0; it < (1u << 17); ++it) {
    float4 v[N];
#pragma unroll
    for (int t = 0; t < N; t++) v[t] = ld_rec(p + t * stride);
    bool ok = true;
    s = make_float4(0.f, 0.f, 0.f, 0.f);
#pragma unroll
    for (int t = 0; t < N; t++) {
      ok &= __float_as_uint(v[t].w) == tag;
      s.x += v[t].x;
      s.y += v[t].y;
      s.z += v[t].z;
    }
    if (ok) break;
    __nanosleep(200);
  }
  return s;
}

__device__ __forceinline__ int fresh_tid() {
  int t;
  asm volatile("mov.u32 %0, %%tid.x;" : "=r"(t));
  return t;
}
#define PHASE_IDS                                  \
  const int tid_ = fresh_tid();                    \
  const int lane = tid_ & 31, wwarp = __shfl_sync(0xffffffffu, (tid_ >> 5) & 3, 0), tid = tid_ & 127; \
  const int g = lane >> 2, c = lane & 3;           \
  (void)tid; (void)g; (void)c; (void)wwarp;

#define STAMPW(cond, i) do { } while (0)
#define STAMP(cond, i) do { } while (0)
#define STA(i) do { } while (0)
#define GTL(i) do { } while (0)
#define GTLX(c, i) do { } while (0)
#define TGET(v) do { } while (0)
#define TPUT(c, i, v) do { } while (0)

constexpr float SM_C = 0.17677669529663687f * 1.4426950408889634f;

constexpr uint32_t OA_TILE = SBASE + OFF_SLOT + 16384;

__device__ __forceinline__ void sched_fence(uint32_t never) {
  asm volatile("{\n.reg .pred p;\nsetp.ne.u32 p, %0, 0;\n@p exit;\n}\n" ::"r"(never) : "memory");
}

template <int K0, int K1>
__device__ __forceinline__ void attn_exp(float (&s)[32]) {
#pragma unroll
  for (int k = K0; k < K1; k++) s[k] = ex2_approx(s[k]);
}
#define ASPL 16
#define ASPM 6
template <int MODE, bool NEXT>
__device__ __forceinline__ void attn_unit(float (&s)[32], float (&sn)[32], float (&o)[16], float (&l)[2], bool valid,
                                          uint32_t vdesc, uint32_t qdesc, uint32_t kdesc, uint32_t tri, int w,
                                          uint32_t hbar, uint32_t hpar, uint32_t rel, uint32_t zero, bool stampon = false) {
  float x[9][2];
  if (MODE == 0) {
    attn_exp<0, ASPL>(s);
  } else {
#pragma unroll
    for (int e = 0; e < 2; e++) {
#pragma unroll
      for (int j = 0; j < 4; j++) x[j][e] = MODE == 1 ? s[4 * j + 2 + e] : s[16 + 4 * j + e];
      x[4][e] = MODE == 1 ? s[e] : s[30 + e];
      x[5][e] = MODE == 1 ? s[18 + e] : s[12 + e];
#pragma unroll
      for (int u = 1; u < 4; u++)
        x[5 + u][e] = MODE == 1 ? (w >= u ? s[4 * u + e] : s[4 * (8 - u) + 2 + e]) : (w >= u ? s[4 * (7 - u) + 2 + e] : s[4 * (u - 1) + e]);
    }
#pragma unroll
    for (int k = 0; k < 2 * ASPM; k++) x[k >> 1][k & 1] = ex2_approx(x[k >> 1][k & 1]);
  }
  sched_fence(zero);
  if (hbar) mbar_wait(hbar, hpar);
  wgmma_wait<0>();
  if (rel) mbar_arrive(rel);
  if (NEXT) {
    wgmma_fence();
    wgmma_n64_ssz_ta0_tb0(sn, desc_lo(qdesc), desc_lo(kdesc));
    wgmma_n64_ss_ta0_tb0(sn, desc_lo(qdesc + 2), desc_lo(kdesc + 2), 1);
    wgmma_commit();
    sched_fence(zero);
  }
  uint32_t p[16];
  if (MODE == 0) {
    attn_exp<ASPL, 32>(s);
#pragma unroll
    for (int k = 0; k < 16; k++) p[k] = pack_bf16x2(s[2 * k], s[2 * k + 1]);
  } else {
#pragma unroll
    for (int k = 2 * ASPM; k < 18; k++) x[k >> 1][k & 1] = ex2_approx(x[k >> 1][k & 1]);
    const uint32_t tm = MODE == 1 ? tri : ~tri;
#pragma unroll
    for (int j = 0; j < 4; j++) {
      p[MODE == 1 ? 2 * j + 1 : 8 + 2 * j] = pack_bf16x2(x[j][0], x[j][1]);
      p[MODE == 1 ? 8 + 2 * j : 2 * j + 1] = 0u;
    }
    p[MODE == 1 ? 0 : 15] = pack_bf16x2(x[4][0], x[4][1]) & (w == 0 ? tm : 0xffffffffu);
    p[MODE == 1 ? 9 : 6] = pack_bf16x2(x[5][0], x[5][1]) & (w == 3 ? tm : 0xffffffffu);
#pragma unroll
    for (int u = 1; u < 4; u++) {
      const uint32_t q = pack_bf16x2(x[5 + u][0], x[5 + u][1]);
      p[MODE == 1 ? 2 * u : 2 * (7 - u) + 1] = q & (w > u ? 0xffffffffu : (w == u ? tm : 0u));
      p[MODE == 1 ? 2 * (8 - u) + 1 : 2 * (u - 1)] = q & (w < u - 1 ? 0xffffffffu : (w == u - 1 ? tm : 0u));
    }
  }
  wgmma_fence();
#pragma unroll
  for (int k = 0; k < 4; k++) wgmma_n32_rs_tb1(o, p + 4 * k, desc_lo(vdesc + k * 128), 1);
  wgmma_commit();
#pragma unroll
  for (int r = 0; r < 2; r++) {
    float t = 0.f;
#pragma unroll
    for (int hf = 0; hf < 2; hf++) {
      if (MODE != 0 && r == MODE - 1 && hf == 2 - MODE) continue;
      const uint32_t* q = p + 8 * hf + r;
      const uint32_t v = add_bf16x2(add_bf16x2(q[0], q[2]), add_bf16x2(q[4], q[6]));
      t = (MODE != 0 && r == MODE - 1) || hf == 0 ? bf_lo(v) + bf_hi(v) : t + (bf_lo(v) + bf_hi(v));
    }
    if (valid) l[r] += t;
  }
  if (NEXT) {
    wgmma_wait<1>();
    reg_fence<32>(sn);
  }
}

__device__ __forceinline__ void attn_a_slow(const uint8_t* __restrict__ kvimg, int L, int gb, int hp,
                                         int hh, int wwarp, int lane) {
  constexpr uint32_t sq = SBASE + OFF_SLOT + 3 * 16384;
  const unsigned ep = (*(volatile unsigned*)(g_flags + F_DONE)) / NCTA;
  wait_ge2(g_flags + F_KV + (gb * 16 + hp) * KSTR, 4u * ep + L + 1u, 2u * ep + (L >> 1) + 1u);
#pragma unroll 1
  for (int t = 0; t < 32; t++) {
    const int row = (t >> 4) * 64 + ((t & 8) ? 7 - wwarp : wwarp) * 8 + (t & 7);
    const int qpos = gb * 128 + row;
    const uint32_t qaddr = sq + ((t >> 4) * 64 + wwarp * 16 + (t & 15)) * 128;
    float mx = -INFINITY, sum = 0.f, acc = 0.f;
#pragma unroll 1
    for (int pass = 0; pass < 2; pass++) {
#pragma unroll 1
      for (int j = 0; j < 8; j++) {
        const int kp = qpos - (lane + 32 * j);
        const uint8_t* kr = kvimg + ((size_t)((kp >> 7) * 16 + hp) * 2 + ((kp >> 6) & 1)) * 16384 + (kp & 63) * 128;
        float d = -INFINITY;
        if (kp >= 0) {
          d = 0.f;
#pragma unroll 1
          for (int q = 0; q < 4; q++) {
            const uint4 kv = __ldcg(reinterpret_cast<const uint4*>(kr + (((hh * 4 + q) ^ (kp & 7)) << 4)));
            const uint4 qv = lds128(qaddr + (((hh * 4 + q) ^ (row & 7)) << 4));
            const uint32_t kw[4] = {kv.x, kv.y, kv.z, kv.w}, qw[4] = {qv.x, qv.y, qv.z, qv.w};
#pragma unroll
            for (int e = 0; e < 4; e++) d = fmaf(bf_lo(kw[e]), bf_lo(qw[e]), fmaf(bf_hi(kw[e]), bf_hi(qw[e]), d));
          }
        }
        if (pass == 0) {
          mx = fmaxf(mx, d);
        } else {
          const float ev = ex2_approx(d - mx);
          sum += ev;
          const float pv = bf16_round(ev);
#pragma unroll 1
          for (int kk = 0; kk < 32; kk++) {
            const float pk = __shfl_sync(0xffffffffu, pv, kk);
            const int k2 = qpos - (kk + 32 * j);
            if (k2 >= 0) {
              const uint8_t* vr = kvimg + ((size_t)((k2 >> 7) * 16 + hp) * 2 + ((k2 >> 6) & 1)) * 16384 + 8192 + (k2 & 63) * 128;
              const unsigned short vv =
                  __ldcg(reinterpret_cast<const unsigned short*>(vr + (((hh * 4 + (lane >> 3)) ^ (k2 & 7)) << 4) + (lane & 7) * 2));
              acc = fmaf(pk, __uint_as_float((uint32_t)vv << 16), acc);
            }
          }
        }
      }
      if (pass == 0) {
#pragma unroll
        for (int o = 16; o > 0; o >>= 1) mx = fmaxf(mx, __shfl_xor_sync(0xffffffffu, mx, o));
      }
    }
#pragma unroll
    for (int o = 16; o > 0; o >>= 1) sum += __shfl_xor_sync(0xffffffffu, sum, o);
    acc *= rcp_fast(sum);
    const float hi = __shfl_down_sync(0xffffffffu, acc, 1);
    __syncwarp();
    if ((lane & 1) == 0)
      sts32(OA_TILE + row * 128 + (((hh * 4 + (lane >> 3)) ^ (row & 7)) << 4) + (lane & 7) * 2, pack_bf16x2(acc, hi));
    __syncwarp();
  }
}

__device__ __forceinline__ void store_o(const float (&o)[16], const float (&inv)[2], uint32_t rowaddr, int hh, int lane) {
  const int mat = lane >> 3, r7 = lane & 7;
#pragma unroll
  for (int jp = 0; jp < 2; jp++)
    stmatrix_x4(rowaddr + (((hh * 4 + 2 * jp + (mat >> 1)) ^ r7) << 4),
                pack_bf16x2(o[8 * jp] * inv[0], o[8 * jp + 1] * inv[0]),
                pack_bf16x2(o[8 * jp + 2] * inv[1], o[8 * jp + 3] * inv[1]),
                pack_bf16x2(o[8 * jp + 4] * inv[0], o[8 * jp + 5] * inv[0]),
                pack_bf16x2(o[8 * jp + 6] * inv[1], o[8 * jp + 7] * inv[1]));
}

__device__ __forceinline__ void attention_a(int HH, int L, int gb, int hp, uint32_t par0, uint32_t parA, int wwarp, int lane,
                                            uint32_t zero) {
  constexpr uint32_t bars = SBASE + OFF_BAR;
  const uint32_t dslot = ((SBASE + OFF_SLOT) >> 4) + 0x10000u + HH * 4;
  const uint32_t dq = dslot + 3 * 1024;
  float sa[32], sb[32], o[2][16], l[2][2];
  auto dch = [&](int n) { return dslot + 1024u * (n % 3 == 0 ? 1 : (n % 3 == 1 ? 0 : 2)); };
  wgmma_fence();
  wgmma_n64_ssz_ta0_tb0(sa, desc_lo(dq + 512), desc_lo(dch(0)));
  wgmma_n64_ss_ta0_tb0(sa, desc_lo(dq + 512 + 2), desc_lo(dch(0) + 2), 1);
  wgmma_commit();
#pragma unroll
  for (int h = 0; h < 2; h++) {
#pragma unroll
    for (int i = 0; i < 16; i++) o[h][i] = 0.f;
    l[h][0] = l[h][1] = 0.f;
  }
  const int dg = (lane >> 2) - 2 * (lane & 3);
  const uint32_t tri = (dg >= 0 ? 0xffffu : 0u) | (dg >= 1 ? 0xffff0000u : 0u);
  const int nmax = 2 * gb + 1;
  wgmma_wait<0>();
  reg_fence<32>(sa);
#define STON false
#define ATT_STEP(i, MODE)                                                                                            \
  attn_unit<MODE, true>(sa, sb, o[1], l[1], i <= nmax, dch(i) + 512, dq, dch(i + 1), tri, wwarp,                     \
                        i >= 1 ? bars + 8u * (B_HALO + i - 1) : 0u, i == 1 ? par0 : parA, 0u, zero, STON);                \
  attn_unit<MODE, (i < 4)>(sb, sa, o[0], l[0], i + 1 <= nmax, dch(i + 1) + 512, dq + 512, dch(i + 1), tri, wwarp, 0u, \
                           0u, i < 3 && lane == 0 ? bars + 8u * (B_REL + i) : 0u, zero);
  ATT_STEP(0, 1)
  ATT_STEP(1, 0)
  ATT_STEP(2, 0)
  ATT_STEP(3, 0)
  ATT_STEP(4, 2)
#undef ATT_STEP
  const uint32_t ra = OA_TILE + (((lane & 8) ? 7 - wwarp : wwarp) * 8 + (lane & 7)) * 128;
  bool bad = false;
#pragma unroll
  for (int h = 1; h >= 0; h--) {
    float inv[2];
#pragma unroll
    for (int r = 0; r < 2; r++) {
      float v = l[h][r];
      v += __shfl_xor_sync(0xffffffffu, v, 1);
      v += __shfl_xor_sync(0xffffffffu, v, 2);
      bad |= !(v <= 1.152921504606846976e18f && v >= 8.673617379884035e-19f);
      inv[r] = rcp_fast(v);
    }
    if (h == 0) wgmma_wait<0>();
    reg_fence<16>(o[h]);
    store_o(o[h], inv, ra + h * 8192, HH, lane);
  }
  if (HH == 0) GTL(45);
  if (__any_sync(0xffffffffu, bad)) attn_a_slow(g_kvA[L >> 1][0][0][0], L, gb, hp, HH, wwarp, lane);
}

constexpr uint32_t KB_ROW0 = SBASE + OFF_SLOT + 2048, VB_ROW0 = SBASE + OFF_SLOT + 24576 + 2048;

__device__ __forceinline__ void attnB_soft(const float (&s)[40], int wwarp, int D, bool edge, bool odd,
                                           uint32_t (&p)[5][4], float (&sum)[2]) {
  float z[2][3];
#define GATHER_(W)                                                                                  \
  _Pragma("unroll") for (int r = 0; r < 2; r++) _Pragma("unroll") for (int t = 0; t < 3; t++)       \
      z[r][t] = odd ? s[4 * (2 * W + r + t) + 2 * r + 1] : s[4 * (2 * W + r + t) + 2 * r];
  if (wwarp < 2) {
    if (wwarp == 0) { GATHER_(0) } else { GATHER_(1) }
  } else {
    if (wwarp == 2) { GATHER_(2) } else { GATHER_(3) }
  }
#undef GATHER_
  float y[2];
  y[0] = D >= 2 ? z[0][0] : z[0][2];
  y[1] = D >= 2 ? z[1][0] : z[1][2];
  if (edge) {
    z[0][1] = -INFINITY;
    if (D >= 2) y[0] = y[1] = -INFINITY;
  }
  float m0 = fmaxf(z[0][1], y[0]), m1 = fmaxf(z[1][1], y[1]);
  m0 = fmaxf(m0, __shfl_xor_sync(0xffffffffu, m0, 1));
  m1 = fmaxf(m1, __shfl_xor_sync(0xffffffffu, m1, 1));
  m0 = fmaxf(m0, __shfl_xor_sync(0xffffffffu, m0, 2));
  m1 = fmaxf(m1, __shfl_xor_sync(0xffffffffu, m1, 2));
  const float e00 = ex2_approx(z[0][1] - m0), e01 = ex2_approx(y[0] - m0);
  const float e10 = ex2_approx(z[1][1] - m1), e11 = ex2_approx(y[1] - m1);
  sum[0] = e00 + e01;
  sum[1] = e10 + e11;
  const int sh = odd ? 16 : 0;
  const uint32_t a0 = pack_bf16x2(e00, 0.f) << sh, a1 = pack_bf16x2(e10, 0.f) << sh;
  const uint32_t b0 = pack_bf16x2(e01, 0.f) << sh, b1 = pack_bf16x2(e11, 0.f) << sh;
  const int kb = wwarp + (D >= 2 ? 0 : 1);
#pragma unroll
  for (int k = 0; k < 5; k++) {
    p[k][0] = k == kb ? b0 : 0u;
    p[k][1] = k == wwarp + 1 ? a1 : 0u;
    p[k][2] = k == wwarp ? a0 : 0u;
    p[k][3] = k == kb ? b1 : 0u;
#pragma unroll
    for (int q = 0; q < 4; q++) asm volatile("" : "+r"(p[k][q]));
  }
}

__device__ __forceinline__ void attnB_s(float (&s)[40], int HH, int h) {
  constexpr uint32_t sq = SBASE + OFF_SLOT + 3 * 16384;
#pragma unroll
  for (int ks = 0; ks < 2; ks++)
    wgmma_n80_ss_ta0_tb0(s, make_desc(sq + h * 8192 + HH * 64 + ks * 32, 16),
                         make_desc(KB_ROW0 + h * 8192 - 2048 + HH * 64 + ks * 32, 16), ks);
}
__device__ __forceinline__ void attnB_pv(float (&o)[16], const uint32_t (&p)[5][4], int HH, int h) {
#pragma unroll
  for (int k = 0; k < 5; k++)
    wgmma_n32_rs_tb1(o, p[k], make_desc(VB_ROW0 + h * 8192 - 2048 + k * 2048 + HH * 64, 16), k);
}

__device__ __forceinline__ void attention_b(int HH, int gb, uint32_t par0, int wwarp, int lane) {
  constexpr uint32_t bars = SBASE + OFF_BAR, sq = SBASE + OFF_SLOT + 3 * 16384;
  float s[40];
  reg_define<40>(s);
  wgmma_fence();
  attnB_s(s, HH, 1);
  wgmma_commit();
  const int g = lane >> 2;
  const bool odd = g & 1;
  const int D = 2 * (lane & 3) + (g & 1) - g;
  const uint32_t ra = sq + (wwarp * 16 + ((lane >> 3) & 1) * 8 + (lane & 7)) * 128;
  wgmma_wait<0>();
  reg_fence<40>(s);
#pragma unroll 1
  for (int h = 1; h >= 0; h--) {
    float o[16], inv[2];
    uint32_t p[5][4];
    reg_define<16>(o);
    attnB_soft(s, wwarp, D, h == 0 && gb == 0 && wwarp == 0, odd, p, inv);
    if (h == 1) {
      mbar_wait(bars + 8u * B_HALO, par0);
      wgmma_fence();
      attnB_s(s, HH, 0);
    }
    wgmma_fence();
    attnB_pv(o, p, HH, h);
    wgmma_commit();
#pragma unroll
    for (int r = 0; r < 2; r++) {
      inv[r] += __shfl_xor_sync(0xffffffffu, inv[r], 1);
      inv[r] += __shfl_xor_sync(0xffffffffu, inv[r], 2);
      inv[r] = rcp_fast(inv[r]);
    }
    wgmma_wait<0>();
    reg_fence<40>(s);
    reg_fence<16>(o);
    store_o(o, inv, ra + h * 8192, HH, lane);
  }
}

#define KTQM 0
#define TRICKLE 300
#define CSPF 4
#define HPOLL 3
#define QTURN 2
struct Params {
  CUtensorMap xq[2], xr[3], o, wqkv[2], wo[2];
  const __nv_bfloat16* in_x;
  const __nv_bfloat16* wqkv_p[2];
  const __nv_bfloat16* wo_p[2];
  __nv_bfloat16* out;
  uint32_t zero;
};

__device__ __forceinline__ void colsum_part(const CUtensorMap* wmap, int ty, int qr, int hp) {
  constexpr uint32_t bars = SBASE + OFF_BAR, slots = SBASE + OFF_SLOT;
  PHASE_IDS
  const unsigned ep1 = (*(volatile unsigned*)(g_flags + F_DONE)) / NCTA + 1u;
  if (wwarp == 0 && elect_one()) {
    mbar_expect_tx(bars + 8u * B_CS, 6 * UNIT);
#pragma unroll 1
    for (int j = 0; j < 2; j++) {
      if (ty == 0) mbar_pace(bars + 8u * (B_EMPTY + 1 + 3 * j), 0);
      else __nanosleep(1000);
      tma_load_3d(slots + j * 3 * UNIT, wmap, bars + 8u * B_CS, hp * 64, qr * 128 + j * 64, 0);
    }
  }
  mbar_wait(bars + 8u * B_CS, ty);
  const uint32_t src = slots + (tid >> 3) * 128 + (((tid & 7) ^ ((tid >> 3) & 7)) << 4);
#pragma unroll 1
  for (int p = 0; p < 3; p++) {
    float s[8];
#pragma unroll
    for (int e = 0; e < 8; e++) s[e] = 0.f;
#pragma unroll
    for (int j = 0; j < 8; j++) {
      const uint4 v = lds128(src + p * UNIT + (j >> 2) * 3 * UNIT + (j & 3) * 2048);
      const uint32_t x[4] = {v.x, v.y, v.z, v.w};
#pragma unroll
      for (int e = 0; e < 4; e++) {
        s[2 * e] += bf_lo(x[e]);
        s[2 * e + 1] += bf_hi(x[e]);
      }
    }
#pragma unroll
    for (int st = 0; st < 2; st++) {
      const bool up = (lane >> (st + 3)) & 1;
#pragma unroll
      for (int e = 0; e < (4 >> st); e++) {
        const float keep = up ? s[e + (4 >> st)] : s[e], give = up ? s[e] : s[e + (4 >> st)];
        s[e] = keep + __shfl_xor_sync(0xffffffffu, give, 8 << st);
      }
    }
    const uint32_t dst = slots + 6 * UNIT + ((wwarp * 3 + p) * 64 + (lane & 7) * 8 + ((lane >> 3) & 1) * 4 + (lane >> 4) * 2) * 4;
    sts32(dst, __float_as_uint(s[0]));
    sts32(dst + 4, __float_as_uint(s[1]));
  }
  named_bar_sync(6, 128);
  if (tid < 64) {
    float r[3] = {0.f, 0.f, 0.f};
#pragma unroll
    for (int e = 0; e < 12; e++) r[e % 3] += __uint_as_float(lds32(slots + 6 * UNIT + (e * 64 + tid) * 4));
    st_rec(&g_cs[ty][hp][qr][tid], r[0], r[1], r[2], ep1);
  }
  named_bar_sync(6, 128);
}

__device__ __forceinline__ int cs_pos(int col) { return (col & ~15) + ((col & 7) >> 1) * 4 + ((col >> 3) & 1) * 2 + (col & 1); }

__device__ __forceinline__ uint32_t ln_params(float s1, float s2) {
  const float mean = s1 * (1.0f / DM);
  const float var = fmaxf(fmaf(-mean, mean, s2 * (1.0f / DM)), 0.f);
  float sd;
  asm("sqrt.approx.f32 %0, %1;" : "=f"(sd) : "f"(bf16_round(bf16_round(var) + 1e-5f)));
  return pack_bf16x2(mean, sd);
}

__host__ __device__ constexpr int w_ua(int kt) { return (kt == 6 ? 20 : 3 * kt) % 20; }
__host__ __device__ constexpr int w_ub(int kt) { return (kt == 6 ? 18 : 3 * kt + 1) % 20; }

constexpr int NSEG = 20;
__host__ __device__ constexpr int SEGQ(int ch, int L, int k0, int k1) { return ch | (L << 2) | ((k0 / 4) << 4) | ((k1 / 4 - 1) << 6); }
__host__ __device__ constexpr int SEGW(int ch, int L) { return ch | 2 | (L << 2); }
__host__ __device__ constexpr unsigned long long pack8(int a, int b, int c, int d, int e, int f, int g, int h) {
  return (unsigned long long)a | ((unsigned long long)b << 8) | ((unsigned long long)c << 16) | ((unsigned long long)d << 24) |
         ((unsigned long long)e << 32) | ((unsigned long long)f << 40) | ((unsigned long long)g << 48) | ((unsigned long long)h << 56);
}
#define SP2 12
#define SP3 12
#define SP4 12
#define SP6 12
__device__ __forceinline__ int seg_code(int sg) {
  constexpr unsigned long long T0 = pack8(SEGQ(0, 0, 0, 16), SEGQ(1, 0, 0, 16), SEGW(0, 0), SEGQ(0, 1, 0, SP2), SEGW(1, 0),
                                          SEGQ(0, 1, SP2, 16), SEGQ(1, 1, 0, SP3), SEGW(0, 1));
  constexpr unsigned long long T1 = pack8(SEGQ(1, 1, SP3, 16), SEGQ(0, 2, 0, SP4), SEGW(1, 1), SEGQ(0, 2, SP4, 16),
                                          SEGQ(1, 2, 0, 16), SEGW(0, 2), SEGQ(0, 3, 0, SP6), SEGW(1, 2));
  constexpr unsigned long long T2 = pack8(SEGQ(0, 3, SP6, 16), SEGQ(1, 3, 0, 16), SEGW(0, 3), SEGW(1, 3), 0, 0, 0, 0);
  return (int)(((sg < 8 ? T0 : (sg < 16 ? T1 : T2)) >> (8 * (sg & 7))) & 255ull);
}
__device__ __forceinline__ int q_first(int inst) { return (int)((pack8(0, 16, 48, 80, 112, 144, 176, 208) >> (8 * inst)) & 255ull); }
__device__ __forceinline__ int w_first(int inst) {
  return (int)((pack8(32, 48 + SP2, 80 + SP3, 112 + SP4, 160, 176 + SP6, 224, 240) >> (8 * inst)) & 255ull);
}
#define PREMASK 0x2Cu
#define PRE0 3
#define PRESH 2
__host__ __device__ constexpr int pre_idx(int kt) {
  const int d = kt - PRE0;
  return (d >= 0 && (d & ((1 << PRESH) - 1)) == 0 && (d >> PRESH) < 4) ? d >> PRESH : -1;
}
__device__ __forceinline__ bool w_pre(int inst) { return (PREMASK >> inst) & 1u; }
__device__ __forceinline__ int q_split(int inst) { return (int)(((0x40400044u | ((SP2 / 4) << 8) | ((SP3 / 4) << 12) | ((SP4 / 4) << 16) | ((SP6 / 4) << 24)) >> (4 * inst)) & 15u); }

__global__ void __launch_bounds__(512, 1) fused_kernel(const __grid_constant__ Params P) {
  extern __shared__ __align__(1024) uint8_t smem_raw[];
  constexpr uint32_t base = SBASE, bars = base + OFF_BAR, slots = base + OFF_SLOT;
  if (smem_u32(smem_raw) != base) __trap();
  const int warp = __shfl_sync(0xffffffffu, threadIdx.x >> 5, 0), lane = threadIdx.x & 31;
  const int b = blockIdx.x;
#define QS 0
#define WS 1
  const int qr = ((b & ((8 << QS) - 1)) >> QS) ^ (((b >> (3 + QS)) & 1) * 7);
  const int hp = ((b >> (3 + QS)) << QS) + (b & ((1 << QS) - 1));
  const int rt = ((b & ((16 << WS) - 1)) >> WS) ^ (((b >> (4 + WS)) & 1) * 15);
  const int ct = ((b >> (4 + WS)) << WS) + (b & ((1 << WS) - 1));

  if (warp == 12) {
    if (elect_one()) {
#pragma unroll
      for (int s = 0; s < 8; s++) {
        mbar_init(bars + 8u * (B_FULL + s), 2);
        mbar_init(bars + 8u * (B_EMPTY + s), 4);
      }
      mbar_init(bars + 8u * B_GO, 1);
      fence_barrier_init();
    }
    __syncwarp();
    named_bar_arrive(0, 512);
  }
  if (threadIdx.x == 0) {
    mbar_init(bars + 8u * B_PREP, 1);
    mbar_init(bars + 8u * (B_PREP + 1), 1);
    for (int s = 0; s < 4; s++) mbar_init(bars + 8u * (B_HALO + s), 1);
    for (int s = 0; s < 3; s++) mbar_init(bars + 8u * (B_REL + s), 8);
    mbar_init(bars + 8u * B_AFREE, 2);
    mbar_init(bars + 8u * B_TURN, 4);
    mbar_init(bars + 8u * (B_TURN + 1), 4);
    mbar_init(bars + 8u * B_CS, 1);
    mbar_init(bars + 8u * B_PRE, 1);
    mbar_init(bars + 8u * B_RESF, 1);
    mbar_init(bars + 8u * B_RESE, 4);
    mbar_init(bars + 8u * B_CSD, 4);
    mbar_init(bars + 8u * B_XRDY, 1);
    mbar_init(bars + 8u * (B_XRDY + 1), 1);
    fence_barrier_init();
  }
  if (warp != 12) named_bar_sync(0, 512);

  if (warp >= 12) {
    setmaxnreg_dec<32>();
    if (warp <= 13) {
      const bool act = warp == 13;
      uint32_t q = 4, dl = 0;
      bool prevw = false;
      unsigned ep1 = 0;
      if (act) {
        mbar_wait(bars + 8u * B_GO, 0);
        ep1 = __shfl_sync(0xffffffffu, (*(volatile unsigned*)(g_flags + F_DONE)) / NCTA + 1u, 0);
      } else {
#pragma unroll 1
        for (int s = 0; s < 16; s++) {
          const uint32_t fb = bars + 8u * (B_FULL + (s & 7)), sa = base + (s & 3) * 5 * UNIT;
          if (s >= 4) mbar_wait(bars + 8u * (B_EMPTY + ((s - 4) & 7)), ((s - 4) >> 3) & 1);
          if (elect_one()) {
            mbar_expect_tx(fb, 5 * UNIT);
            mbar_arrive(fb);
            tma_load_3d(sa, &P.xq[0], fb, 0, qr * 128, s);
            tma_load_3d(sa + 2 * UNIT, &P.wqkv[0], fb, hp * 64, s * 64, 0);
          }
        }
        if (elect_one()) mbar_arrive(bars + 8u * B_GO);
      }
      auto rbar = [&](int b0, int c) { return bars + 8u * b0 + ((8u * (c & 7)) ^ ((q & 1u) << 5)); };
      auto rpar = [&](int c) { return ((q + (c >> 2)) >> 1) & 1u; };
#pragma unroll 1
      for (int sg = 1; sg < NSEG; sg++) {
        const int code = seg_code(sg);
        const int L = (code >> 2) & 3, ch = code & 1;
        uint32_t seen = act ? 0u : 0xFFFFu;
        if ((code & 2) == 0) {
          const CUtensorMap* map = act ? &P.xq[L == 0 ? 0 : 1] : &P.wqkv[L & 1];
          if (act && (L == 0 || __any_sync(0xffffffffu, mbar_test(bars + 8u * (B_XRDY + ch), (L & 1) ^ 1)))) {
            seen = 0xFFFFu;
            fence_proxy_async_all();
          }
          const int k1 = ((code >> 4) & 12) + 4;
#pragma unroll 1
          for (int k4 = (code >> 2) & 12; k4 < k1; k4 += 4, q++) {
#pragma unroll
            for (int ks = 0; ks < 4; ks++) {
              const int kt = k4 + ks;
              if ((ks & 1) == 0)
                wait_mask<false>(g_flags + F_X + (ch * 8 + qr) * XSTR, 8, 6u * ep1 - 6u + 2u * L, 1u << (kt >> 1), seen, lane);
              if (ks == 0 && prevw) mbar_wait(rbar(B_EMPTY, -5), rpar(-5));
              else mbar_wait(rbar(B_EMPTY, ks - 4), rpar(-4));
              if (ks == 3 && prevw && !act) mbar_wait(bars + 8u * B_RESE, dl == 0 ? 1u : 0u);
              if (elect_one()) {
                mbar_expect_tx(rbar(B_FULL, ks), act ? 2 * UNIT : 3 * UNIT);
                tma_load_3d(base + ks * 5 * UNIT + (act ? 0 : 2 * UNIT) + (ks < 2 ? dl : 0u - dl), map, rbar(B_FULL, ks),
                            act ? 0 : hp * 64, act ? ch * 1024 + qr * 128 : kt * 64, act ? kt : 0);
              }
            }
            prevw = false;
          }
        } else {
          const CUtensorMap* map = act ? &P.o : &P.wo[L & 1];
          const bool pre = !act && w_pre(2 * L + ch);
          const int m0 = ch * 1024 + rt * 64;
#pragma unroll
          for (int kt = 0; kt < 16; kt++) {
            if (kt == 0 || kt == 1 || kt == 4 || kt == 8)
              wait_mask<false>(g_flags + F_O + (ch * 16 + rt) * OSTR, 16, 4u * ep1 - 3u + L,
                               kt == 0 ? 1u : (kt == 1 ? 0xEu : (kt == 4 ? 0xF0u : 0xFF00u)), seen, lane);
            if (kt < 4 && !prevw) mbar_wait(rbar(B_EMPTY, kt - 4 - (kt >> 1)), rpar(-4));
            else mbar_wait(rbar(B_EMPTY, kt - 6), rpar(kt - 6));
            if (kt == 6 && prevw && !act) mbar_wait(bars + 8u * B_RESE, dl == 0 ? 1u : 0u);
            if (elect_one()) {
              if (pre_idx(kt) >= 0 && pre) {
                mbar_arrive(rbar(B_FULL, kt));
              } else {
                mbar_expect_tx(rbar(B_FULL, kt), act ? UNIT : 2 * UNIT);
                const uint32_t da = base + w_ua(kt) * UNIT + (w_ua(kt) < 10 ? dl : 0u - dl);
                const uint32_t db = base + w_ub(kt) * UNIT + (w_ub(kt) < 10 ? dl : 0u - dl);
                tma_load_3d(act ? da : db, map, rbar(B_FULL, kt), 0, act ? m0 : kt * 64, act ? kt : ct * 2);
              }
            }
          }
          if (act && elect_one()) {
            mbar_expect_tx(bars + 8u * B_RESF, 2 * UNIT);
            tma_load_3d(base + 8 * UNIT + dl, &P.xr[L == 0 ? 0 : 1], bars + 8u * B_RESF, 0, m0, ct * 2);
          }
          q += 4;
          dl ^= 10u * UNIT;
          prevw = true;
        }
      }
    } else if (warp == 14) {
      const unsigned ep1 = (*(volatile unsigned*)(g_flags + F_DONE)) / NCTA + 1u;
#pragma unroll 1
      for (int inst = 0; inst < 8; inst++) {
        const int L = inst >> 1, ch = inst & 1, gb = ch * 8 + qr;
        unsigned* kvf = g_flags + F_KV;
        const unsigned kvt = 4u * ep1 - 3u + L, kvt0 = 2u * ep1 - 1u + (L >> 1);
        if (L & 1) {
          named_bar_sync(3, 192);
          named_bar_arrive(7, 160);
        } else {
          named_bar_arrive(3, 192);
          named_bar_sync(7, 160);
        }
        STA(34);
        if (elect_one()) {
          const unsigned* nf = kvf + ((gb - 1) * 16 + hp) * KSTR;
          if ((L & 1) == 0) {
            bulk_store(g_kvA[L >> 1][gb][hp][0], slots, 16384);
            bulk_commit();
            const uint32_t parA = ((L >> 1) * 2 + ch) & 1;
            const uint8_t* s1 = gb >= 1 ? g_kvA[L >> 1][gb - 1][hp][0] : g_zero;
            bool got = gb == 0;
#pragma unroll 1
            for (int it = 0; it < HPOLL && !got; it++) got = (int)(ld_acquire_u32(nf) - kvt) >= 0;
#pragma unroll 1
            for (int ph = 0; ph < 2; ph++) {
              if (got == (ph == 0)) {
                if (!got) wait_ge(nf, kvt);
                fence_proxy_async_all();
                STA(36);
                mbar_expect_tx(bars + 8u * B_HALO, 16384);
                bulk_load(slots + 2 * 16384, gb >= 1 ? s1 + 16384 : s1, 16384, bars + 8u * B_HALO);
              } else {
                bulk_wait0();
                fence_proxy_async_all();
                red_relaxed_add(kvf + (gb * 16 + hp) * KSTR + 1, 1u);
                STA(35);
              }
            }
            if (gb >= 1) {
              wait_ge(nf + 1, kvt0);
              fence_proxy_async_all();
            }
            STA(37);
            mbar_wait_lazy<100>(bars + 8u * B_REL, parA);
            STA(38);
            mbar_expect_tx(bars + 8u * (B_HALO + 1), 16384);
            bulk_load(slots + 16384, s1, 16384, bars + 8u * (B_HALO + 1));
            if (gb >= 2) {
              wait_ge2(kvf + ((gb - 2) * 16 + hp) * KSTR, kvt, kvt0);
              fence_proxy_async_all();
            }
            const uint8_t* s2 = gb >= 2 ? g_kvA[L >> 1][gb - 2][hp][0] : g_zero;
            STA(39);
            mbar_wait_lazy<100>(bars + 8u * (B_REL + 1), parA);
            STA(40);
            mbar_expect_tx(bars + 8u * (B_HALO + 2), 16384);
            bulk_load(slots, gb >= 2 ? s2 + 16384 : s2, 16384, bars + 8u * (B_HALO + 2));
            mbar_wait_lazy<100>(bars + 8u * (B_REL + 2), parA);
            STA(41);
            mbar_expect_tx(bars + 8u * (B_HALO + 3), 16384);
            bulk_load(slots + 2 * 16384, s2, 16384, bars + 8u * (B_HALO + 3));
          } else {
            const uint8_t* s1 = gb >= 1 ? g_kvB[L >> 1][gb - 1][hp] : g_zero;
            if (gb >= 1) {
              wait_ge(nf, kvt);
              fence_proxy_async_all();
            }
            mbar_expect_tx(bars + 8u * B_HALO, 4096);
            bulk_load(KB_ROW0 - 2048, s1, 2048, bars + 8u * B_HALO);
            bulk_load(VB_ROW0 - 2048, s1 + 2048, 2048, bars + 8u * B_HALO);
          }
          if (w_pre(inst)) {
            mbar_wait(bars + 8u * B_AFREE, (inst & 1) ^ 1);
            if (inst == 1) mbar_wait(bars + 8u * B_CSD, 0);
            mbar_expect_tx(bars + 8u * B_PRE, 8 * UNIT);
#pragma unroll 1
            for (int j = 0; j < 4; j++) {
              tma_load_3d(slots + j * 2 * UNIT, &P.wo[L & 1], bars + 8u * B_PRE, 0, (PRE0 + (j << PRESH)) * 64, ct * 2);
              __nanosleep(200);
            }
          }
        }
        __syncwarp();
      }
    } else {
      const unsigned ep1 = (*(volatile unsigned*)(g_flags + F_DONE)) / NCTA + 1u;
      mbar_wait(bars + 8u * B_GO, 0);
#pragma unroll 1
      for (int i = 0; i < 20; i++) {
        const char* src = i < 4 ? reinterpret_cast<const char*>(P.wo_p[0]) + (size_t)b * 16384 + i * 4096
                                : (i < 16 ? reinterpret_cast<const char*>(P.wqkv_p[1]) + (size_t)b * 49152 + (i - 4) * 4096
                                          : reinterpret_cast<const char*>(P.wo_p[1]) + (size_t)b * 16384 + (i - 16) * 4096);
        asm volatile("prefetch.global.L2 [%0];" ::"l"(src + lane * 128));
        __nanosleep(TRICKLE);
      }
#pragma unroll 1
      for (int inst = 2; inst < 8; inst++) {
        const int L = inst >> 1, ch = inst & 1, gb = ch * 8 + qr;
        uint32_t seen = 0;
        wait_mask<true>(g_flags + F_X + gb * XSTR, 8, 6u * ep1 - 6u + 2u * L, 0xFFu, seen, lane);
        if (lane == 0) mbar_arrive(bars + 8u * (B_XRDY + ch));
#pragma unroll 1
        for (int h = 0; h < 4; h++) {
          const float4* sp = &g_stats[L][0][gb * 128 + h * 32 + lane];
          const float4 s0 = sum_recs<4>(sp, S_LEN, ep1), s1 = sum_recs<4>(sp + 4 * S_LEN, S_LEN, ep1);
          sts32(base + OFF_RS + (ch * 128 + h * 32 + lane) * 4, ln_params(s0.x + s1.x, s0.y + s1.y));
        }
        if (inst == 2) {
          mbar_wait(bars + 8u * B_CSD, 0);
#pragma unroll 1
          for (int hf = 0; hf < 2; hf++) {
            const float4* cp = &g_cs[1][hp][0][hf * 32 + lane];
            const float4 s0 = sum_recs<4>(cp, 64, ep1), s1 = sum_recs<4>(cp + 4 * 64, 64, ep1);
            const uint32_t ca = base + OFF_CS + (192 + cs_pos(hf * 32 + lane)) * 4;
            sts32(ca, __float_as_uint(s0.x + s1.x));
            sts32(ca + 256, __float_as_uint(s0.y + s1.y));
            sts32(ca + 512, __float_as_uint(s0.z + s1.z));
          }
        }
        __syncwarp();
        if (lane == 0) mbar_arrive(bars + 8u * (B_PREP + ch));
      }
    }
  } else {
    const bool asst = warp >= 8;
    const bool lane0 = lane == 0;
    uint32_t tpar = 0;
    GTL(0);
    if (asst) {
      colsum_part(&P.wqkv[0], 0, qr, hp);
      if ((threadIdx.x & 127) < 2) mbar_arrive(bars + 8u * B_AFREE);
    } else if (warp >= 4) {
      PHASE_IDS
      {
        const unsigned ep1 = (*(volatile unsigned*)(g_flags + F_DONE)) / NCTA + 1u;
        const int row = b * 16 + (tid >> 3);
        const uint4* src = reinterpret_cast<const uint4*>(P.in_x + (size_t)row * DM) + (tid & 7);
        float s1 = 0.f, s2 = 0.f;
#pragma unroll 1
        for (int k = 0; k < 4; k++) {
          mbar_pace(bars + 8u * (B_EMPTY + 2 * k), 0);
          uint4 v[4];
#pragma unroll
          for (int j = 0; j < 4; j++) v[j] = __ldg(src + (k * 4 + j) * 8);
#pragma unroll
          for (int j = 0; j < 4; j++) {
            const uint32_t w[4] = {v[j].x, v[j].y, v[j].z, v[j].w};
#pragma unroll
            for (int e = 0; e < 4; e++) {
              const float x0 = bf_lo(w[e]), x1 = bf_hi(w[e]);
              s1 += x0 + x1;
              s2 = fmaf(x0, x0, fmaf(x1, x1, s2));
            }
          }
        }
#pragma unroll
        for (int o = 1; o < 8; o <<= 1) {
          s1 += __shfl_xor_sync(0xffffffffu, s1, o);
          s2 += __shfl_xor_sync(0xffffffffu, s2, o);
        }
        if ((tid & 7) == 0) st_rec(&g_stats[0][0][row], s1, s2, 0.f, ep1);
        if (tid == 0) sts32(base + OFF_EPOCH, ep1);
        if (tid < 64) {
          const float4 s0 = sum_recs<8>(&g_cs[0][hp][0][tid], 64, ep1);
          sts32(base + OFF_CS + cs_pos(tid) * 4, __float_as_uint(s0.x));
          sts32(base + OFF_CS + cs_pos(tid) * 4 + 256, __float_as_uint(s0.y));
          sts32(base + OFF_CS + cs_pos(tid) * 4 + 512, __float_as_uint(s0.z));
        }
#pragma unroll 1
        for (int cc = 0; cc < 2; cc++) {
          const float4 s0 = sum_recs<1>(&g_stats[0][0][(cc * 8 + qr) * 128 + tid], 0, ep1);
          sts32(base + OFF_RS + (cc * 128 + tid) * 4, ln_params(s0.x, s0.y));
        }
        named_bar_sync(2, 128);
        if (tid < 2) mbar_arrive(bars + 8u * (B_PREP + tid));
      }
    }
#pragma unroll 1
    for (int inst = asst ? 0 : warp >> 2; inst < 8; inst += asst ? 1 : 2) {
      const int L = inst >> 1, ch = inst & 1, gb = ch * 8 + qr;
      if (asst) {
        setmaxnreg_dec<24>();
        if (warp == 8) {
          named_bar_sync(3, 192);
          STA(32);
          if (elect_one()) {
            if ((L & 1) == 0) {
              bulk_store(g_kvA[L >> 1][gb][hp][1], slots + 16384, 16384);
            } else {
              bulk_store(g_kvB[L >> 1][gb][hp], KB_ROW0 + 112 * 128, 2048);
              bulk_store(g_kvB[L >> 1][gb][hp] + 2048, VB_ROW0 + 112 * 128, 2048);
            }
            bulk_commit();
            bulk_wait0();
            fence_proxy_async_all();
            red_relaxed_add(g_flags + F_KV + (gb * 16 + hp) * KSTR, 1u);
            STA(33);
          }
          __syncwarp();
        }
        named_bar_sync(4, 256);
        setmaxnreg_inc<128>();
      } else {
      setmaxnreg_inc<224>();
      {
        float acc[2][96];
        const int ksp = q_split(inst);
        int n = q_first(inst);
        uint32_t dlt = (ch == 0 && L > 0) ? 10u * (UNIT >> 4) : 0u;
        if (inst != 0 && inst != 2 && inst != 6) {
          mbar_wait_lazy<100>(bars + 8u * (B_TURN + ch), tpar);
          tpar ^= 1u;
        }
        if (L == 3) GTL(37);
        mbar_wait(bars + 8u * (B_FULL + (n & 7)), (n >> 3) & 1);
        GTL(1 + L * 8);
        {
          const uint32_t da = (base >> 4) + 0x10000u + dlt;
          const uint64_t db = desc_lo(da - 0x10000u + ((UNIT >> 4) << 16) + 2 * (UNIT >> 4));
          wgmma_fence();
          wgmma_n192_ssz_ta0_tb1(acc[0], desc_lo(da), db);
          wgmma_commit();
          wgmma_n192_ssz_ta0_tb1(acc[1], desc_lo(da + (UNIT >> 4)), db);
          wgmma_commit();
        }
#pragma unroll 1
        for (int k4 = 0; k4 < 4; k4++) {
          const bool brk = k4 + 1 == ksp && k4 < 3;
#pragma unroll
          for (int ks = 0; ks < 4; ks++, n++) {
            STAMP(inst == KSQ, k4 * 4 + ks);
            const uint32_t da = ((base + ks * 5 * UNIT) >> 4) + 0x10000u + (ks < 2 ? dlt : 0u - dlt);
            const uint32_t dbb = da - 0x10000u + ((UNIT >> 4) << 16) + 2 * (UNIT >> 4);
#pragma unroll
            for (int k16 = 0; k16 < 4; k16++) {
              if (ks == 0 && k16 == 0 && k4 == 0) continue;
              const uint64_t db = desc_lo(dbb + k16 * 128);
              wgmma_fence();
              wgmma_n192_ss_ta0_tb1(acc[0], desc_lo(da + k16 * 2), db, 1);
              wgmma_commit();
              wgmma_wait<1>();
              if (k16 == 0 && lane0 && (ks != 0 || k4 != ksp)) mbar_arrive(bars + 8u * (B_EMPTY + ((n - 1) & 7)));
              wgmma_fence();
              wgmma_n192_ss_ta0_tb1(acc[1], desc_lo(da + (UNIT >> 4) + k16 * 2), db, 1);
              wgmma_commit();
              bool ok = true;
              if (k16 == 2) ok = mbar_test(bars + 8u * (B_FULL + ((n + 1) & 7)), ((n + 1) >> 3) & 1) || (ks == 3 && (k4 == 3 || brk));
              if (k16 == QTURN && ks == 3 && (k4 == 3 || brk) && lane0) mbar_arrive(bars + 8u * (B_TURN + (ch ^ 1)));
              if (ks < 3 || k16 < 3) wgmma_wait<1>();
              if (k16 == 2 && !ok) mbar_wait(bars + 8u * (B_FULL + ((n + 1) & 7)), ((n + 1) >> 3) & 1);
            }
          }
          if (brk) {
            wgmma_wait<0>();
            if (lane0) mbar_arrive(bars + 8u * (B_EMPTY + ((n - 1) & 7)));
            n += 16;
            dlt ^= 10u * (UNIT >> 4);
            mbar_wait_lazy<100>(bars + 8u * (B_TURN + ch), tpar);
            tpar ^= 1u;
            STAMP(inst == KSQ, 17);
            mbar_wait(bars + 8u * (B_FULL + (n & 7)), (n >> 3) & 1);
          }
        }
        PHASE_IDS
        mbar_wait(bars + 8u * (B_PREP + ch), L & 1);
        const bool afree = mbar_test(bars + 8u * B_AFREE, inst & 1);
        float nmean[2][2], rinv[2][2];
        const uint32_t csa = base + OFF_CS + ((L & 1) * 192 + 4 * c) * 4;
        uint4 cs[20];
        {
          uint32_t v[4];
#pragma unroll
          for (int i = 0; i < 4; i++)
            v[i] = lds32(base + OFF_RS + (ch * 128 + (i >> 1) * 64 + wwarp * 16 + g + 8 * (i & 1)) * 4);
#pragma unroll
          for (int t = 0; t < 2; t++) cs[t] = lds128(csa + (t + 4) * 64);
#pragma unroll
          for (int i = 0; i < 4; i++) {
            nmean[i >> 1][i & 1] = -bf_lo(v[i]);
            rinv[i >> 1][i & 1] = rcp_fast(bf_hi(v[i]));
            asm volatile("" : "+f"(rinv[i >> 1][i & 1]), "+f"(nmean[i >> 1][i & 1]));
          }
        }
        const int mat = lane >> 3;
        const uint32_t soff = (wwarp * 16 + (mat & 1) * 8 + (lane & 7)) * 128;
        const uint32_t kdst = ((L & 1) ? KB_ROW0 : slots) + soff, vdst = ((L & 1) ? VB_ROW0 : slots + 8192) + soff;
        const uint32_t hs = (L & 1) ? 8192 : 16384;
        const int rg = 2 * wwarp + (mat & 1);
        const uint32_t qdst = slots + 3 * 16384 + ((L & 1) ? soff : ((rg < 4 ? 2 * rg : 15 - 2 * rg) * 8 + (lane & 7)) * 128);
        wgmma_wait<0>();
        reg_fence<96>(acc[0]);
        reg_fence<96>(acc[1]);
        if (lane0) mbar_arrive(bars + 8u * (B_EMPTY + ((n - 1) & 7)));
        STAMP(inst == KSQ, 16);
        GTL(2 + L * 8);
        if (!afree) mbar_wait(bars + 8u * B_AFREE, inst & 1);
#pragma unroll
        for (int t = 2; t < CSPF; t++) cs[t] = lds128(csa + (t + 4) * 64);
#pragma unroll
        for (int t = 0; t < 20; t++) {
          const int p = t >= 16 ? 0 : ((t >> 2) & 1) + 1, jp = t & 3;
          if (t + CSPF < 20) {
            const int tn = t + CSPF, jn = tn >= 16 ? tn - 16 : (tn & 7) + 4;
            cs[tn] = lds128(csa + jn * 64);
          }
          if (t == 16) {
#pragma unroll
            for (int i = 0; i < 4; i++) rinv[i >> 1][i & 1] *= SM_C;
          }
          const int j = p * 8 + 2 * jp;
          const float2 cs0 = make_float2(__uint_as_float(cs[t].x), __uint_as_float(cs[t].y));
          const float2 cs1 = make_float2(__uint_as_float(cs[t].z), __uint_as_float(cs[t].w));
          const uint32_t sw = ((2 * jp + (mat >> 1)) ^ (lane & 7)) << 4;
#pragma unroll
          for (int h = 0; h < 2; h++) {
            if (t < 16 && h != (t < 8 ? 1 : 0)) continue;
            const float* a = &acc[h][4 * j];
            const uint32_t r0 = pack_bf16x2(fmaf(nmean[h][0], cs0.x, a[0]) * rinv[h][0], fmaf(nmean[h][0], cs0.y, a[1]) * rinv[h][0]);
            const uint32_t r1 = pack_bf16x2(fmaf(nmean[h][1], cs0.x, a[2]) * rinv[h][1], fmaf(nmean[h][1], cs0.y, a[3]) * rinv[h][1]);
            const uint32_t r2 = pack_bf16x2(fmaf(nmean[h][0], cs1.x, a[4]) * rinv[h][0], fmaf(nmean[h][0], cs1.y, a[5]) * rinv[h][0]);
            const uint32_t r3 = pack_bf16x2(fmaf(nmean[h][1], cs1.x, a[6]) * rinv[h][1], fmaf(nmean[h][1], cs1.y, a[7]) * rinv[h][1]);
            const uint32_t dst = p == 0 ? qdst + h * 8192 : (p == 1 ? kdst : vdst) + h * hs;
            stmatrix_x4(dst + sw, r0, r1, r2, r3);
          }
          if (t == 7 || t == 15) {
            fence_proxy_async_smem();
            named_bar_arrive(t == 7 ? 3 : 7, t == 7 ? 192 : 160);
          }
        }
      }
      fence_proxy_async_smem();
      setmaxnreg_dec<128>();
      named_bar_sync(4, 256);
      }
      GTL(3 + L * 8);
      {
        PHASE_IDS
        if ((L & 1) == 0) attention_a(asst, L, gb, hp, inst & 1, ch, (tid_ >> 5) & 3, lane, P.zero);
        else attention_b(asst, gb, inst & 1, wwarp, lane);
        GTL(4 + L * 8);
        fence_proxy_async_smem();
      }
      if (asst) {
        named_bar_arrive(5, 256);
        if (inst == 1) {
          mbar_wait(bars + 8u * B_AFREE, 0);
          colsum_part(&P.wqkv[1], 1, qr, hp);
          if (lane0) mbar_arrive(bars + 8u * B_CSD);
        }
        continue;
      }
      {
        named_bar_sync(5, 256);
        const int wwarp = warp & 3;
        if (wwarp < 2 && elect_one()) {
          tma_store_3d(&P.o, ((L & 1) ? slots + 3 * 16384 : OA_TILE) + wwarp * 8192, 0, gb * 128 + wwarp * 64, hp);
          bulk_commit();
          bulk_wait0();
          mbar_arrive(bars + 8u * B_AFREE);
          fence_proxy_async_all();
          red_relaxed_add(g_flags + F_O + (gb * 2 + wwarp) * OSTR + hp, 1u);
        }
        __syncwarp();
      }
      GTL(5 + L * 8);

      {
        float acc[64];
        const int n0 = w_first(inst);
        const bool pre = w_pre(inst);
        const uint32_t dl = ch * 10u * (UNIT >> 4);
        mbar_wait_lazy<100>(bars + 8u * (B_TURN + ch), tpar);
        tpar ^= 1u;
        mbar_wait(bars + 8u * (B_FULL + (n0 & 7)), (n0 >> 3) & 1);
        GTL(6 + L * 8);
#pragma unroll
        for (int kt = 0; kt < 16; kt++) {
          const int n = n0 + kt;
          STAMP(inst == KSW, 20 + kt);
          const uint32_t da = ((base + w_ua(kt) * UNIT) >> 4) + 0x10000u + (w_ua(kt) < 10 ? dl : 0u - dl);
          uint32_t db = ((base + w_ub(kt) * UNIT) >> 4) + ((UNIT >> 4) << 16) + (w_ub(kt) < 10 ? dl : 0u - dl);
          if (pre_idx(kt) >= 0 && pre) db = ((slots + pre_idx(kt) * 2 * UNIT) >> 4) + ((UNIT >> 4) << 16);
          if (kt == PRE0 && pre) mbar_wait(bars + 8u * B_PRE, __popc(PREMASK & ((1u << inst) - 1u)) & 1);
          if (kt == 15 && lane0 && (inst & 3) != 0) mbar_arrive(bars + 8u * (B_TURN + (ch ^ 1)));
          wgmma_fence();
          if (kt == 0) wgmma_n128_ssz_ta0_tb1(acc, desc_lo(da), desc_lo(db));
#pragma unroll
          for (int k16 = kt == 0 ? 1 : 0; k16 < 4; k16++) wgmma_n128_ss_ta0_tb1(acc, desc_lo(da + 2 * k16), desc_lo(db + 128 * k16), 1);
          wgmma_commit();
          const uint32_t nb = bars + 8u * (kt == 15 ? B_RESF : B_FULL + ((n + 1) & 7)), np = kt == 15 ? ch : ((n + 1) >> 3) & 1;
          const bool ok = mbar_test(nb, np);
          if (kt > 0) {
            wgmma_wait<1>();
            if (lane0) mbar_arrive(bars + 8u * (B_EMPTY + ((n - 1) & 7)));
          }
          if (!ok) mbar_wait(nb, np);
        }
        PHASE_IDS
        const uint32_t xb = base + (8 + ch * 10) * UNIT;
        const int mat = lane >> 3;
        const uint32_t xrow = xb + (wwarp * 16 + (mat & 1) * 8 + (lane & 7)) * 128;
        uint32_t xv[8][4];
#pragma unroll
        for (int jp = 0; jp < 8; jp++)
          ldmatrix_x4(xv[jp], xrow + (jp >> 2) * UNIT + (((2 * (jp & 3) + (mat >> 1)) ^ (lane & 7)) << 4));
        wgmma_wait<0>();
        reg_fence<64>(acc);
        if (lane0) mbar_arrive(bars + 8u * (B_EMPTY + ((n0 + 15) & 7)));
        STAMP(inst == KSW, 36);
        GTL(7 + L * 8);
#pragma unroll
        for (int jp = 0; jp < 8; jp++) {
#pragma unroll
          for (int q = 0; q < 4; q++) xv[jp][q] = add_bf16x2(xv[jp][q], pack_bf16x2(acc[8 * jp + 2 * q], acc[8 * jp + 2 * q + 1]));
          stmatrix_x4(xrow + (jp >> 2) * UNIT + (((2 * (jp & 3) + (mat >> 1)) ^ (lane & 7)) << 4), xv[jp][0], xv[jp][1],
                      xv[jp][2], xv[jp][3]);
        }
        fence_proxy_async_smem();
        named_bar_sync(1 + ch, 128);
        const int grow = ch * 1024 + rt * 64;
        if (wwarp == 0) {
          if (elect_one()) {
            tma_store_3d(&P.xr[L == 3 ? 2 : 1], xb, 0, grow, ct * 2);
            bulk_commit();
            bulk_wait_read0();
            mbar_arrive(bars + 8u * B_RESE);
            bulk_wait0();
            TGET(t35);
            fence_proxy_async_all();
            if (L < 3) red_relaxed_add(g_flags + F_X + (ch * 8 + (rt >> 1)) * XSTR + ct, 1u);
            if (L == 2) TPUT(ch, 35, t35);
          }
          __syncwarp();
        } else if (lane == 0) {
          mbar_arrive(bars + 8u * B_RESE);
        }
        if (L < 3) {
          const unsigned ep1 = lds32(base + OFF_EPOCH);
          float s1[2] = {0.f, 0.f}, s2[2] = {0.f, 0.f};
#pragma unroll
          for (int jp = 0; jp < 8; jp++)
#pragma unroll
            for (int q = 0; q < 4; q++) {
              const float x0 = bf_lo(xv[jp][q]), x1 = bf_hi(xv[jp][q]);
              s1[q & 1] += x0 + x1;
              s2[q & 1] = fmaf(x0, x0, fmaf(x1, x1, s2[q & 1]));
            }
#pragma unroll
          for (int r = 0; r < 2; r++) {
            s1[r] += __shfl_xor_sync(0xffffffffu, s1[r], 1);
            s2[r] += __shfl_xor_sync(0xffffffffu, s2[r], 1);
            s1[r] += __shfl_xor_sync(0xffffffffu, s1[r], 2);
            s2[r] += __shfl_xor_sync(0xffffffffu, s2[r], 2);
            if (c == 0) st_rec(&g_stats[L + 1][ct][grow + wwarp * 16 + g + 8 * r], s1[r], s2[r], 0.f, ep1);
          }
        }
        GTL(8 + L * 8);
      }
    }
    if (threadIdx.x == 128) atomicAdd(g_flags + F_DONE, 1u);
  }
}

typedef CUresult (*PFN_tmEncode)(CUtensorMap*, CUtensorMapDataType, cuuint32_t, void*, const cuuint64_t*,
                                 const cuuint64_t*, const cuuint32_t*, const cuuint32_t*, CUtensorMapInterleave,
                                 CUtensorMapSwizzle, CUtensorMapL2promotion, CUtensorMapFloatOOBfill);

PFN_tmEncode get_encode_fn() {
  static PFN_tmEncode fn = nullptr;
  if (!fn) {
    cudaDriverEntryPointQueryResult qr;
    void* p = nullptr;
    cudaGetDriverEntryPoint("cuTensorMapEncodeTiled", &p, cudaEnableDefault, &qr);
    fn = (PFN_tmEncode)p;
  }
  return fn;
}

CUtensorMap make_map(const void* ptr, int rows, int cols, int inner, int box_rows, int box_blk) {
  CUtensorMap m;
  cuuint64_t gdim[3] = {(cuuint64_t)inner, (cuuint64_t)rows, (cuuint64_t)(cols / inner)};
  cuuint64_t gstr[2] = {(cuuint64_t)cols * 2, (cuuint64_t)inner * 2};
  cuuint32_t box[3] = {64, (cuuint32_t)box_rows, (cuuint32_t)box_blk};
  cuuint32_t estr[3] = {1, 1, 1};
  get_encode_fn()(&m, CU_TENSOR_MAP_DATA_TYPE_BFLOAT16, 3, const_cast<void*>(ptr), gdim, gstr, box, estr,
                  CU_TENSOR_MAP_INTERLEAVE_NONE, CU_TENSOR_MAP_SWIZZLE_128B, CU_TENSOR_MAP_L2_PROMOTION_L2_128B,
                  CU_TENSOR_MAP_FLOAT_OOB_FILL_NONE);
  return m;
}

}

extern "C" void kernel_launch(void* const* d_in, const int* in_sizes, int n_in, void* d_out, int out_size) {
  (void)in_sizes; (void)n_in; (void)out_size;
  void *p_o, *p_x;
  cudaGetSymbolAddress(&p_o, g_o);
  cudaGetSymbolAddress(&p_x, g_x);
  static bool attr_done = false;
  if (!attr_done) {
    cudaFuncSetAttribute(fused_kernel, cudaFuncAttributeMaxDynamicSharedMemorySize, SMEM_BYTES);
    attr_done = true;
  }
  Params P;
  P.in_x = (const __nv_bfloat16*)d_in[0];
  P.wqkv_p[0] = (const __nv_bfloat16*)d_in[1];
  P.wo_p[0] = (const __nv_bfloat16*)d_in[2];
  P.wqkv_p[1] = (const __nv_bfloat16*)d_in[4];
  P.wo_p[1] = (const __nv_bfloat16*)d_in[5];
  P.out = (__nv_bfloat16*)d_out;
  P.zero = 0;
  P.xq[0] = make_map(P.in_x, S_LEN, DM, 64, 128, 1);
  P.xq[1] = make_map(p_x, S_LEN, DM, 64, 128, 1);
  P.xr[0] = make_map(P.in_x, S_LEN, DM, 64, 64, 2);
  P.xr[1] = make_map(p_x, S_LEN, DM, 64, 64, 2);
  P.xr[2] = make_map(d_out, S_LEN, DM, 64, 64, 2);
  P.o = make_map(p_o, S_LEN, DM, 64, 64, 1);
  for (int t = 0; t < 2; t++) {
    P.wqkv[t] = make_map(P.wqkv_p[t], DM, NQKV, 1024, 64, 3);
    P.wo[t] = make_map(P.wo_p[t], DM, DM, 64, 64, 2);
  }
  fused_kernel<<<NCTA, 512, SMEM_BYTES>>>(P);
}
```

```cpp
#include <cuda_runtime.h>
#include <cuda_bf16.h>
#include <cuda.h>
#include <stdint.h>

namespace {

constexpr int S_LEN = 2048;
constexpr int DM = 1024;
constexpr int NQKV = 3072;
constexpr int NCTA = 128;

__device__ __align__(1024) uint8_t g_kvA[2][16][16][2][16384];
__device__ __align__(1024) uint8_t g_kvB[2][16][16][4096];
__device__ __align__(1024) uint8_t g_zero[16384];
__device__ __align__(1024) __nv_bfloat16 g_o[S_LEN * DM];
__device__ __align__(1024) __nv_bfloat16 g_x[S_LEN * DM];
__device__ __align__(1024) float4 g_stats[4][8][S_LEN];
__device__ __align__(1024) float4 g_cs[2][16][8][64];
constexpr int F_X = 0;
constexpr int XSTR = 32, OSTR = 32, KSTR = 32;
constexpr int F_O = F_X + 16 * XSTR;
constexpr int F_KV = F_O + 32 * OSTR;
constexpr int F_DONE = F_KV + 256 * KSTR;
__device__ __align__(1024) unsigned g_flags[F_DONE + 32];

constexpr uint32_t SBASE = 1024;
constexpr int UNIT = 8192;
constexpr int NUNITS = 20;
constexpr int OFF_SLOT = NUNITS * UNIT;
constexpr int OFF_BAR = OFF_SLOT + 4 * 16384;
constexpr int OFF_EPOCH = OFF_BAR + 296;
constexpr int OFF_CS = OFF_BAR + 304;
constexpr int OFF_RS = OFF_CS + 1536;
constexpr int OFF_TS = OFF_RS + 1024;
constexpr int SMEM_BYTES = OFF_RS + 1024;
constexpr int B_FULL = 0, B_EMPTY = 8, B_PREP = 16, B_HALO = 18, B_REL = 22, B_AFREE = 25, B_TURN = 26, B_XRDY = 28,
              B_CS = 30, B_CSD = 31, B_GO = 32, B_PRE = 33, B_RESF = 34, B_RESE = 35;

__device__ __forceinline__ uint32_t smem_u32(const void* p) { return (uint32_t)__cvta_generic_to_shared(p); }

__device__ __forceinline__ void mbar_init(uint32_t bar, uint32_t cnt) {
  asm volatile("mbarrier.init.shared::cta.b64 [%0], %1;" ::"r"(bar), "r"(cnt));
}
__device__ __forceinline__ void mbar_expect_tx(uint32_t bar, uint32_t bytes) {
  asm volatile("mbarrier.arrive.expect_tx.shared::cta.b64 _, [%0], %1;" ::"r"(bar), "r"(bytes) : "memory");
}
__device__ __forceinline__ void mbar_arrive(uint32_t bar) {
  asm volatile("mbarrier.arrive.shared::cta.b64 _, [%0];" ::"r"(bar) : "memory");
}
__device__ __forceinline__ bool mbar_try_wait(uint32_t bar, uint32_t parity) {
  uint32_t ok;
  asm volatile(
      "{\n.reg .pred p;\nmbarrier.try_wait.parity.shared::cta.b64 p, [%1], %2;\nselp.b32 %0, 1, 0, p;\n}\n"
      : "=r"(ok)
      : "r"(bar), "r"(parity)
      : "memory");
  return ok != 0;
}
__device__ __forceinline__ bool mbar_test(uint32_t bar, uint32_t parity) {
  uint32_t ok;
  asm volatile(
      "{\n.reg .pred p;\nmbarrier.test_wait.parity.shared::cta.b64 p, [%1], %2;\nselp.b32 %0, 1, 0, p;\n}\n"
      : "=r"(ok)
      : "r"(bar), "r"(parity)
      : "memory");
  return ok != 0;
}
__device__ __forceinline__ void mbar_wait(uint32_t bar, uint32_t parity) {
#pragma unroll 1
  for (uint32_t it = 0; it < (1u << 18); ++it) {
    if (mbar_try_wait(bar, parity)) return;
  }
}
__device__ __forceinline__ void mbar_pace(uint32_t bar, uint32_t parity) {
#pragma unroll 1
  for (uint32_t it = 0; it < 24; ++it) {
    if (mbar_try_wait(bar, parity)) return;
  }
}
template <int NS>
__device__ __forceinline__ void mbar_wait_lazy(uint32_t bar, uint32_t parity) {
#pragma unroll 1
  for (uint32_t it = 0; it < (1u << 18); ++it) {
    if (mbar_try_wait(bar, parity)) return;
    __nanosleep(NS);
  }
}
__device__ __forceinline__ bool elect_one() {
  uint32_t ok;
  asm volatile("{\n.reg .pred p;\nelect.sync _|p, 0xffffffff;\nselp.b32 %0, 1, 0, p;\n}\n" : "=r"(ok));
  return ok != 0;
}
__device__ __forceinline__ void fence_barrier_init() { asm volatile("fence.mbarrier_init.release.cluster;" ::: "memory"); }
__device__ __forceinline__ void fence_proxy_async_smem() { asm volatile("fence.proxy.async.shared::cta;" ::: "memory"); }
__device__ __forceinline__ void fence_proxy_async_all() { asm volatile("fence.proxy.async.global;" ::: "memory"); }

__device__ __forceinline__ void tma_load_3d(uint32_t dst, const CUtensorMap* map, uint32_t bar, int c0, int c1, int c2) {
  asm volatile(
      "cp.async.bulk.tensor.3d.shared::cluster.global.mbarrier::complete_tx::bytes [%0], [%1, {%3, %4, %5}], [%2];" ::"r"(dst),
      "l"(map), "r"(bar), "r"(c0), "r"(c1), "r"(c2)
      : "memory");
}
__device__ __forceinline__ void bulk_load(uint32_t dst, const void* src, uint32_t bytes, uint32_t bar) {
  asm volatile("cp.async.bulk.shared::cluster.global.mbarrier::complete_tx::bytes [%0], [%1], %2, [%3];" ::"r"(dst),
               "l"(src), "r"(bytes), "r"(bar)
               : "memory");
}
__device__ __forceinline__ void bulk_store(void* dst, uint32_t src, uint32_t bytes) {
  asm volatile("cp.async.bulk.global.shared::cta.bulk_group [%0], [%1], %2;" ::"l"(dst), "r"(src), "r"(bytes) : "memory");
}
__device__ __forceinline__ void tma_store_3d(const CUtensorMap* map, uint32_t src, int c0, int c1, int c2) {
  asm volatile("cp.async.bulk.tensor.3d.global.shared::cta.bulk_group [%0, {%2, %3, %4}], [%1];" ::"l"(map), "r"(src),
               "r"(c0), "r"(c1), "r"(c2)
               : "memory");
}
__device__ __forceinline__ void bulk_commit() { asm volatile("cp.async.bulk.commit_group;" ::: "memory"); }
__device__ __forceinline__ void bulk_wait_read0() { asm volatile("cp.async.bulk.wait_group.read 0;" ::: "memory"); }
__device__ __forceinline__ void bulk_wait0() { asm volatile("cp.async.bulk.wait_group 0;" ::: "memory"); }
__device__ __forceinline__ void named_bar_sync(int id, int nthreads) {
  asm volatile("bar.sync %0, %1;" ::"r"(id), "r"(nthreads) : "memory");
}
__device__ __forceinline__ void named_bar_arrive(int id, int nthreads) {
  asm volatile("bar.arrive %0, %1;" ::"r"(id), "r"(nthreads) : "memory");
}

__device__ __forceinline__ void wgmma_fence() { asm volatile("wgmma.fence.sync.aligned;\n" ::: "memory"); }
__device__ __forceinline__ void wgmma_commit() { asm volatile("wgmma.commit_group.sync.aligned;\n" ::: "memory"); }
template <int N>
__device__ __forceinline__ void wgmma_wait() {
  asm volatile("wgmma.wait_group.sync.aligned %0;\n" ::"n"(N) : "memory");
}
template <int R>
__device__ __forceinline__ void setmaxnreg_inc() { asm volatile("setmaxnreg.inc.sync.aligned.u32 %0;\n" ::"n"(R)); }
template <int R>
__device__ __forceinline__ void setmaxnreg_dec() { asm volatile("setmaxnreg.dec.sync.aligned.u32 %0;\n" ::"n"(R)); }
template <int N>
__device__ __forceinline__ void reg_fence(float* r) {
#pragma unroll
  for (int i = 0; i < N; i++) asm volatile("" : "+f"(r[i])::"memory");
}

template <int N>
__device__ __forceinline__ void reg_define(float* r) {
#pragma unroll
  for (int i = 0; i < N; i++) r[i] = 0.f;
}

__device__ __forceinline__ uint64_t desc_lo(uint32_t lo) {
  uint64_t d;
  asm("mov.b64 %0, {%1, %2};" : "=l"(d) : "r"(lo), "r"(0x40000040u));
  return d;
}
__device__ __forceinline__ uint64_t make_desc(uint32_t addr, uint32_t lbo_bytes) {
  return desc_lo((addr >> 4) + ((lbo_bytes >> 4) << 16));
}

__device__ __forceinline__ void wgmma_n192_ss_ta0_tb1(float* d, uint64_t descA, uint64_t descB, int scaleD) {
  asm volatile("{\n.reg .pred p;\nsetp.ne.b32 p, %98, 0;\n"
    "wgmma.mma_async.sync.aligned.m64n192k16.f32.bf16.bf16 {%0, %1, %2, %3, %4, %5, %6, %7, %8, %9, %10, %11, %12, %13, %14, %15, %16, %17, %18, %19, %20, %21, %22, %23, %24, %25, %26, %27, %28, %29, %30, %31, %32, %33, %34, %35, %36, %37, %38, %39, %40, %41, %42, %43, %44, %45, %46, %47, %48, %49, %50, %51, %52, %53, %54, %55, %56, %57, %58, %59, %60, %61, %62, %63, %64, %65, %66, %67, %68, %69, %70, %71, %72, %73, %74, %75, %76, %77, %78, %79, %80, %81, %82, %83, %84, %85, %86, %87, %88, %89, %90, %91, %92, %93, %94, %95}, %96, %97, p, 1, 1, 0, 1;\n}\n"
    : "+f"(d[0]), "+f"(d[1]), "+f"(d[2]), "+f"(d[3]), "+f"(d[4]), "+f"(d[5]), "+f"(d[6]), "+f"(d[7]), "+f"(d[8]), "+f"(d[9]), "+f"(d[10]), "+f"(d[11]), "+f"(d[12]), "+f"(d[13]), "+f"(d[14]), "+f"(d[15]), "+f"(d[16]), "+f"(d[17]), "+f"(d[18]), "+f"(d[19]), "+f"(d[20]), "+f"(d[21]), "+f"(d[22]), "+f"(d[23]), "+f"(d[24]), "+f"(d[25]), "+f"(d[26]), "+f"(d[27]), "+f"(d[28]), "+f"(d[29]), "+f"(d[30]), "+f"(d[31]), "+f"(d[32]), "+f"(d[33]), "+f"(d[34]), "+f"(d[35]), "+f"(d[36]), "+f"(d[37]), "+f"(d[38]), "+f"(d[39]), "+f"(d[40]), "+f"(d[41]), "+f"(d[42]), "+f"(d[43]), "+f"(d[44]), "+f"(d[45]), "+f"(d[46]), "+f"(d[47]), "+f"(d[48]), "+f"(d[49]), "+f"(d[50]), "+f"(d[51]), "+f"(d[52]), "+f"(d[53]), "+f"(d[54]), "+f"(d[55]), "+f"(d[56]), "+f"(d[57]), "+f"(d[58]), "+f"(d[59]), "+f"(d[60]), "+f"(d[61]), "+f"(d[62]), "+f"(d[63]), "+f"(d[64]), "+f"(d[65]), "+f"(d[66]), "+f"(d[67]), "+f"(d[68]), "+f"(d[69]), "+f"(d[70]), "+f"(d[71]), "+f"(d[72]), "+f"(d[73]), "+f"(d[74]), "+f"(d[75]), "+f"(d[76]), "+f"(d[77]), "+f"(d[78]), "+f"(d[79]), "+f"(d[80]), "+f"(d[81]), "+f"(d[82]), "+f"(d[83]), "+f"(d[84]), "+f"(d[85]), "+f"(d[86]), "+f"(d[87]), "+f"(d[88]), "+f"(d[89]), "+f"(d[90]), "+f"(d[91]), "+f"(d[92]), "+f"(d[93]), "+f"(d[94]), "+f"(d[95])
    : "l"(descA), "l"(descB), "r"(scaleD));
}

__device__ __forceinline__ void wgmma_n128_ss_ta0_tb1(float* d, uint64_t descA, uint64_t descB, int scaleD) {
  asm volatile("{\n.reg .pred p;\nsetp.ne.b32 p, %66, 0;\n"
    "wgmma.mma_async.sync.aligned.m64n128k16.f32.bf16.bf16 {%0, %1, %2, %3, %4, %5, %6, %7, %8, %9, %10, %11, %12, %13, %14, %15, %16, %17, %18, %19, %20, %21, %22, %23, %24, %25, %26, %27, %28, %29, %30, %31, %32, %33, %34, %35, %36, %37, %38, %39, %40, %41, %42, %43, %44, %45, %46, %47, %48, %49, %50, %51, %52, %53, %54, %55, %56, %57, %58, %59, %60, %61, %62, %63}, %64, %65, p, 1, 1, 0, 1;\n}\n"
    : "+f"(d[0]), "+f"(d[1]), "+f"(d[2]), "+f"(d[3]), "+f"(d[4]), "+f"(d[5]), "+f"(d[6]), "+f"(d[7]), "+f"(d[8]), "+f"(d[9]), "+f"(d[10]), "+f"(d[11]), "+f"(d[12]), "+f"(d[13]), "+f"(d[14]), "+f"(d[15]), "+f"(d[16]), "+f"(d[17]), "+f"(d[18]), "+f"(d[19]), "+f"(d[20]), "+f"(d[21]), "+f"(d[22]), "+f"(d[23]), "+f"(d[24]), "+f"(d[25]), "+f"(d[26]), "+f"(d[27]), "+f"(d[28]), "+f"(d[29]), "+f"(d[30]), "+f"(d[31]), "+f"(d[32]), "+f"(d[33]), "+f"(d[34]), "+f"(d[35]), "+f"(d[36]), "+f"(d[37]), "+f"(d[38]), "+f"(d[39]), "+f"(d[40]), "+f"(d[41]), "+f"(d[42]), "+f"(d[43]), "+f"(d[44]), "+f"(d[45]), "+f"(d[46]), "+f"(d[47]), "+f"(d[48]), "+f"(d[49]), "+f"(d[50]), "+f"(d[51]), "+f"(d[52]), "+f"(d[53]), "+f"(d[54]), "+f"(d[55]), "+f"(d[56]), "+f"(d[57]), "+f"(d[58]), "+f"(d[59]), "+f"(d[60]), "+f"(d[61]), "+f"(d[62]), "+f"(d[63])
    : "l"(descA), "l"(descB), "r"(scaleD));
}

__device__ __forceinline__ void wgmma_n192_ssz_ta0_tb1(float* d, uint64_t descA, uint64_t descB) {
  asm volatile("{\n.reg .pred p;\nsetp.ne.b32 p, 0, 0;\n"
    "wgmma.mma_async.sync.aligned.m64n192k16.f32.bf16.bf16 {%0, %1, %2, %3, %4, %5, %6, %7, %8, %9, %10, %11, %12, %13, %14, %15, %16, %17, %18, %19, %20, %21, %22, %23, %24, %25, %26, %27, %28, %29, %30, %31, %32, %33, %34, %35, %36, %37, %38, %39, %40, %41, %42, %43, %44, %45, %46, %47, %48, %49, %50, %51, %52, %53, %54, %55, %56, %57, %58, %59, %60, %61, %62, %63, %64, %65, %66, %67, %68, %69, %70, %71, %72, %73, %74, %75, %76, %77, %78, %79, %80, %81, %82, %83, %84, %85, %86, %87, %88, %89, %90, %91, %92, %93, %94, %95}, %96, %97, p, 1, 1, 0, 1;\n}\n"
    : "=f"(d[0]), "=f"(d[1]), "=f"(d[2]), "=f"(d[3]), "=f"(d[4]), "=f"(d[5]), "=f"(d[6]), "=f"(d[7]), "=f"(d[8]), "=f"(d[9]), "=f"(d[10]), "=f"(d[11]), "=f"(d[12]), "=f"(d[13]), "=f"(d[14]), "=f"(d[15]), "=f"(d[16]), "=f"(d[17]), "=f"(d[18]), "=f"(d[19]), "=f"(d[20]), "=f"(d[21]), "=f"(d[22]), "=f"(d[23]), "=f"(d[24]), "=f"(d[25]), "=f"(d[26]), "=f"(d[27]), "=f"(d[28]), "=f"(d[29]), "=f"(d[30]), "=f"(d[31]), "=f"(d[32]), "=f"(d[33]), "=f"(d[34]), "=f"(d[35]), "=f"(d[36]), "=f"(d[37]), "=f"(d[38]), "=f"(d[39]), "=f"(d[40]), "=f"(d[41]), "=f"(d[42]), "=f"(d[43]), "=f"(d[44]), "=f"(d[45]), "=f"(d[46]), "=f"(d[47]), "=f"(d[48]), "=f"(d[49]), "=f"(d[50]), "=f"(d[51]), "=f"(d[52]), "=f"(d[53]), "=f"(d[54]), "=f"(d[55]), "=f"(d[56]), "=f"(d[57]), "=f"(d[58]), "=f"(d[59]), "=f"(d[60]), "=f"(d[61]), "=f"(d[62]), "=f"(d[63]), "=f"(d[64]), "=f"(d[65]), "=f"(d[66]), "=f"(d[67]), "=f"(d[68]), "=f"(d[69]), "=f"(d[70]), "=f"(d[71]), "=f"(d[72]), "=f"(d[73]), "=f"(d[74]), "=f"(d[75]), "=f"(d[76]), "=f"(d[77]), "=f"(d[78]), "=f"(d[79]), "=f"(d[80]), "=f"(d[81]), "=f"(d[82]), "=f"(d[83]), "=f"(d[84]), "=f"(d[85]), "=f"(d[86]), "=f"(d[87]), "=f"(d[88]), "=f"(d[89]), "=f"(d[90]), "=f"(d[91]), "=f"(d[92]), "=f"(d[93]), "=f"(d[94]), "=f"(d[95])
    : "l"(descA), "l"(descB));
}

__device__ __forceinline__ void wgmma_n128_ssz_ta0_tb1(float* d, uint64_t descA, uint64_t descB) {
  asm volatile("{\n.reg .pred p;\nsetp.ne.b32 p, 0, 0;\n"
    "wgmma.mma_async.sync.aligned.m64n128k16.f32.bf16.bf16 {%0, %1, %2, %3, %4, %5, %6, %7, %8, %9, %10, %11, %12, %13, %14, %15, %16, %17, %18, %19, %20, %21, %22, %23, %24, %25, %26, %27, %28, %29, %30, %31, %32, %33, %34, %35, %36, %37, %38, %39, %40, %41, %42, %43, %44, %45, %46, %47, %48, %49, %50, %51, %52, %53, %54, %55, %56, %57, %58, %59, %60, %61, %62, %63}, %64, %65, p, 1, 1, 0, 1;\n}\n"
    : "=f"(d[0]), "=f"(d[1]), "=f"(d[2]), "=f"(d[3]), "=f"(d[4]), "=f"(d[5]), "=f"(d[6]), "=f"(d[7]), "=f"(d[8]), "=f"(d[9]), "=f"(d[10]), "=f"(d[11]), "=f"(d[12]), "=f"(d[13]), "=f"(d[14]), "=f"(d[15]), "=f"(d[16]), "=f"(d[17]), "=f"(d[18]), "=f"(d[19]), "=f"(d[20]), "=f"(d[21]), "=f"(d[22]), "=f"(d[23]), "=f"(d[24]), "=f"(d[25]), "=f"(d[26]), "=f"(d[27]), "=f"(d[28]), "=f"(d[29]), "=f"(d[30]), "=f"(d[31]), "=f"(d[32]), "=f"(d[33]), "=f"(d[34]), "=f"(d[35]), "=f"(d[36]), "=f"(d[37]), "=f"(d[38]), "=f"(d[39]), "=f"(d[40]), "=f"(d[41]), "=f"(d[42]), "=f"(d[43]), "=f"(d[44]), "=f"(d[45]), "=f"(d[46]), "=f"(d[47]), "=f"(d[48]), "=f"(d[49]), "=f"(d[50]), "=f"(d[51]), "=f"(d[52]), "=f"(d[53]), "=f"(d[54]), "=f"(d[55]), "=f"(d[56]), "=f"(d[57]), "=f"(d[58]), "=f"(d[59]), "=f"(d[60]), "=f"(d[61]), "=f"(d[62]), "=f"(d[63])
    : "l"(descA), "l"(descB));
}

__device__ __forceinline__ void wgmma_n64_ss_ta0_tb0(float* d, uint64_t descA, uint64_t descB, int scaleD) {
  asm volatile("{\n.reg .pred p;\nsetp.ne.b32 p, %34, 0;\n"
    "wgmma.mma_async.sync.aligned.m64n64k16.f32.bf16.bf16 {%0, %1, %2, %3, %4, %5, %6, %7, %8, %9, %10, %11, %12, %13, %14, %15, %16, %17, %18, %19, %20, %21, %22, %23, %24, %25, %26, %27, %28, %29, %30, %31}, %32, %33, p, 1, 1, 0, 0;\n}\n"
    : "+f"(d[0]), "+f"(d[1]), "+f"(d[2]), "+f"(d[3]), "+f"(d[4]), "+f"(d[5]), "+f"(d[6]), "+f"(d[7]), "+f"(d[8]), "+f"(d[9]), "+f"(d[10]), "+f"(d[11]), "+f"(d[12]), "+f"(d[13]), "+f"(d[14]), "+f"(d[15]), "+f"(d[16]), "+f"(d[17]), "+f"(d[18]), "+f"(d[19]), "+f"(d[20]), "+f"(d[21]), "+f"(d[22]), "+f"(d[23]), "+f"(d[24]), "+f"(d[25]), "+f"(d[26]), "+f"(d[27]), "+f"(d[28]), "+f"(d[29]), "+f"(d[30]), "+f"(d[31])
    : "l"(descA), "l"(descB), "r"(scaleD));
}

__device__ __forceinline__ void wgmma_n64_ssz_ta0_tb0(float* d, uint64_t descA, uint64_t descB) {
  asm volatile("{\n.reg .pred p;\nsetp.ne.b32 p, 0, 0;\n"
    "wgmma.mma_async.sync.aligned.m64n64k16.f32.bf16.bf16 {%0, %1, %2, %3, %4, %5, %6, %7, %8, %9, %10, %11, %12, %13, %14, %15, %16, %17, %18, %19, %20, %21, %22, %23, %24, %25, %26, %27, %28, %29, %30, %31}, %32, %33, p, 1, 1, 0, 0;\n}\n"
    : "=f"(d[0]), "=f"(d[1]), "=f"(d[2]), "=f"(d[3]), "=f"(d[4]), "=f"(d[5]), "=f"(d[6]), "=f"(d[7]), "=f"(d[8]), "=f"(d[9]), "=f"(d[10]), "=f"(d[11]), "=f"(d[12]), "=f"(d[13]), "=f"(d[14]), "=f"(d[15]), "=f"(d[16]), "=f"(d[17]), "=f"(d[18]), "=f"(d[19]), "=f"(d[20]), "=f"(d[21]), "=f"(d[22]), "=f"(d[23]), "=f"(d[24]), "=f"(d[25]), "=f"(d[26]), "=f"(d[27]), "=f"(d[28]), "=f"(d[29]), "=f"(d[30]), "=f"(d[31])
    : "l"(descA), "l"(descB));
}

__device__ __forceinline__ void wgmma_n80_ss_ta0_tb0(float* d, uint64_t descA, uint64_t descB, int scaleD) {
  asm volatile("{\n.reg .pred p;\nsetp.ne.b32 p, %42, 0;\n"
    "wgmma.mma_async.sync.aligned.m64n80k16.f32.bf16.bf16 {%0, %1, %2, %3, %4, %5, %6, %7, %8, %9, %10, %11, %12, %13, %14, %15, %16, %17, %18, %19, %20, %21, %22, %23, %24, %25, %26, %27, %28, %29, %30, %31, %32, %33, %34, %35, %36, %37, %38, %39}, %40, %41, p, 1, 1, 0, 0;\n}\n"
    : "+f"(d[0]), "+f"(d[1]), "+f"(d[2]), "+f"(d[3]), "+f"(d[4]), "+f"(d[5]), "+f"(d[6]), "+f"(d[7]), "+f"(d[8]), "+f"(d[9]), "+f"(d[10]), "+f"(d[11]), "+f"(d[12]), "+f"(d[13]), "+f"(d[14]), "+f"(d[15]), "+f"(d[16]), "+f"(d[17]), "+f"(d[18]), "+f"(d[19]), "+f"(d[20]), "+f"(d[21]), "+f"(d[22]), "+f"(d[23]), "+f"(d[24]), "+f"(d[25]), "+f"(d[26]), "+f"(d[27]), "+f"(d[28]), "+f"(d[29]), "+f"(d[30]), "+f"(d[31]), "+f"(d[32]), "+f"(d[33]), "+f"(d[34]), "+f"(d[35]), "+f"(d[36]), "+f"(d[37]), "+f"(d[38]), "+f"(d[39])
    : "l"(descA), "l"(descB), "r"(scaleD));
}

__device__ __forceinline__ void wgmma_n32_rs_tb1(float* d, const uint32_t* a, uint64_t descB, int scaleD) {
  asm volatile("{\n.reg .pred p;\nsetp.ne.b32 p, %21, 0;\n"
    "wgmma.mma_async.sync.aligned.m64n32k16.f32.bf16.bf16 {%0, %1, %2, %3, %4, %5, %6, %7, %8, %9, %10, %11, %12, %13, %14, %15}, {%16, %17, %18, %19}, %20, p, 1, 1, 1;\n}\n"
    : "+f"(d[0]), "+f"(d[1]), "+f"(d[2]), "+f"(d[3]), "+f"(d[4]), "+f"(d[5]), "+f"(d[6]), "+f"(d[7]), "+f"(d[8]), "+f"(d[9]), "+f"(d[10]), "+f"(d[11]), "+f"(d[12]), "+f"(d[13]), "+f"(d[14]), "+f"(d[15])
    : "r"(a[0]), "r"(a[1]), "r"(a[2]), "r"(a[3]), "l"(descB), "r"(scaleD));
}

__device__ __forceinline__ uint32_t pack_bf16x2(float lo, float hi) {
  uint32_t r;
  asm("cvt.rn.bf16x2.f32 %0, %1, %2;" : "=r"(r) : "f"(hi), "f"(lo));
  return r;
}
__device__ __forceinline__ float bf_lo(uint32_t p) { return __uint_as_float(p << 16); }
__device__ __forceinline__ float bf_hi(uint32_t p) { return __uint_as_float(p & 0xffff0000u); }
__device__ __forceinline__ float bf16_round(float v) { return __bfloat162float(__float2bfloat16_rn(v)); }
__device__ __forceinline__ float ex2_approx(float x) {
  float r;
  asm("ex2.approx.ftz.f32 %0, %1;" : "=f"(r) : "f"(x));
  return r;
}
__device__ __forceinline__ float rcp_fast(float x) {
  float r;
  asm("rcp.approx.ftz.f32 %0, %1;" : "=f"(r) : "f"(x));
  return r;
}
__device__ __forceinline__ void ldmatrix_x4(uint32_t (&r)[4], uint32_t addr) {
  asm volatile("ldmatrix.sync.aligned.m8n8.x4.shared.b16 {%0,%1,%2,%3}, [%4];"
               : "=r"(r[0]), "=r"(r[1]), "=r"(r[2]), "=r"(r[3])
               : "r"(addr)
               : "memory");
}
__device__ __forceinline__ void stmatrix_x4(uint32_t addr, uint32_t r0, uint32_t r1, uint32_t r2, uint32_t r3) {
  asm volatile("stmatrix.sync.aligned.m8n8.x4.shared.b16 [%0], {%1,%2,%3,%4};" ::"r"(addr), "r"(r0), "r"(r1), "r"(r2),
               "r"(r3));
}
__device__ __forceinline__ uint32_t add_bf16x2(uint32_t a, uint32_t b) {
  uint32_t r;
  asm("add.rn.bf16x2 %0, %1, %2;" : "=r"(r) : "r"(a), "r"(b));
  return r;
}
__device__ __forceinline__ uint4 lds128(uint32_t addr) {
  uint4 v;
  asm volatile("ld.shared.v4.b32 {%0,%1,%2,%3}, [%4];" : "=r"(v.x), "=r"(v.y), "=r"(v.z), "=r"(v.w) : "r"(addr) : "memory");
  return v;
}
__device__ __forceinline__ uint32_t lds32(uint32_t addr) {
  uint32_t v;
  asm volatile("ld.shared.b32 %0, [%1];" : "=r"(v) : "r"(addr) : "memory");
  return v;
}
__device__ __forceinline__ void sts32(uint32_t addr, uint32_t v) {
  asm volatile("st.shared.b32 [%0], %1;" ::"r"(addr), "r"(v) : "memory");
}

__device__ __forceinline__ unsigned ld_acquire_u32(const unsigned* p) {
  unsigned v;
  asm volatile("ld.acquire.gpu.global.u32 %0, [%1];" : "=r"(v) : "l"(p) : "memory");
  return v;
}
__device__ __forceinline__ void red_relaxed_add(unsigned* p, unsigned v) {
  asm volatile("red.relaxed.gpu.global.add.u32 [%0], %1;" ::"l"(p), "r"(v) : "memory");
}
__device__ __forceinline__ void wait_ge(const unsigned* p, unsigned target) {
#pragma unroll 1
  for (uint32_t it = 0; it < (1u << 17); ++it) {
    if ((int)(ld_acquire_u32(p) - target) >= 0) return;
  }
}

__device__ __forceinline__ void wait_ge2(const unsigned* p, unsigned t0, unsigned t1) {
#pragma unroll 1
  for (uint32_t it = 0; it < (1u << 17); ++it) {
    unsigned long long v;
    asm volatile("ld.acquire.gpu.global.u64 %0, [%1];" : "=l"(v) : "l"(p) : "memory");
    if ((int)((unsigned)v - t0) >= 0 && (int)((unsigned)(v >> 32) - t1) >= 0) return;
  }
}

template <bool SLOW>
__device__ __forceinline__ void wait_mask(const unsigned* f, int cnt, unsigned target, uint32_t need, uint32_t& seen, int lane) {
  if ((seen & need) == need) return;
  const unsigned* fp = f + (lane & (cnt - 1));
#pragma unroll 1
  for (uint32_t it = 0; it < (1u << 17); ++it) {
    seen = __ballot_sync(0xffffffffu, (int)(ld_acquire_u32(fp) - target) >= 0);
    if ((seen & need) == need) break;
    if (SLOW) __nanosleep(400);
  }
  fence_proxy_async_all();
}
__device__ __forceinline__ float4 ld_rec(const float4* p) {
  float4 v;
  asm volatile("ld.relaxed.gpu.global.v4.f32 {%0,%1,%2,%3}, [%4];" : "=f"(v.x), "=f"(v.y), "=f"(v.z), "=f"(v.w) : "l"(p) : "memory");
  return v;
}
__device__ __forceinline__ void st_rec(float4* p, float a, float b, float c, unsigned tag) {
  asm volatile("st.relaxed.gpu.global.v4.f32 [%0], {%1,%2,%3,%4};" ::"l"(p), "f"(a), "f"(b), "f"(c), "f"(__uint_as_float(tag)) : "memory");
}
template <int N>
__device__ __forceinline__ float4 sum_recs(const float4* p, int stride, unsigned tag) {
  float4 s;
#pragma unroll 1
  for (uint32_t it = 0; it < (1u << 17); ++it) {
    float4 v[N];
#pragma unroll
    for (int t = 0; t < N; t++) v[t] = ld_rec(p + t * stride);
    bool ok = true;
    s = make_float4(0.f, 0.f, 0.f, 0.f);
#pragma unroll
    for (int t = 0; t < N; t++) {
      ok &= __float_as_uint(v[t].w) == tag;
      s.x += v[t].x;
      s.y += v[t].y;
      s.z += v[t].z;
    }
    if (ok) break;
    __nanosleep(200);
  }
  return s;
}

__device__ __forceinline__ int fresh_tid() {
  int t;
  asm volatile("mov.u32 %0, %%tid.x;" : "=r"(t));
  return t;
}
#define PHASE_IDS                                  \
  const int tid_ = fresh_tid();                    \
  const int lane = tid_ & 31, wwarp = __shfl_sync(0xffffffffu, (tid_ >> 5) & 3, 0), tid = tid_ & 127; \
  const int g = lane >> 2, c = lane & 3;           \
  (void)tid; (void)g; (void)c; (void)wwarp;

#define STAMPW(cond, i) do { } while (0)
#define STAMP(cond, i) do { } while (0)
#define STA(i) do { } while (0)
#define GTL(i) do { } while (0)
#define GTLX(c, i) do { } while (0)
#define TGET(v) do { } while (0)
#define TPUT(c, i, v) do { } while (0)

constexpr float SM_C = 0.17677669529663687f * 1.4426950408889634f;

constexpr uint32_t OA_TILE = SBASE + OFF_SLOT + 16384;

__device__ __forceinline__ void sched_fence(uint32_t never) {
  asm volatile("{\n.reg .pred p;\nsetp.ne.u32 p, %0, 0;\n@p exit;\n}\n" ::"r"(never) : "memory");
}

template <int K0, int K1>
__device__ __forceinline__ void attn_exp(float (&s)[32]) {
#pragma unroll
  for (int k = K0; k < K1; k++) s[k] = ex2_approx(s[k]);
}
#define ASPL 16
#define ASPM 6
template <int MODE, bool NEXT>
__device__ __forceinline__ void attn_unit(float (&s)[32], float (&sn)[32], float (&o)[16], float (&l)[2], bool valid,
                                          uint32_t vdesc, uint32_t qdesc, uint32_t kdesc, uint32_t tri, int w,
                                          uint32_t hbar, uint32_t hpar, uint32_t rel, uint32_t zero, bool stampon = false) {
  float x[9][2];
  if (MODE == 0) {
    attn_exp<0, ASPL>(s);
  } else {
#pragma unroll
    for (int e = 0; e < 2; e++) {
#pragma unroll
      for (int j = 0; j < 4; j++) x[j][e] = MODE == 1 ? s[4 * j + 2 + e] : s[16 + 4 * j + e];
      x[4][e] = MODE == 1 ? s[e] : s[30 + e];
      x[5][e] = MODE == 1 ? s[18 + e] : s[12 + e];
#pragma unroll
      for (int u = 1; u < 4; u++)
        x[5 + u][e] = MODE == 1 ? (w >= u ? s[4 * u + e] : s[4 * (8 - u) + 2 + e]) : (w >= u ? s[4 * (7 - u) + 2 + e] : s[4 * (u - 1) + e]);
    }
#pragma unroll
    for (int k = 0; k < 2 * ASPM; k++) x[k >> 1][k & 1] = ex2_approx(x[k >> 1][k & 1]);
  }
  sched_fence(zero);
  if (hbar) mbar_wait(hbar, hpar);
  wgmma_wait<0>();
  if (rel) mbar_arrive(rel);
  if (NEXT) {
    wgmma_fence();
    wgmma_n64_ssz_ta0_tb0(sn, desc_lo(qdesc), desc_lo(kdesc));
    wgmma_n64_ss_ta0_tb0(sn, desc_lo(qdesc + 2), desc_lo(kdesc + 2), 1);
    wgmma_commit();
    sched_fence(zero);
  }
  uint32_t p[16];
  if (MODE == 0) {
    attn_exp<ASPL, 32>(s);
#pragma unroll
    for (int k = 0; k < 16; k++) p[k] = pack_bf16x2(s[2 * k], s[2 * k + 1]);
  } else {
#pragma unroll
    for (int k = 2 * ASPM; k < 18; k++) x[k >> 1][k & 1] = ex2_approx(x[k >> 1][k & 1]);
    const uint32_t tm = MODE == 1 ? tri : ~tri;
#pragma unroll
    for (int j = 0; j < 4; j++) {
      p[MODE == 1 ? 2 * j + 1 : 8 + 2 * j] = pack_bf16x2(x[j][0], x[j][1]);
      p[MODE == 1 ? 8 + 2 * j : 2 * j + 1] = 0u;
    }
    p[MODE == 1 ? 0 : 15] = pack_bf16x2(x[4][0], x[4][1]) & (w == 0 ? tm : 0xffffffffu);
    p[MODE == 1 ? 9 : 6] = pack_bf16x2(x[5][0], x[5][1]) & (w == 3 ? tm : 0xffffffffu);
#pragma unroll
    for (int u = 1; u < 4; u++) {
      const uint32_t q = pack_bf16x2(x[5 + u][0], x[5 + u][1]);
      p[MODE == 1 ? 2 * u : 2 * (7 - u) + 1] = q & (w > u ? 0xffffffffu : (w == u ? tm : 0u));
      p[MODE == 1 ? 2 * (8 - u) + 1 : 2 * (u - 1)] = q & (w < u - 1 ? 0xffffffffu : (w == u - 1 ? tm : 0u));
    }
  }
  wgmma_fence();
#pragma unroll
  for (int k = 0; k < 4; k++) wgmma_n32_rs_tb1(o, p + 4 * k, desc_lo(vdesc + k * 128), 1);
  wgmma_commit();
#pragma unroll
  for (int r = 0; r < 2; r++) {
    float t = 0.f;
#pragma unroll
    for (int hf = 0; hf < 2; hf++) {
      if (MODE != 0 && r == MODE - 1 && hf == 2 - MODE) continue;
      const uint32_t* q = p + 8 * hf + r;
      const uint32_t v = add_bf16x2(add_bf16x2(q[0], q[2]), add_bf16x2(q[4], q[6]));
      t = (MODE != 0 && r == MODE - 1) || hf == 0 ? bf_lo(v) + bf_hi(v) : t + (bf_lo(v) + bf_hi(v));
    }
    if (valid) l[r] += t;
  }
  if (NEXT) {
    wgmma_wait<1>();
    reg_fence<32>(sn);
  }
}

__device__ __forceinline__ void attn_a_slow(const uint8_t* __restrict__ kvimg, int L, int gb, int hp,
                                         int hh, int wwarp, int lane) {
  constexpr uint32_t sq = SBASE + OFF_SLOT + 3 * 16384;
  const unsigned ep = (*(volatile unsigned*)(g_flags + F_DONE)) / NCTA;
  wait_ge2(g_flags + F_KV + (gb * 16 + hp) * KSTR, 4u * ep + L + 1u, 2u * ep + (L >> 1) + 1u);
#pragma unroll 1
  for (int t = 0; t < 32; t++) {
    const int row = (t >> 4) * 64 + ((t & 8) ? 7 - wwarp : wwarp) * 8 + (t & 7);
    const int qpos = gb * 128 + row;
    const uint32_t qaddr = sq + ((t >> 4) * 64 + wwarp * 16 + (t & 15)) * 128;
    float mx = -INFINITY, sum = 0.f, acc = 0.f;
#pragma unroll 1
    for (int pass = 0; pass < 2; pass++) {
#pragma unroll 1
      for (int j = 0; j < 8; j++) {
        const int kp = qpos - (lane + 32 * j);
        const uint8_t* kr = kvimg + ((size_t)((kp >> 7) * 16 + hp) * 2 + ((kp >> 6) & 1)) * 16384 + (kp & 63) * 128;
        float d = -INFINITY;
        if (kp >= 0) {
          d = 0.f;
#pragma unroll 1
          for (int q = 0; q < 4; q++) {
            const uint4 kv = __ldcg(reinterpret_cast<const uint4*>(kr + (((hh * 4 + q) ^ (kp & 7)) << 4)));
            const uint4 qv = lds128(qaddr + (((hh * 4 + q) ^ (row & 7)) << 4));
            const uint32_t kw[4] = {kv.x, kv.y, kv.z, kv.w}, qw[4] = {qv.x, qv.y, qv.z, qv.w};
#pragma unroll
            for (int e = 0; e < 4; e++) d = fmaf(bf_lo(kw[e]), bf_lo(qw[e]), fmaf(bf_hi(kw[e]), bf_hi(qw[e]), d));
          }
        }
        if (pass == 0) {
          mx = fmaxf(mx, d);
        } else {
          const float ev = ex2_approx(d - mx);
          sum += ev;
          const float pv = bf16_round(ev);
#pragma unroll 1
          for (int kk = 0; kk < 32; kk++) {
            const float pk = __shfl_sync(0xffffffffu, pv, kk);
            const int k2 = qpos - (kk + 32 * j);
            if (k2 >= 0) {
              const uint8_t* vr = kvimg + ((size_t)((k2 >> 7) * 16 + hp) * 2 + ((k2 >> 6) & 1)) * 16384 + 8192 + (k2 & 63) * 128;
              const unsigned short vv =
                  __ldcg(reinterpret_cast<const unsigned short*>(vr + (((hh * 4 + (lane >> 3)) ^ (k2 & 7)) << 4) + (lane & 7) * 2));
              acc = fmaf(pk, __uint_as_float((uint32_t)vv << 16), acc);
            }
          }
        }
      }
      if (pass == 0) {
#pragma unroll
        for (int o = 16; o > 0; o >>= 1) mx = fmaxf(mx, __shfl_xor_sync(0xffffffffu, mx, o));
      }
    }
#pragma unroll
    for (int o = 16; o > 0; o >>= 1) sum += __shfl_xor_sync(0xffffffffu, sum, o);
    acc *= rcp_fast(sum);
    const float hi = __shfl_down_sync(0xffffffffu, acc, 1);
    __syncwarp();
    if ((lane & 1) == 0)
      sts32(OA_TILE + row * 128 + (((hh * 4 + (lane >> 3)) ^ (row & 7)) << 4) + (lane & 7) * 2, pack_bf16x2(acc, hi));
    __syncwarp();
  }
}

__device__ __forceinline__ void store_o(const float (&o)[16], const float (&inv)[2], uint32_t rowaddr, int hh, int lane) {
  const int mat = lane >> 3, r7 = lane & 7;
#pragma unroll
  for (int jp = 0; jp < 2; jp++)
    stmatrix_x4(rowaddr + (((hh * 4 + 2 * jp + (mat >> 1)) ^ r7) << 4),
                pack_bf16x2(o[8 * jp] * inv[0], o[8 * jp + 1] * inv[0]),
                pack_bf16x2(o[8 * jp + 2] * inv[1], o[8 * jp + 3] * inv[1]),
                pack_bf16x2(o[8 * jp + 4] * inv[0], o[8 * jp + 5] * inv[0]),
                pack_bf16x2(o[8 * jp + 6] * inv[1], o[8 * jp + 7] * inv[1]));
}

__device__ __forceinline__ void attention_a(int HH, int L, int gb, int hp, uint32_t par0, uint32_t parA, int wwarp, int lane,
                                            uint32_t zero) {
  constexpr uint32_t bars = SBASE + OFF_BAR;
  const uint32_t dslot = ((SBASE + OFF_SLOT) >> 4) + 0x10000u + HH * 4;
  const uint32_t dq = dslot + 3 * 1024;
  float sa[32], sb[32], o[2][16], l[2][2];
  auto dch = [&](int n) { return dslot + 1024u * (n % 3 == 0 ? 1 : (n % 3 == 1 ? 0 : 2)); };
  wgmma_fence();
  wgmma_n64_ssz_ta0_tb0(sa, desc_lo(dq + 512), desc_lo(dch(0)));
  wgmma_n64_ss_ta0_tb0(sa, desc_lo(dq + 512 + 2), desc_lo(dch(0) + 2), 1);
  wgmma_commit();
#pragma unroll
  for (int h = 0; h < 2; h++) {
#pragma unroll
    for (int i = 0; i < 16; i++) o[h][i] = 0.f;
    l[h][0] = l[h][1] = 0.f;
  }
  const int dg = (lane >> 2) - 2 * (lane & 3);
  const uint32_t tri = (dg >= 0 ? 0xffffu : 0u) | (dg >= 1 ? 0xffff0000u : 0u);
  const int nmax = 2 * gb + 1;
  wgmma_wait<0>();
  reg_fence<32>(sa);
#define STON false
#define ATT_STEP(i, MODE)                                                                                            \
  attn_unit<MODE, true>(sa, sb, o[1], l[1], i <= nmax, dch(i) + 512, dq, dch(i + 1), tri, wwarp,                     \
                        i >= 1 ? bars + 8u * (B_HALO + i - 1) : 0u, i == 1 ? par0 : parA, 0u, zero, STON);                \
  attn_unit<MODE, (i < 4)>(sb, sa, o[0], l[0], i + 1 <= nmax, dch(i + 1) + 512, dq + 512, dch(i + 1), tri, wwarp, 0u, \
                           0u, i < 3 && lane == 0 ? bars + 8u * (B_REL + i) : 0u, zero);
  ATT_STEP(0, 1)
  ATT_STEP(1, 0)
  ATT_STEP(2, 0)
  ATT_STEP(3, 0)
  ATT_STEP(4, 2)
#undef ATT_STEP
  const uint32_t ra = OA_TILE + (((lane & 8) ? 7 - wwarp : wwarp) * 8 + (lane & 7)) * 128;
  bool bad = false;
#pragma unroll
  for (int h = 1; h >= 0; h--) {
    float inv[2];
#pragma unroll
    for (int r = 0; r < 2; r++) {
      float v = l[h][r];
      v += __shfl_xor_sync(0xffffffffu, v, 1);
      v += __shfl_xor_sync(0xffffffffu, v, 2);
      bad |= !(v <= 1.152921504606846976e18f && v >= 8.673617379884035e-19f);
      inv[r] = rcp_fast(v);
    }
    if (h == 0) wgmma_wait<0>();
    reg_fence<16>(o[h]);
    store_o(o[h], inv, ra + h * 8192, HH, lane);
  }
  if (HH == 0) GTL(45);
  if (__any_sync(0xffffffffu, bad)) attn_a_slow(g_kvA[L >> 1][0][0][0], L, gb, hp, HH, wwarp, lane);
}

constexpr uint32_t KB_ROW0 = SBASE + OFF_SLOT + 2048, VB_ROW0 = SBASE + OFF_SLOT + 24576 + 2048;

__device__ __forceinline__ void attnB_soft(const float (&s)[40], int wwarp, int D, bool edge, bool odd,
                                           uint32_t (&p)[5][4], float (&sum)[2]) {
  float z[2][3];
#define GATHER_(W)                                                                                  \
  _Pragma("unroll") for (int r = 0; r < 2; r++) _Pragma("unroll") for (int t = 0; t < 3; t++)       \
      z[r][t] = odd ? s[4 * (2 * W + r + t) + 2 * r + 1] : s[4 * (2 * W + r + t) + 2 * r];
  if (wwarp < 2) {
    if (wwarp == 0) { GATHER_(0) } else { GATHER_(1) }
  } else {
    if (wwarp == 2) { GATHER_(2) } else { GATHER_(3) }
  }
#undef GATHER_
  float y[2];
  y[0] = D >= 2 ? z[0][0] : z[0][2];
  y[1] = D >= 2 ? z[1][0] : z[1][2];
  if (edge) {
    z[0][1] = -INFINITY;
    if (D >= 2) y[0] = y[1] = -INFINITY;
  }
  float m0 = fmaxf(z[0][1], y[0]), m1 = fmaxf(z[1][1], y[1]);
  m0 = fmaxf(m0, __shfl_xor_sync(0xffffffffu, m0, 1));
  m1 = fmaxf(m1, __shfl_xor_sync(0xffffffffu, m1, 1));
  m0 = fmaxf(m0, __shfl_xor_sync(0xffffffffu, m0, 2));
  m1 = fmaxf(m1, __shfl_xor_sync(0xffffffffu, m1, 2));
  const float e00 = ex2_approx(z[0][1] - m0), e01 = ex2_approx(y[0] - m0);
  const float e10 = ex2_approx(z[1][1] - m1), e11 = ex2_approx(y[1] - m1);
  sum[0] = e00 + e01;
  sum[1] = e10 + e11;
  const int sh = odd ? 16 : 0;
  const uint32_t a0 = pack_bf16x2(e00, 0.f) << sh, a1 = pack_bf16x2(e10, 0.f) << sh;
  const uint32_t b0 = pack_bf16x2(e01, 0.f) << sh, b1 = pack_bf16x2(e11, 0.f) << sh;
  const int kb = wwarp + (D >= 2 ? 0 : 1);
#pragma unroll
  for (int k = 0; k < 5; k++) {
    p[k][0] = k == kb ? b0 : 0u;
    p[k][1] = k == wwarp + 1 ? a1 : 0u;
    p[k][2] = k == wwarp ? a0 : 0u;
    p[k][3] = k == kb ? b1 : 0u;
#pragma unroll
    for (int q = 0; q < 4; q++) asm volatile("" : "+r"(p[k][q]));
  }
}

__device__ __forceinline__ void attnB_s(float (&s)[40], int HH, int h) {
  constexpr uint32_t sq = SBASE + OFF_SLOT + 3 * 16384;
#pragma unroll
  for (int ks = 0; ks < 2; ks++)
    wgmma_n80_ss_ta0_tb0(s, make_desc(sq + h * 8192 + HH * 64 + ks * 32, 16),
                         make_desc(KB_ROW0 + h * 8192 - 2048 + HH * 64 + ks * 32, 16), ks);
}
__device__ __forceinline__ void attnB_pv(float (&o)[16], const uint32_t (&p)[5][4], int HH, int h) {
#pragma unroll
  for (int k = 0; k < 5; k++)
    wgmma_n32_rs_tb1(o, p[k], make_desc(VB_ROW0 + h * 8192 - 2048 + k * 2048 + HH * 64, 16), k);
}

__device__ __forceinline__ void attention_b(int HH, int gb, uint32_t par0, int wwarp, int lane) {
  constexpr uint32_t bars = SBASE + OFF_BAR, sq = SBASE + OFF_SLOT + 3 * 16384;
  float s[40];
  reg_define<40>(s);
  wgmma_fence();
  attnB_s(s, HH, 1);
  wgmma_commit();
  const int g = lane >> 2;
  const bool odd = g & 1;
  const int D = 2 * (lane & 3) + (g & 1) - g;
  const uint32_t ra = sq + (wwarp * 16 + ((lane >> 3) & 1) * 8 + (lane & 7)) * 128;
  wgmma_wait<0>();
  reg_fence<40>(s);
#pragma unroll 1
  for (int h = 1; h >= 0; h--) {
    float o[16], inv[2];
    uint32_t p[5][4];
    reg_define<16>(o);
    attnB_soft(s, wwarp, D, h == 0 && gb == 0 && wwarp == 0, odd, p, inv);
    if (h == 1) {
      mbar_wait(bars + 8u * B_HALO, par0);
      wgmma_fence();
      attnB_s(s, HH, 0);
    }
    wgmma_fence();
    attnB_pv(o, p, HH, h);
    wgmma_commit();
#pragma unroll
    for (int r = 0; r < 2; r++) {
      inv[r] += __shfl_xor_sync(0xffffffffu, inv[r], 1);
      inv[r] += __shfl_xor_sync(0xffffffffu, inv[r], 2);
      inv[r] = rcp_fast(inv[r]);
    }
    wgmma_wait<0>();
    reg_fence<40>(s);
    reg_fence<16>(o);
    store_o(o, inv, ra + h * 8192, HH, lane);
  }
}

#define KTQM 0
#define TRICKLE 300
#define CSPF 4
#define EPT -1
#define EPW1 2
#define EPW0 5
#define HPOLL 3
#define QTURN 2
struct Params {
  CUtensorMap xq[2], xr[3], o, wqkv[2], wo[2];
  const __nv_bfloat16* in_x;
  const __nv_bfloat16* wqkv_p[2];
  const __nv_bfloat16* wo_p[2];
  __nv_bfloat16* out;
  uint32_t zero;
};

__device__ __forceinline__ void colsum_part(const CUtensorMap* wmap, int ty, int qr, int hp) {
  constexpr uint32_t bars = SBASE + OFF_BAR, slots = SBASE + OFF_SLOT;
  PHASE_IDS
  const unsigned ep1 = (*(volatile unsigned*)(g_flags + F_DONE)) / NCTA + 1u;
  if (wwarp == 0 && elect_one()) {
    mbar_expect_tx(bars + 8u * B_CS, 6 * UNIT);
#pragma unroll 1
    for (int j = 0; j < 2; j++) {
      if (ty == 0) mbar_pace(bars + 8u * (B_EMPTY + 1 + 3 * j), 0);
      else __nanosleep(1000);
      tma_load_3d(slots + j * 3 * UNIT, wmap, bars + 8u * B_CS, hp * 64, qr * 128 + j * 64, 0);
    }
  }
  mbar_wait(bars + 8u * B_CS, ty);
  const uint32_t src = slots + (tid >> 3) * 128 + (((tid & 7) ^ ((tid >> 3) & 7)) << 4);
#pragma unroll 1
  for (int p = 0; p < 3; p++) {
    float s[8];
#pragma unroll
    for (int e = 0; e < 8; e++) s[e] = 0.f;
#pragma unroll
    for (int j = 0; j < 8; j++) {
      const uint4 v = lds128(src + p * UNIT + (j >> 2) * 3 * UNIT + (j & 3) * 2048);
      const uint32_t x[4] = {v.x, v.y, v.z, v.w};
#pragma unroll
      for (int e = 0; e < 4; e++) {
        s[2 * e] += bf_lo(x[e]);
        s[2 * e + 1] += bf_hi(x[e]);
      }
    }
#pragma unroll
    for (int st = 0; st < 2; st++) {
      const bool up = (lane >> (st + 3)) & 1;
#pragma unroll
      for (int e = 0; e < (4 >> st); e++) {
        const float keep = up ? s[e + (4 >> st)] : s[e], give = up ? s[e] : s[e + (4 >> st)];
        s[e] = keep + __shfl_xor_sync(0xffffffffu, give, 8 << st);
      }
    }
    const uint32_t dst = slots + 6 * UNIT + ((wwarp * 3 + p) * 64 + (lane & 7) * 8 + ((lane >> 3) & 1) * 4 + (lane >> 4) * 2) * 4;
    sts32(dst, __float_as_uint(s[0]));
    sts32(dst + 4, __float_as_uint(s[1]));
  }
  named_bar_sync(6, 128);
  if (tid < 64) {
    float r[3] = {0.f, 0.f, 0.f};
#pragma unroll
    for (int e = 0; e < 12; e++) r[e % 3] += __uint_as_float(lds32(slots + 6 * UNIT + (e * 64 + tid) * 4));
    st_rec(&g_cs[ty][hp][qr][tid], r[0], r[1], r[2], ep1);
  }
  named_bar_sync(6, 128);
}

__device__ __forceinline__ int cs_pos(int col) { return (col & ~15) + ((col & 7) >> 1) * 4 + ((col >> 3) & 1) * 2 + (col & 1); }

__device__ __forceinline__ uint32_t ln_params(float s1, float s2) {
  const float mean = s1 * (1.0f / DM);
  const float var = fmaxf(fmaf(-mean, mean, s2 * (1.0f / DM)), 0.f);
  float sd;
  asm("sqrt.approx.f32 %0, %1;" : "=f"(sd) : "f"(bf16_round(bf16_round(var) + 1e-5f)));
  return pack_bf16x2(mean, sd);
}

__host__ __device__ constexpr int w_ua(int kt) { return (kt == 6 ? 20 : 3 * kt) % 20; }
__host__ __device__ constexpr int w_ub(int kt) { return (kt == 6 ? 18 : 3 * kt + 1) % 20; }

constexpr int NSEG = 20;
__host__ __device__ constexpr int SEGQ(int ch, int L, int k0, int k1) { return ch | (L << 2) | ((k0 / 4) << 4) | ((k1 / 4 - 1) << 6); }
__host__ __device__ constexpr int SEGW(int ch, int L) { return ch | 2 | (L << 2); }
__host__ __device__ constexpr unsigned long long pack8(int a, int b, int c, int d, int e, int f, int g, int h) {
  return (unsigned long long)a | ((unsigned long long)b << 8) | ((unsigned long long)c << 16) | ((unsigned long long)d << 24) |
         ((unsigned long long)e << 32) | ((unsigned long long)f << 40) | ((unsigned long long)g << 48) | ((unsigned long long)h << 56);
}
#define SP2 12
#define SP3 12
#define SP4 12
#define SP6 12
__device__ __forceinline__ int seg_code(int sg) {
  constexpr unsigned long long T0 = pack8(SEGQ(0, 0, 0, 16), SEGQ(1, 0, 0, 16), SEGW(0, 0), SEGQ(0, 1, 0, SP2), SEGW(1, 0),
                                          SEGQ(0, 1, SP2, 16), SEGQ(1, 1, 0, SP3), SEGW(0, 1));
  constexpr unsigned long long T1 = pack8(SEGQ(1, 1, SP3, 16), SEGQ(0, 2, 0, SP4), SEGW(1, 1), SEGQ(0, 2, SP4, 16),
                                          SEGQ(1, 2, 0, 16), SEGW(0, 2), SEGQ(0, 3, 0, SP6), SEGW(1, 2));
  constexpr unsigned long long T2 = pack8(SEGQ(0, 3, SP6, 16), SEGQ(1, 3, 0, 16), SEGW(0, 3), SEGW(1, 3), 0, 0, 0, 0);
  return (int)(((sg < 8 ? T0 : (sg < 16 ? T1 : T2)) >> (8 * (sg & 7))) & 255ull);
}
__device__ __forceinline__ int q_first(int inst) { return (int)((pack8(0, 16, 48, 80, 112, 144, 176, 208) >> (8 * inst)) & 255ull); }
__device__ __forceinline__ int w_first(int inst) {
  return (int)((pack8(32, 48 + SP2, 80 + SP3, 112 + SP4, 160, 176 + SP6, 224, 240) >> (8 * inst)) & 255ull);
}
#define PREMASK 0x2Cu
#define PRE0 3
#define PRESH 2
__host__ __device__ constexpr int pre_idx(int kt) {
  const int d = kt - PRE0;
  return (d >= 0 && (d & ((1 << PRESH) - 1)) == 0 && (d >> PRESH) < 4) ? d >> PRESH : -1;
}
__device__ __forceinline__ bool w_pre(int inst) { return (PREMASK >> inst) & 1u; }
__device__ __forceinline__ int q_split(int inst) { return (int)(((0x40400044u | ((SP2 / 4) << 8) | ((SP3 / 4) << 12) | ((SP4 / 4) << 16) | ((SP6 / 4) << 24)) >> (4 * inst)) & 15u); }

__global__ void __launch_bounds__(512, 1) fused_kernel(const __grid_constant__ Params P) {
  extern __shared__ __align__(1024) uint8_t smem_raw[];
  constexpr uint32_t base = SBASE, bars = base + OFF_BAR, slots = base + OFF_SLOT;
  if (smem_u32(smem_raw) != base) __trap();
  const int warp = __shfl_sync(0xffffffffu, threadIdx.x >> 5, 0), lane = threadIdx.x & 31;
  const int b = blockIdx.x;
#define QS 0
#define WS 1
  const int qr = ((b & ((8 << QS) - 1)) >> QS) ^ (((b >> (3 + QS)) & 1) * 7);
  const int hp = ((b >> (3 + QS)) << QS) + (b & ((1 << QS) - 1));
  const int rt = ((b & ((16 << WS) - 1)) >> WS) ^ (((b >> (4 + WS)) & 1) * 15);
  const int ct = ((b >> (4 + WS)) << WS) + (b & ((1 << WS) - 1));

  if (warp == 12) {
    if (elect_one()) {
#pragma unroll
      for (int s = 0; s < 8; s++) {
        mbar_init(bars + 8u * (B_FULL + s), 2);
        mbar_init(bars + 8u * (B_EMPTY + s), 4);
      }
      mbar_init(bars + 8u * B_GO, 1);
      fence_barrier_init();
    }
    __syncwarp();
    named_bar_arrive(0, 512);
  }
  if (threadIdx.x == 0) {
    mbar_init(bars + 8u * B_PREP, 1);
    mbar_init(bars + 8u * (B_PREP + 1), 1);
    for (int s = 0; s < 4; s++) mbar_init(bars + 8u * (B_HALO + s), 1);
    for (int s = 0; s < 3; s++) mbar_init(bars + 8u * (B_REL + s), 8);
    mbar_init(bars + 8u * B_AFREE, 2);
    mbar_init(bars + 8u * B_TURN, 4);
    mbar_init(bars + 8u * (B_TURN + 1), 4);
    mbar_init(bars + 8u * B_CS, 1);
    mbar_init(bars + 8u * B_PRE, 1);
    mbar_init(bars + 8u * B_RESF, 1);
    mbar_init(bars + 8u * B_RESE, 4);
    mbar_init(bars + 8u * B_CSD, 4);
    mbar_init(bars + 8u * B_XRDY, 1);
    mbar_init(bars + 8u * (B_XRDY + 1), 1);
    fence_barrier_init();
  }
  if (warp != 12) named_bar_sync(0, 512);

  if (warp >= 12) {
    setmaxnreg_dec<32>();
    if (warp <= 13) {
      const bool act = warp == 13;
      uint32_t q = 4, dl = 0;
      bool prevw = false;
      unsigned ep1 = 0;
      if (act) {
        mbar_wait(bars + 8u * B_GO, 0);
        ep1 = __shfl_sync(0xffffffffu, (*(volatile unsigned*)(g_flags + F_DONE)) / NCTA + 1u, 0);
      } else {
#pragma unroll 1
        for (int s = 0; s < 16; s++) {
          const uint32_t fb = bars + 8u * (B_FULL + (s & 7)), sa = base + (s & 3) * 5 * UNIT;
          if (s >= 4) mbar_wait(bars + 8u * (B_EMPTY + ((s - 4) & 7)), ((s - 4) >> 3) & 1);
          if (elect_one()) {
            mbar_expect_tx(fb, 5 * UNIT);
            mbar_arrive(fb);
            tma_load_3d(sa, &P.xq[0], fb, 0, qr * 128, s);
            tma_load_3d(sa + 2 * UNIT, &P.wqkv[0], fb, hp * 64, s * 64, 0);
          }
        }
        if (elect_one()) mbar_arrive(bars + 8u * B_GO);
      }
      auto rbar = [&](int b0, int c) { return bars + 8u * b0 + ((8u * (c & 7)) ^ ((q & 1u) << 5)); };
      auto rpar = [&](int c) { return ((q + (c >> 2)) >> 1) & 1u; };
#pragma unroll 1
      for (int sg = 1; sg < NSEG; sg++) {
        const int code = seg_code(sg);
        const int L = (code >> 2) & 3, ch = code & 1;
        uint32_t seen = act ? 0u : 0xFFFFu;
        if ((code & 2) == 0) {
          const CUtensorMap* map = act ? &P.xq[L == 0 ? 0 : 1] : &P.wqkv[L & 1];
          if (act && (L == 0 || __any_sync(0xffffffffu, mbar_test(bars + 8u * (B_XRDY + ch), (L & 1) ^ 1)))) {
            seen = 0xFFFFu;
            fence_proxy_async_all();
          }
          const int k1 = ((code >> 4) & 12) + 4;
#pragma unroll 1
          for (int k4 = (code >> 2) & 12; k4 < k1; k4 += 4, q++) {
#pragma unroll
            for (int ks = 0; ks < 4; ks++) {
              const int kt = k4 + ks;
              if ((ks & 1) == 0)
                wait_mask<false>(g_flags + F_X + (ch * 8 + qr) * XSTR, 8, 6u * ep1 - 6u + 2u * L, 1u << (kt >> 1), seen, lane);
              if (ks == 0 && prevw) mbar_wait(rbar(B_EMPTY, -5), rpar(-5));
              else mbar_wait(rbar(B_EMPTY, ks - 4), rpar(-4));
              if (ks == 3 && prevw && !act) mbar_wait(bars + 8u * B_RESE, dl == 0 ? 1u : 0u);
              if (elect_one()) {
                mbar_expect_tx(rbar(B_FULL, ks), act ? 2 * UNIT : 3 * UNIT);
                tma_load_3d(base + ks * 5 * UNIT + (act ? 0 : 2 * UNIT) + (ks < 2 ? dl : 0u - dl), map, rbar(B_FULL, ks),
                            act ? 0 : hp * 64, act ? ch * 1024 + qr * 128 : kt * 64, act ? kt : 0);
              }
            }
            prevw = false;
          }
        } else {
          const CUtensorMap* map = act ? &P.o : &P.wo[L & 1];
          const bool pre = !act && w_pre(2 * L + ch);
          const int m0 = ch * 1024 + rt * 64;
#pragma unroll
          for (int kt = 0; kt < 16; kt++) {
            if (kt == 0 || kt == 1 || kt == 4 || kt == 8)
              wait_mask<false>(g_flags + F_O + (ch * 16 + rt) * OSTR, 16, 4u * ep1 - 3u + L,
                               kt == 0 ? 1u : (kt == 1 ? 0xEu : (kt == 4 ? 0xF0u : 0xFF00u)), seen, lane);
            if (kt < 4 && !prevw) mbar_wait(rbar(B_EMPTY, kt - 4 - (kt >> 1)), rpar(-4));
            else mbar_wait(rbar(B_EMPTY, kt - 6), rpar(kt - 6));
            if (kt == 6 && prevw && !act) mbar_wait(bars + 8u * B_RESE, dl == 0 ? 1u : 0u);
            if (elect_one()) {
              if (pre_idx(kt) >= 0 && pre) {
                mbar_arrive(rbar(B_FULL, kt));
              } else {
                mbar_expect_tx(rbar(B_FULL, kt), act ? UNIT : 2 * UNIT);
                const uint32_t da = base + w_ua(kt) * UNIT + (w_ua(kt) < 10 ? dl : 0u - dl);
                const uint32_t db = base + w_ub(kt) * UNIT + (w_ub(kt) < 10 ? dl : 0u - dl);
                tma_load_3d(act ? da : db, map, rbar(B_FULL, kt), 0, act ? m0 : kt * 64, act ? kt : ct * 2);
              }
            }
          }
          if (act && elect_one()) {
            mbar_expect_tx(bars + 8u * B_RESF, 2 * UNIT);
            tma_load_3d(base + 8 * UNIT + dl, &P.xr[L == 0 ? 0 : 1], bars + 8u * B_RESF, 0, m0, ct * 2);
          }
          q += 4;
          dl ^= 10u * UNIT;
          prevw = true;
        }
      }
    } else if (warp == 14) {
      const unsigned ep1 = (*(volatile unsigned*)(g_flags + F_DONE)) / NCTA + 1u;
#pragma unroll 1
      for (int inst = 0; inst < 8; inst++) {
        const int L = inst >> 1, ch = inst & 1, gb = ch * 8 + qr;
        unsigned* kvf = g_flags + F_KV;
        const unsigned kvt = 4u * ep1 - 3u + L, kvt0 = 2u * ep1 - 1u + (L >> 1);
        if (L & 1) {
          named_bar_sync(3, 192);
          named_bar_arrive(7, 160);
        } else {
          named_bar_arrive(3, 192);
          named_bar_sync(7, 160);
        }
        STA(34);
        if (elect_one()) {
          const unsigned* nf = kvf + ((gb - 1) * 16 + hp) * KSTR;
          if ((L & 1) == 0) {
            bulk_store(g_kvA[L >> 1][gb][hp][0], slots, 16384);
            bulk_commit();
            const uint32_t parA = ((L >> 1) * 2 + ch) & 1;
            const uint8_t* s1 = gb >= 1 ? g_kvA[L >> 1][gb - 1][hp][0] : g_zero;
            bool got = gb == 0;
#pragma unroll 1
            for (int it = 0; it < HPOLL && !got; it++) got = (int)(ld_acquire_u32(nf) - kvt) >= 0;
#pragma unroll 1
            for (int ph = 0; ph < 2; ph++) {
              if (got == (ph == 0)) {
                if (!got) wait_ge(nf, kvt);
                fence_proxy_async_all();
                STA(36);
                mbar_expect_tx(bars + 8u * B_HALO, 16384);
                bulk_load(slots + 2 * 16384, gb >= 1 ? s1 + 16384 : s1, 16384, bars + 8u * B_HALO);
              } else {
                bulk_wait0();
                fence_proxy_async_all();
                red_relaxed_add(kvf + (gb * 16 + hp) * KSTR + 1, 1u);
                STA(35);
              }
            }
            if (gb >= 1) {
              wait_ge(nf + 1, kvt0);
              fence_proxy_async_all();
            }
            STA(37);
            mbar_wait_lazy<100>(bars + 8u * B_REL, parA);
            STA(38);
            mbar_expect_tx(bars + 8u * (B_HALO + 1), 16384);
            bulk_load(slots + 16384, s1, 16384, bars + 8u * (B_HALO + 1));
            if (gb >= 2) {
              wait_ge2(kvf + ((gb - 2) * 16 + hp) * KSTR, kvt, kvt0);
              fence_proxy_async_all();
            }
            const uint8_t* s2 = gb >= 2 ? g_kvA[L >> 1][gb - 2][hp][0] : g_zero;
            STA(39);
            mbar_wait_lazy<100>(bars + 8u * (B_REL + 1), parA);
            STA(40);
            mbar_expect_tx(bars + 8u * (B_HALO + 2), 16384);
            bulk_load(slots, gb >= 2 ? s2 + 16384 : s2, 16384, bars + 8u * (B_HALO + 2));
            mbar_wait_lazy<100>(bars + 8u * (B_REL + 2), parA);
            STA(41);
            mbar_expect_tx(bars + 8u * (B_HALO + 3), 16384);
            bulk_load(slots + 2 * 16384, s2, 16384, bars + 8u * (B_HALO + 3));
          } else {
            const uint8_t* s1 = gb >= 1 ? g_kvB[L >> 1][gb - 1][hp] : g_zero;
            if (gb >= 1) {
              wait_ge(nf, kvt);
              fence_proxy_async_all();
            }
            mbar_expect_tx(bars + 8u * B_HALO, 4096);
            bulk_load(KB_ROW0 - 2048, s1, 2048, bars + 8u * B_HALO);
            bulk_load(VB_ROW0 - 2048, s1 + 2048, 2048, bars + 8u * B_HALO);
          }
          if (w_pre(inst)) {
            mbar_wait(bars + 8u * B_AFREE, (inst & 1) ^ 1);
            if (inst == 1) mbar_wait(bars + 8u * B_CSD, 0);
            mbar_expect_tx(bars + 8u * B_PRE, 8 * UNIT);
#pragma unroll 1
            for (int j = 0; j < 4; j++) {
              tma_load_3d(slots + j * 2 * UNIT, &P.wo[L & 1], bars + 8u * B_PRE, 0, (PRE0 + (j << PRESH)) * 64, ct * 2);
              __nanosleep(200);
            }
          }
        }
        __syncwarp();
      }
    } else {
      const unsigned ep1 = (*(volatile unsigned*)(g_flags + F_DONE)) / NCTA + 1u;
      mbar_wait(bars + 8u * B_GO, 0);
#pragma unroll 1
      for (int i = 0; i < 20; i++) {
        const char* src = i < 4 ? reinterpret_cast<const char*>(P.wo_p[0]) + (size_t)b * 16384 + i * 4096
                                : (i < 16 ? reinterpret_cast<const char*>(P.wqkv_p[1]) + (size_t)b * 49152 + (i - 4) * 4096
                                          : reinterpret_cast<const char*>(P.wo_p[1]) + (size_t)b * 16384 + (i - 16) * 4096);
        asm volatile("prefetch.global.L2 [%0];" ::"l"(src + lane * 128));
        __nanosleep(TRICKLE);
      }
#pragma unroll 1
      for (int inst = 2; inst < 8; inst++) {
        const int L = inst >> 1, ch = inst & 1, gb = ch * 8 + qr;
        uint32_t seen = 0;
        wait_mask<true>(g_flags + F_X + gb * XSTR, 8, 6u * ep1 - 6u + 2u * L, 0xFFu, seen, lane);
        if (lane == 0) mbar_arrive(bars + 8u * (B_XRDY + ch));
#pragma unroll 1
        for (int h = 0; h < 4; h++) {
          const float4* sp = &g_stats[L][0][gb * 128 + h * 32 + lane];
          const float4 s0 = sum_recs<4>(sp, S_LEN, ep1), s1 = sum_recs<4>(sp + 4 * S_LEN, S_LEN, ep1);
          sts32(base + OFF_RS + (ch * 128 + h * 32 + lane) * 4, ln_params(s0.x + s1.x, s0.y + s1.y));
        }
        if (inst == 2) {
          mbar_wait(bars + 8u * B_CSD, 0);
#pragma unroll 1
          for (int hf = 0; hf < 2; hf++) {
            const float4* cp = &g_cs[1][hp][0][hf * 32 + lane];
            const float4 s0 = sum_recs<4>(cp, 64, ep1), s1 = sum_recs<4>(cp + 4 * 64, 64, ep1);
            const uint32_t ca = base + OFF_CS + (192 + cs_pos(hf * 32 + lane)) * 4;
            sts32(ca, __float_as_uint(s0.x + s1.x));
            sts32(ca + 256, __float_as_uint(s0.y + s1.y));
            sts32(ca + 512, __float_as_uint(s0.z + s1.z));
          }
        }
        __syncwarp();
        if (lane == 0) mbar_arrive(bars + 8u * (B_PREP + ch));
      }
    }
  } else {
    const bool asst = warp >= 8;
    const bool lane0 = lane == 0;
    uint32_t tpar = 0;
    GTL(0);
    if (asst) {
      colsum_part(&P.wqkv[0], 0, qr, hp);
      if ((threadIdx.x & 127) < 2) mbar_arrive(bars + 8u * B_AFREE);
    } else if (warp >= 4) {
      PHASE_IDS
      {
        const unsigned ep1 = (*(volatile unsigned*)(g_flags + F_DONE)) / NCTA + 1u;
        const int row = b * 16 + (tid >> 3);
        const uint4* src = reinterpret_cast<const uint4*>(P.in_x + (size_t)row * DM) + (tid & 7);
        float s1 = 0.f, s2 = 0.f;
#pragma unroll 1
        for (int k = 0; k < 4; k++) {
          mbar_pace(bars + 8u * (B_EMPTY + 2 * k), 0);
          uint4 v[4];
#pragma unroll
          for (int j = 0; j < 4; j++) v[j] = __ldg(src + (k * 4 + j) * 8);
#pragma unroll
          for (int j = 0; j < 4; j++) {
            const uint32_t w[4] = {v[j].x, v[j].y, v[j].z, v[j].w};
#pragma unroll
            for (int e = 0; e < 4; e++) {
              const float x0 = bf_lo(w[e]), x1 = bf_hi(w[e]);
              s1 += x0 + x1;
              s2 = fmaf(x0, x0, fmaf(x1, x1, s2));
            }
          }
        }
#pragma unroll
        for (int o = 1; o < 8; o <<= 1) {
          s1 += __shfl_xor_sync(0xffffffffu, s1, o);
          s2 += __shfl_xor_sync(0xffffffffu, s2, o);
        }
        if ((tid & 7) == 0) st_rec(&g_stats[0][0][row], s1, s2, 0.f, ep1);
        if (tid == 0) sts32(base + OFF_EPOCH, ep1);
        if (tid < 64) {
          const float4 s0 = sum_recs<8>(&g_cs[0][hp][0][tid], 64, ep1);
          sts32(base + OFF_CS + cs_pos(tid) * 4, __float_as_uint(s0.x));
          sts32(base + OFF_CS + cs_pos(tid) * 4 + 256, __float_as_uint(s0.y));
          sts32(base + OFF_CS + cs_pos(tid) * 4 + 512, __float_as_uint(s0.z));
        }
#pragma unroll 1
        for (int cc = 0; cc < 2; cc++) {
          const float4 s0 = sum_recs<1>(&g_stats[0][0][(cc * 8 + qr) * 128 + tid], 0, ep1);
          sts32(base + OFF_RS + (cc * 128 + tid) * 4, ln_params(s0.x, s0.y));
        }
        named_bar_sync(2, 128);
        if (tid < 2) mbar_arrive(bars + 8u * (B_PREP + tid));
      }
    }
#pragma unroll 1
    for (int inst = asst ? 0 : warp >> 2; inst < 8; inst += asst ? 1 : 2) {
      const int L = inst >> 1, ch = inst & 1, gb = ch * 8 + qr;
      if (asst) {
        setmaxnreg_dec<24>();
        if (warp == 8) {
          named_bar_sync(3, 192);
          STA(32);
          if (elect_one()) {
            if ((L & 1) == 0) {
              bulk_store(g_kvA[L >> 1][gb][hp][1], slots + 16384, 16384);
            } else {
              bulk_store(g_kvB[L >> 1][gb][hp], KB_ROW0 + 112 * 128, 2048);
              bulk_store(g_kvB[L >> 1][gb][hp] + 2048, VB_ROW0 + 112 * 128, 2048);
            }
            bulk_commit();
            bulk_wait0();
            fence_proxy_async_all();
            red_relaxed_add(g_flags + F_KV + (gb * 16 + hp) * KSTR, 1u);
            STA(33);
          }
          __syncwarp();
        }
        named_bar_sync(4, 256);
        setmaxnreg_inc<128>();
      } else {
      setmaxnreg_inc<224>();
      {
        float acc[2][96];
        const int ksp = q_split(inst);
        int n = q_first(inst);
        uint32_t dlt = (ch == 0 && L > 0) ? 10u * (UNIT >> 4) : 0u;
        if (inst != 0 && inst != 2 && inst != 6) {
          mbar_wait_lazy<100>(bars + 8u * (B_TURN + ch), tpar);
          tpar ^= 1u;
        }
        if (L == 3) GTL(37);
        mbar_wait(bars + 8u * (B_FULL + (n & 7)), (n >> 3) & 1);
        GTL(1 + L * 8);
        {
          const uint32_t da = (base >> 4) + 0x10000u + dlt;
          const uint64_t db = desc_lo(da - 0x10000u + ((UNIT >> 4) << 16) + 2 * (UNIT >> 4));
          wgmma_fence();
          wgmma_n192_ssz_ta0_tb1(acc[0], desc_lo(da), db);
          wgmma_commit();
          wgmma_n192_ssz_ta0_tb1(acc[1], desc_lo(da + (UNIT >> 4)), db);
          wgmma_commit();
        }
#pragma unroll 1
        for (int k4 = 0; k4 < 4; k4++) {
          const bool brk = k4 + 1 == ksp && k4 < 3;
#pragma unroll
          for (int ks = 0; ks < 4; ks++, n++) {
            if (ks == 2 && k4 == 3) break;
            STAMP(inst == KSQ, k4 * 4 + ks);
            const uint32_t da = ((base + ks * 5 * UNIT) >> 4) + 0x10000u + (ks < 2 ? dlt : 0u - dlt);
            const uint32_t dbb = da - 0x10000u + ((UNIT >> 4) << 16) + 2 * (UNIT >> 4);
#pragma unroll
            for (int k16 = 0; k16 < 4; k16++) {
              if (ks == 0 && k16 == 0 && k4 == 0) continue;
              const uint64_t db = desc_lo(dbb + k16 * 128);
              wgmma_fence();
              wgmma_n192_ss_ta0_tb1(acc[0], desc_lo(da + k16 * 2), db, 1);
              wgmma_commit();
              wgmma_wait<1>();
              if (k16 == 0 && lane0 && (ks != 0 || k4 != ksp)) mbar_arrive(bars + 8u * (B_EMPTY + ((n - 1) & 7)));
              wgmma_fence();
              wgmma_n192_ss_ta0_tb1(acc[1], desc_lo(da + (UNIT >> 4) + k16 * 2), db, 1);
              wgmma_commit();
              bool ok = true;
              if (k16 == 2) ok = mbar_test(bars + 8u * (B_FULL + ((n + 1) & 7)), ((n + 1) >> 3) & 1) || (ks == 3 && brk);
              if (k16 == QTURN && ks == 3 && brk && lane0) mbar_arrive(bars + 8u * (B_TURN + (ch ^ 1)));
              if ((ks & 1) == 0 || k16 < 3) wgmma_wait<1>();
              if (k16 == 2 && !ok) mbar_wait(bars + 8u * (B_FULL + ((n + 1) & 7)), ((n + 1) >> 3) & 1);
            }
          }
          if (brk) {
            wgmma_wait<0>();
            if (lane0) mbar_arrive(bars + 8u * (B_EMPTY + ((n - 1) & 7)));
            n += 16;
            dlt ^= 10u * (UNIT >> 4);
            mbar_wait_lazy<100>(bars + 8u * (B_TURN + ch), tpar);
            tpar ^= 1u;
            STAMP(inst == KSQ, 17);
            mbar_wait(bars + 8u * (B_FULL + (n & 7)), (n >> 3) & 1);
          }
        }
        auto tail_group = [&](int u) {
          const uint32_t da = ((base + (2 + (u & 1)) * 5 * UNIT) >> 4) + 0x10000u - dlt;
          const uint32_t dbb = da - 0x10000u + ((UNIT >> 4) << 16) + 2 * (UNIT >> 4);
          wgmma_fence();
#pragma unroll
          for (int k16 = 0; k16 < 4; k16++)
            wgmma_n192_ss_ta0_tb1(acc[u < 2], desc_lo(da + (u < 2 ? UNIT >> 4 : 0) + k16 * 2), desc_lo(dbb + k16 * 128), 1);
          wgmma_commit();
        };
        tail_group(0);
        wgmma_wait<1>();
        if (lane0) mbar_arrive(bars + 8u * (B_EMPTY + ((n - 1) & 7)));
        mbar_wait(bars + 8u * (B_FULL + ((n + 1) & 7)), ((n + 1) >> 3) & 1);
        tail_group(1);
        PHASE_IDS
        mbar_wait(bars + 8u * (B_PREP + ch), L & 1);
        const bool afree = mbar_test(bars + 8u * B_AFREE, inst & 1);
        float nmean[2][2], rinv[2][2];
        const uint32_t csa = base + OFF_CS + ((L & 1) * 192 + 4 * c) * 4;
        uint4 cs[20];
        {
          uint32_t v[4];
#pragma unroll
          for (int i = 0; i < 4; i++)
            v[i] = lds32(base + OFF_RS + (ch * 128 + (i >> 1) * 64 + wwarp * 16 + g + 8 * (i & 1)) * 4);
#pragma unroll
          for (int t = 0; t < 2; t++) cs[t] = lds128(csa + (t + 4) * 64);
#pragma unroll
          for (int i = 0; i < 4; i++) {
            nmean[i >> 1][i & 1] = -bf_lo(v[i]);
            rinv[i >> 1][i & 1] = rcp_fast(bf_hi(v[i]));
            asm volatile("" : "+f"(rinv[i >> 1][i & 1]), "+f"(nmean[i >> 1][i & 1]));
          }
        }
        const int mat = lane >> 3;
        const uint32_t soff = (wwarp * 16 + (mat & 1) * 8 + (lane & 7)) * 128;
        const uint32_t kdst = ((L & 1) ? KB_ROW0 : slots) + soff, vdst = ((L & 1) ? VB_ROW0 : slots + 8192) + soff;
        const uint32_t hs = (L & 1) ? 8192 : 16384;
        const int rg = 2 * wwarp + (mat & 1);
        const uint32_t qdst = slots + 3 * 16384 + ((L & 1) ? soff : ((rg < 4 ? 2 * rg : 15 - 2 * rg) * 8 + (lane & 7)) * 128);
        tail_group(2);
        tail_group(3);
        if (EPT < 0 && lane0) mbar_arrive(bars + 8u * (B_TURN + (ch ^ 1)));
        if (!afree) {
          if (EPT >= 0 && lane0) mbar_arrive(bars + 8u * (B_TURN + (ch ^ 1)));
          wgmma_wait<1>();
          if (lane0) mbar_arrive(bars + 8u * (B_EMPTY + (n & 7)));
          wgmma_wait<0>();
          if (lane0) mbar_arrive(bars + 8u * (B_EMPTY + ((n + 1) & 7)));
          mbar_wait(bars + 8u * B_AFREE, inst & 1);
        }
        wgmma_wait<2>();
        reg_fence<96>(acc[1]);
        STAMP(inst == KSQ, 15);
#pragma unroll
        for (int t = 2; t < CSPF; t++) cs[t] = lds128(csa + (t + 4) * 64);
#pragma unroll
        for (int t = 0; t < 20; t++) {
          const int p = t >= 16 ? 0 : ((t >> 2) & 1) + 1, jp = t & 3;
          if (t + CSPF < 20) {
            const int tn = t + CSPF, jn = tn >= 16 ? tn - 16 : (tn & 7) + 4;
            cs[tn] = lds128(csa + jn * 64);
          }
          if (t == EPT && lane0 && afree) mbar_arrive(bars + 8u * (B_TURN + (ch ^ 1)));
          if (t == EPW1) {
            wgmma_wait<1>();
            if (lane0 && afree) mbar_arrive(bars + 8u * (B_EMPTY + (n & 7)));
          }
          if (t == EPW0) {
            wgmma_wait<0>();
            reg_fence<96>(acc[0]);
            if (lane0 && afree) mbar_arrive(bars + 8u * (B_EMPTY + ((n + 1) & 7)));
            STAMP(inst == KSQ, 16);
            GTL(2 + L * 8);
          }
          if (t == 16) {
#pragma unroll
            for (int i = 0; i < 4; i++) rinv[i >> 1][i & 1] *= SM_C;
          }
          const int j = p * 8 + 2 * jp;
          const float2 cs0 = make_float2(__uint_as_float(cs[t].x), __uint_as_float(cs[t].y));
          const float2 cs1 = make_float2(__uint_as_float(cs[t].z), __uint_as_float(cs[t].w));
          const uint32_t sw = ((2 * jp + (mat >> 1)) ^ (lane & 7)) << 4;
#pragma unroll
          for (int h = 0; h < 2; h++) {
            if (t < 16 && h != (t < 8 ? 1 : 0)) continue;
            const float* a = &acc[h][4 * j];
            const uint32_t r0 = pack_bf16x2(fmaf(nmean[h][0], cs0.x, a[0]) * rinv[h][0], fmaf(nmean[h][0], cs0.y, a[1]) * rinv[h][0]);
            const uint32_t r1 = pack_bf16x2(fmaf(nmean[h][1], cs0.x, a[2]) * rinv[h][1], fmaf(nmean[h][1], cs0.y, a[3]) * rinv[h][1]);
            const uint32_t r2 = pack_bf16x2(fmaf(nmean[h][0], cs1.x, a[4]) * rinv[h][0], fmaf(nmean[h][0], cs1.y, a[5]) * rinv[h][0]);
            const uint32_t r3 = pack_bf16x2(fmaf(nmean[h][1], cs1.x, a[6]) * rinv[h][1], fmaf(nmean[h][1], cs1.y, a[7]) * rinv[h][1]);
            const uint32_t dst = p == 0 ? qdst + h * 8192 : (p == 1 ? kdst : vdst) + h * hs;
            stmatrix_x4(dst + sw, r0, r1, r2, r3);
          }
          if (t == 7 || t == 15) {
            fence_proxy_async_smem();
            named_bar_arrive(t == 7 ? 3 : 7, t == 7 ? 192 : 160);
            sched_fence(P.zero);
          }
        }
      }
      fence_proxy_async_smem();
      setmaxnreg_dec<128>();
      named_bar_sync(4, 256);
      }
      GTL(3 + L * 8);
      {
        PHASE_IDS
        if ((L & 1) == 0) attention_a(asst, L, gb, hp, inst & 1, ch, (tid_ >> 5) & 3, lane, P.zero);
        else attention_b(asst, gb, inst & 1, wwarp, lane);
        GTL(4 + L * 8);
        fence_proxy_async_smem();
      }
      if (asst) {
        named_bar_arrive(5, 256);
        if (inst == 1) {
          mbar_wait(bars + 8u * B_AFREE, 0);
          colsum_part(&P.wqkv[1], 1, qr, hp);
          if (lane0) mbar_arrive(bars + 8u * B_CSD);
        }
        continue;
      }
      {
        named_bar_sync(5, 256);
        const int wwarp = warp & 3;
        if (wwarp < 2 && elect_one()) {
          tma_store_3d(&P.o, ((L & 1) ? slots + 3 * 16384 : OA_TILE) + wwarp * 8192, 0, gb * 128 + wwarp * 64, hp);
          bulk_commit();
          bulk_wait0();
          mbar_arrive(bars + 8u * B_AFREE);
          fence_proxy_async_all();
          red_relaxed_add(g_flags + F_O + (gb * 2 + wwarp) * OSTR + hp, 1u);
        }
        __syncwarp();
      }
      GTL(5 + L * 8);

      {
        float acc[64];
        const int n0 = w_first(inst);
        const bool pre = w_pre(inst);
        const uint32_t dl = ch * 10u * (UNIT >> 4);
        mbar_wait_lazy<100>(bars + 8u * (B_TURN + ch), tpar);
        tpar ^= 1u;
        mbar_wait(bars + 8u * (B_FULL + (n0 & 7)), (n0 >> 3) & 1);
        GTL(6 + L * 8);
#pragma unroll
        for (int kt = 0; kt < 16; kt++) {
          const int n = n0 + kt;
          STAMP(inst == KSW, 20 + kt);
          const uint32_t da = ((base + w_ua(kt) * UNIT) >> 4) + 0x10000u + (w_ua(kt) < 10 ? dl : 0u - dl);
          uint32_t db = ((base + w_ub(kt) * UNIT) >> 4) + ((UNIT >> 4) << 16) + (w_ub(kt) < 10 ? dl : 0u - dl);
          if (pre_idx(kt) >= 0 && pre) db = ((slots + pre_idx(kt) * 2 * UNIT) >> 4) + ((UNIT >> 4) << 16);
          if (kt == PRE0 && pre) mbar_wait(bars + 8u * B_PRE, __popc(PREMASK & ((1u << inst) - 1u)) & 1);
          if (kt == 15 && lane0 && (inst & 3) != 0) mbar_arrive(bars + 8u * (B_TURN + (ch ^ 1)));
          wgmma_fence();
          if (kt == 0) wgmma_n128_ssz_ta0_tb1(acc, desc_lo(da), desc_lo(db));
#pragma unroll
          for (int k16 = kt == 0 ? 1 : 0; k16 < 4; k16++) wgmma_n128_ss_ta0_tb1(acc, desc_lo(da + 2 * k16), desc_lo(db + 128 * k16), 1);
          wgmma_commit();
          const uint32_t nb = bars + 8u * (kt == 15 ? B_RESF : B_FULL + ((n + 1) & 7)), np = kt == 15 ? ch : ((n + 1) >> 3) & 1;
          const bool ok = mbar_test(nb, np);
          if (kt > 0) {
            wgmma_wait<1>();
            if (lane0) mbar_arrive(bars + 8u * (B_EMPTY + ((n - 1) & 7)));
          }
          if (!ok) mbar_wait(nb, np);
        }
        PHASE_IDS
        const uint32_t xb = base + (8 + ch * 10) * UNIT;
        const int mat = lane >> 3;
        const uint32_t xrow = xb + (wwarp * 16 + (mat & 1) * 8 + (lane & 7)) * 128;
        uint32_t xv[8][4];
#pragma unroll
        for (int jp = 0; jp < 8; jp++)
          ldmatrix_x4(xv[jp], xrow + (jp >> 2) * UNIT + (((2 * (jp & 3) + (mat >> 1)) ^ (lane & 7)) << 4));
        wgmma_wait<0>();
        reg_fence<64>(acc);
        if (lane0) mbar_arrive(bars + 8u * (B_EMPTY + ((n0 + 15) & 7)));
        STAMP(inst == KSW, 36);
        GTL(7 + L * 8);
#pragma unroll
        for (int jp = 0; jp < 8; jp++) {
#pragma unroll
          for (int q = 0; q < 4; q++) xv[jp][q] = add_bf16x2(xv[jp][q], pack_bf16x2(acc[8 * jp + 2 * q], acc[8 * jp + 2 * q + 1]));
          stmatrix_x4(xrow + (jp >> 2) * UNIT + (((2 * (jp & 3) + (mat >> 1)) ^ (lane & 7)) << 4), xv[jp][0], xv[jp][1],
                      xv[jp][2], xv[jp][3]);
        }
        fence_proxy_async_smem();
        named_bar_sync(1 + ch, 128);
        const int grow = ch * 1024 + rt * 64;
        if (wwarp == 0) {
          if (elect_one()) {
            tma_store_3d(&P.xr[L == 3 ? 2 : 1], xb, 0, grow, ct * 2);
            bulk_commit();
            bulk_wait_read0();
            mbar_arrive(bars + 8u * B_RESE);
            bulk_wait0();
            TGET(t35);
            fence_proxy_async_all();
            if (L < 3) red_relaxed_add(g_flags + F_X + (ch * 8 + (rt >> 1)) * XSTR + ct, 1u);
            if (L == 2) TPUT(ch, 35, t35);
          }
          __syncwarp();
        } else if (lane == 0) {
          mbar_arrive(bars + 8u * B_RESE);
        }
        if (L < 3) {
          const unsigned ep1 = lds32(base + OFF_EPOCH);
          float s1[2] = {0.f, 0.f}, s2[2] = {0.f, 0.f};
#pragma unroll
          for (int jp = 0; jp < 8; jp++)
#pragma unroll
            for (int q = 0; q < 4; q++) {
              const float x0 = bf_lo(xv[jp][q]), x1 = bf_hi(xv[jp][q]);
              s1[q & 1] += x0 + x1;
              s2[q & 1] = fmaf(x0, x0, fmaf(x1, x1, s2[q & 1]));
            }
#pragma unroll
          for (int r = 0; r < 2; r++) {
            s1[r] += __shfl_xor_sync(0xffffffffu, s1[r], 1);
            s2[r] += __shfl_xor_sync(0xffffffffu, s2[r], 1);
            s1[r] += __shfl_xor_sync(0xffffffffu, s1[r], 2);
            s2[r] += __shfl_xor_sync(0xffffffffu, s2[r], 2);
            if (c == 0) st_rec(&g_stats[L + 1][ct][grow + wwarp * 16 + g + 8 * r], s1[r], s2[r], 0.f, ep1);
          }
        }
        GTL(8 + L * 8);
      }
    }
    if (threadIdx.x == 128) atomicAdd(g_flags + F_DONE, 1u);
  }
}

typedef CUresult (*PFN_tmEncode)(CUtensorMap*, CUtensorMapDataType, cuuint32_t, void*, const cuuint64_t*,
                                 const cuuint64_t*, const cuuint32_t*, const cuuint32_t*, CUtensorMapInterleave,
                                 CUtensorMapSwizzle, CUtensorMapL2promotion, CUtensorMapFloatOOBfill);

PFN_tmEncode get_encode_fn() {
  static PFN_tmEncode fn = nullptr;
  if (!fn) {
    cudaDriverEntryPointQueryResult qr;
    void* p = nullptr;
    cudaGetDriverEntryPoint("cuTensorMapEncodeTiled", &p, cudaEnableDefault, &qr);
    fn = (PFN_tmEncode)p;
  }
  return fn;
}

CUtensorMap make_map(const void* ptr, int rows, int cols, int inner, int box_rows, int box_blk) {
  CUtensorMap m;
  cuuint64_t gdim[3] = {(cuuint64_t)inner, (cuuint64_t)rows, (cuuint64_t)(cols / inner)};
  cuuint64_t gstr[2] = {(cuuint64_t)cols * 2, (cuuint64_t)inner * 2};
  cuuint32_t box[3] = {64, (cuuint32_t)box_rows, (cuuint32_t)box_blk};
  cuuint32_t estr[3] = {1, 1, 1};
  get_encode_fn()(&m, CU_TENSOR_MAP_DATA_TYPE_BFLOAT16, 3, const_cast<void*>(ptr), gdim, gstr, box, estr,
                  CU_TENSOR_MAP_INTERLEAVE_NONE, CU_TENSOR_MAP_SWIZZLE_128B, CU_TENSOR_MAP_L2_PROMOTION_L2_128B,
                  CU_TENSOR_MAP_FLOAT_OOB_FILL_NONE);
  return m;
}

}

extern "C" void kernel_launch(void* const* d_in, const int* in_sizes, int n_in, void* d_out, int out_size) {
  (void)in_sizes; (void)n_in; (void)out_size;
  void *p_o, *p_x;
  cudaGetSymbolAddress(&p_o, g_o);
  cudaGetSymbolAddress(&p_x, g_x);
  static bool attr_done = false;
  if (!attr_done) {
    cudaFuncSetAttribute(fused_kernel, cudaFuncAttributeMaxDynamicSharedMemorySize, SMEM_BYTES);
    attr_done = true;
  }
  Params P;
  P.in_x = (const __nv_bfloat16*)d_in[0];
  P.wqkv_p[0] = (const __nv_bfloat16*)d_in[1];
  P.wo_p[0] = (const __nv_bfloat16*)d_in[2];
  P.wqkv_p[1] = (const __nv_bfloat16*)d_in[4];
  P.wo_p[1] = (const __nv_bfloat16*)d_in[5];
  P.out = (__nv_bfloat16*)d_out;
  P.zero = 0;
  P.xq[0] = make_map(P.in_x, S_LEN, DM, 64, 128, 1);
  P.xq[1] = make_map(p_x, S_LEN, DM, 64, 128, 1);
  P.xr[0] = make_map(P.in_x, S_LEN, DM, 64, 64, 2);
  P.xr[1] = make_map(p_x, S_LEN, DM, 64, 64, 2);
  P.xr[2] = make_map(d_out, S_LEN, DM, 64, 64, 2);
  P.o = make_map(p_o, S_LEN, DM, 64, 64, 1);
  for (int t = 0; t < 2; t++) {
    P.wqkv[t] = make_map(P.wqkv_p[t], DM, NQKV, 1024, 64, 3);
    P.wo[t] = make_map(P.wo_p[t], DM, DM, 64, 64, 2);
  }
  fused_kernel<<<NCTA, 512, SMEM_BYTES>>>(P);
}
```

```cpp
#include <cuda_runtime.h>
#include <cuda_bf16.h>
#include <cuda.h>
#include <stdint.h>

namespace {

constexpr int S_LEN = 2048;
constexpr int DM = 1024;
constexpr int NQKV = 3072;
constexpr int NCTA = 128;

__device__ __align__(1024) uint8_t g_kvA[2][16][16][2][16384];
__device__ __align__(1024) uint8_t g_kvB[2][16][16][4096];
__device__ __align__(1024) uint8_t g_zero[16384];
__device__ __align__(1024) __nv_bfloat16 g_o[S_LEN * DM];
__device__ __align__(1024) __nv_bfloat16 g_x[S_LEN * DM];
__device__ __align__(1024) float4 g_stats[4][8][S_LEN];
__device__ __align__(1024) float4 g_cs[2][16][8][64];
constexpr int F_X = 0;
constexpr int XSTR = 32, OSTR = 32, KSTR = 32;
constexpr int F_O = F_X + 16 * XSTR;
constexpr int F_KV = F_O + 32 * OSTR;
constexpr int F_DONE = F_KV + 256 * KSTR;
__device__ __align__(1024) unsigned g_flags[F_DONE + 32];

constexpr uint32_t SBASE = 1024;
constexpr int UNIT = 8192;
constexpr int NUNITS = 20;
constexpr int OFF_SLOT = NUNITS * UNIT;
constexpr int OFF_CS = OFF_SLOT + 4 * 16384;
constexpr int OFF_RS = OFF_CS + 1536;
constexpr int OFF_BAR = OFF_RS + 1024;
constexpr int OFF_EPOCH = OFF_BAR + 296;
constexpr int OFF_TS = OFF_BAR + 304;
constexpr int SMEM_BYTES = OFF_TS;
constexpr int B_FULL = 0, B_EMPTY = 8, B_PREP = 16, B_HALO = 18, B_REL = 22, B_AFREE = 25, B_TURN = 26, B_XRDY = 28,
              B_CS = 30, B_CSD = 31, B_GO = 32, B_PRE = 33, B_RESF = 34, B_RESE = 35;

__device__ __forceinline__ uint32_t smem_u32(const void* p) { return (uint32_t)__cvta_generic_to_shared(p); }

__device__ __forceinline__ void mbar_init(uint32_t bar, uint32_t cnt) {
  asm volatile("mbarrier.init.shared::cta.b64 [%0], %1;" ::"r"(bar), "r"(cnt));
}
__device__ __forceinline__ void mbar_expect_tx(uint32_t bar, uint32_t bytes) {
  asm volatile("mbarrier.arrive.expect_tx.shared::cta.b64 _, [%0], %1;" ::"r"(bar), "r"(bytes) : "memory");
}
__device__ __forceinline__ void mbar_arrive(uint32_t bar) {
  asm volatile("mbarrier.arrive.shared::cta.b64 _, [%0];" ::"r"(bar) : "memory");
}
__device__ __forceinline__ bool mbar_try_wait(uint32_t bar, uint32_t parity) {
  uint32_t ok;
  asm volatile(
      "{\n.reg .pred p;\nmbarrier.try_wait.parity.shared::cta.b64 p, [%1], %2;\nselp.b32 %0, 1, 0, p;\n}\n"
      : "=r"(ok)
      : "r"(bar), "r"(parity)
      : "memory");
  return ok != 0;
}
__device__ __forceinline__ bool mbar_test(uint32_t bar, uint32_t parity) {
  uint32_t ok;
  asm volatile(
      "{\n.reg .pred p;\nmbarrier.test_wait.parity.shared::cta.b64 p, [%1], %2;\nselp.b32 %0, 1, 0, p;\n}\n"
      : "=r"(ok)
      : "r"(bar), "r"(parity)
      : "memory");
  return ok != 0;
}
__device__ __forceinline__ void mbar_wait(uint32_t bar, uint32_t parity) {
#pragma unroll 1
  for (uint32_t it = 0; it < (1u << 18); ++it) {
    if (mbar_try_wait(bar, parity)) return;
  }
}
__device__ __forceinline__ void mbar_pace(uint32_t bar, uint32_t parity) {
#pragma unroll 1
  for (uint32_t it = 0; it < 24; ++it) {
    if (mbar_try_wait(bar, parity)) return;
  }
}
template <int NS>
__device__ __forceinline__ void mbar_wait_lazy(uint32_t bar, uint32_t parity) {
#pragma unroll 1
  for (uint32_t it = 0; it < (1u << 18); ++it) {
    if (mbar_try_wait(bar, parity)) return;
    __nanosleep(NS);
  }
}
__device__ __forceinline__ bool elect_one() {
  uint32_t ok;
  asm volatile("{\n.reg .pred p;\nelect.sync _|p, 0xffffffff;\nselp.b32 %0, 1, 0, p;\n}\n" : "=r"(ok));
  return ok != 0;
}
__device__ __forceinline__ void fence_barrier_init() { asm volatile("fence.mbarrier_init.release.cluster;" ::: "memory"); }
__device__ __forceinline__ void fence_proxy_async_smem() { asm volatile("fence.proxy.async.shared::cta;" ::: "memory"); }
__device__ __forceinline__ void fence_proxy_async_all() { asm volatile("fence.proxy.async.global;" ::: "memory"); }

__device__ __forceinline__ void tma_load_3d(uint32_t dst, const CUtensorMap* map, uint32_t bar, int c0, int c1, int c2) {
  asm volatile(
      "cp.async.bulk.tensor.3d.shared::cluster.global.mbarrier::complete_tx::bytes [%0], [%1, {%3, %4, %5}], [%2];" ::"r"(dst),
      "l"(map), "r"(bar), "r"(c0), "r"(c1), "r"(c2)
      : "memory");
}
__device__ __forceinline__ void bulk_load(uint32_t dst, const void* src, uint32_t bytes, uint32_t bar) {
  asm volatile("cp.async.bulk.shared::cluster.global.mbarrier::complete_tx::bytes [%0], [%1], %2, [%3];" ::"r"(dst),
               "l"(src), "r"(bytes), "r"(bar)
               : "memory");
}
__device__ __forceinline__ void bulk_store(void* dst, uint32_t src, uint32_t bytes) {
  asm volatile("cp.async.bulk.global.shared::cta.bulk_group [%0], [%1], %2;" ::"l"(dst), "r"(src), "r"(bytes) : "memory");
}
__device__ __forceinline__ void tma_store_3d(const CUtensorMap* map, uint32_t src, int c0, int c1, int c2) {
  asm volatile("cp.async.bulk.tensor.3d.global.shared::cta.bulk_group [%0, {%2, %3, %4}], [%1];" ::"l"(map), "r"(src),
               "r"(c0), "r"(c1), "r"(c2)
               : "memory");
}
__device__ __forceinline__ void bulk_commit() { asm volatile("cp.async.bulk.commit_group;" ::: "memory"); }
__device__ __forceinline__ void bulk_wait_read0() { asm volatile("cp.async.bulk.wait_group.read 0;" ::: "memory"); }
__device__ __forceinline__ void bulk_wait0() { asm volatile("cp.async.bulk.wait_group 0;" ::: "memory"); }
__device__ __forceinline__ void named_bar_sync(int id, int nthreads) {
  asm volatile("bar.sync %0, %1;" ::"r"(id), "r"(nthreads) : "memory");
}
__device__ __forceinline__ void named_bar_arrive(int id, int nthreads) {
  asm volatile("bar.arrive %0, %1;" ::"r"(id), "r"(nthreads) : "memory");
}

__device__ __forceinline__ void wgmma_fence() { asm volatile("wgmma.fence.sync.aligned;\n" ::: "memory"); }
__device__ __forceinline__ void wgmma_commit() { asm volatile("wgmma.commit_group.sync.aligned;\n" ::: "memory"); }
template <int N>
__device__ __forceinline__ void wgmma_wait() {
  asm volatile("wgmma.wait_group.sync.aligned %0;\n" ::"n"(N) : "memory");
}
template <int R>
__device__ __forceinline__ void setmaxnreg_inc() { asm volatile("setmaxnreg.inc.sync.aligned.u32 %0;\n" ::"n"(R)); }
template <int R>
__device__ __forceinline__ void setmaxnreg_dec() { asm volatile("setmaxnreg.dec.sync.aligned.u32 %0;\n" ::"n"(R)); }
template <int N>
__device__ __forceinline__ void reg_fence(float* r) {
#pragma unroll
  for (int i = 0; i < N; i++) asm volatile("" : "+f"(r[i])::"memory");
}

template <int N>
__device__ __forceinline__ void reg_define(float* r) {
#pragma unroll
  for (int i = 0; i < N; i++) r[i] = 0.f;
}

__device__ __forceinline__ uint64_t desc_lo(uint32_t lo) {
  uint64_t d;
  asm("mov.b64 %0, {%1, %2};" : "=l"(d) : "r"(lo), "r"(0x40000040u));
  return d;
}
__device__ __forceinline__ uint64_t make_desc(uint32_t addr, uint32_t lbo_bytes) {
  return desc_lo((addr >> 4) + ((lbo_bytes >> 4) << 16));
}

__device__ __forceinline__ void wgmma_n192_ss_ta0_tb1(float* d, uint64_t descA, uint64_t descB, int scaleD) {
  asm volatile("{\n.reg .pred p;\nsetp.ne.b32 p, %98, 0;\n"
    "wgmma.mma_async.sync.aligned.m64n192k16.f32.bf16.bf16 {%0, %1, %2, %3, %4, %5, %6, %7, %8, %9, %10, %11, %12, %13, %14, %15, %16, %17, %18, %19, %20, %21, %22, %23, %24, %25, %26, %27, %28, %29, %30, %31, %32, %33, %34, %35, %36, %37, %38, %39, %40, %41, %42, %43, %44, %45, %46, %47, %48, %49, %50, %51, %52, %53, %54, %55, %56, %57, %58, %59, %60, %61, %62, %63, %64, %65, %66, %67, %68, %69, %70, %71, %72, %73, %74, %75, %76, %77, %78, %79, %80, %81, %82, %83, %84, %85, %86, %87, %88, %89, %90, %91, %92, %93, %94, %95}, %96, %97, p, 1, 1, 0, 1;\n}\n"
    : "+f"(d[0]), "+f"(d[1]), "+f"(d[2]), "+f"(d[3]), "+f"(d[4]), "+f"(d[5]), "+f"(d[6]), "+f"(d[7]), "+f"(d[8]), "+f"(d[9]), "+f"(d[10]), "+f"(d[11]), "+f"(d[12]), "+f"(d[13]), "+f"(d[14]), "+f"(d[15]), "+f"(d[16]), "+f"(d[17]), "+f"(d[18]), "+f"(d[19]), "+f"(d[20]), "+f"(d[21]), "+f"(d[22]), "+f"(d[23]), "+f"(d[24]), "+f"(d[25]), "+f"(d[26]), "+f"(d[27]), "+f"(d[28]), "+f"(d[29]), "+f"(d[30]), "+f"(d[31]), "+f"(d[32]), "+f"(d[33]), "+f"(d[34]), "+f"(d[35]), "+f"(d[36]), "+f"(d[37]), "+f"(d[38]), "+f"(d[39]), "+f"(d[40]), "+f"(d[41]), "+f"(d[42]), "+f"(d[43]), "+f"(d[44]), "+f"(d[45]), "+f"(d[46]), "+f"(d[47]), "+f"(d[48]), "+f"(d[49]), "+f"(d[50]), "+f"(d[51]), "+f"(d[52]), "+f"(d[53]), "+f"(d[54]), "+f"(d[55]), "+f"(d[56]), "+f"(d[57]), "+f"(d[58]), "+f"(d[59]), "+f"(d[60]), "+f"(d[61]), "+f"(d[62]), "+f"(d[63]), "+f"(d[64]), "+f"(d[65]), "+f"(d[66]), "+f"(d[67]), "+f"(d[68]), "+f"(d[69]), "+f"(d[70]), "+f"(d[71]), "+f"(d[72]), "+f"(d[73]), "+f"(d[74]), "+f"(d[75]), "+f"(d[76]), "+f"(d[77]), "+f"(d[78]), "+f"(d[79]), "+f"(d[80]), "+f"(d[81]), "+f"(d[82]), "+f"(d[83]), "+f"(d[84]), "+f"(d[85]), "+f"(d[86]), "+f"(d[87]), "+f"(d[88]), "+f"(d[89]), "+f"(d[90]), "+f"(d[91]), "+f"(d[92]), "+f"(d[93]), "+f"(d[94]), "+f"(d[95])
    : "l"(descA), "l"(descB), "r"(scaleD));
}

__device__ __forceinline__ void wgmma_n128_ss_ta0_tb1(float* d, uint64_t descA, uint64_t descB, int scaleD) {
  asm volatile("{\n.reg .pred p;\nsetp.ne.b32 p, %66, 0;\n"
    "wgmma.mma_async.sync.aligned.m64n128k16.f32.bf16.bf16 {%0, %1, %2, %3, %4, %5, %6, %7, %8, %9, %10, %11, %12, %13, %14, %15, %16, %17, %18, %19, %20, %21, %22, %23, %24, %25, %26, %27, %28, %29, %30, %31, %32, %33, %34, %35, %36, %37, %38, %39, %40, %41, %42, %43, %44, %45, %46, %47, %48, %49, %50, %51, %52, %53, %54, %55, %56, %57, %58, %59, %60, %61, %62, %63}, %64, %65, p, 1, 1, 0, 1;\n}\n"
    : "+f"(d[0]), "+f"(d[1]), "+f"(d[2]), "+f"(d[3]), "+f"(d[4]), "+f"(d[5]), "+f"(d[6]), "+f"(d[7]), "+f"(d[8]), "+f"(d[9]), "+f"(d[10]), "+f"(d[11]), "+f"(d[12]), "+f"(d[13]), "+f"(d[14]), "+f"(d[15]), "+f"(d[16]), "+f"(d[17]), "+f"(d[18]), "+f"(d[19]), "+f"(d[20]), "+f"(d[21]), "+f"(d[22]), "+f"(d[23]), "+f"(d[24]), "+f"(d[25]), "+f"(d[26]), "+f"(d[27]), "+f"(d[28]), "+f"(d[29]), "+f"(d[30]), "+f"(d[31]), "+f"(d[32]), "+f"(d[33]), "+f"(d[34]), "+f"(d[35]), "+f"(d[36]), "+f"(d[37]), "+f"(d[38]), "+f"(d[39]), "+f"(d[40]), "+f"(d[41]), "+f"(d[42]), "+f"(d[43]), "+f"(d[44]), "+f"(d[45]), "+f"(d[46]), "+f"(d[47]), "+f"(d[48]), "+f"(d[49]), "+f"(d[50]), "+f"(d[51]), "+f"(d[52]), "+f"(d[53]), "+f"(d[54]), "+f"(d[55]), "+f"(d[56]), "+f"(d[57]), "+f"(d[58]), "+f"(d[59]), "+f"(d[60]), "+f"(d[61]), "+f"(d[62]), "+f"(d[63])
    : "l"(descA), "l"(descB), "r"(scaleD));
}

__device__ __forceinline__ void wgmma_n192_ssz_ta0_tb1(float* d, uint64_t descA, uint64_t descB) {
  asm volatile("{\n.reg .pred p;\nsetp.ne.b32 p, 0, 0;\n"
    "wgmma.mma_async.sync.aligned.m64n192k16.f32.bf16.bf16 {%0, %1, %2, %3, %4, %5, %6, %7, %8, %9, %10, %11, %12, %13, %14, %15, %16, %17, %18, %19, %20, %21, %22, %23, %24, %25, %26, %27, %28, %29, %30, %31, %32, %33, %34, %35, %36, %37, %38, %39, %40, %41, %42, %43, %44, %45, %46, %47, %48, %49, %50, %51, %52, %53, %54, %55, %56, %57, %58, %59, %60, %61, %62, %63, %64, %65, %66, %67, %68, %69, %70, %71, %72, %73, %74, %75, %76, %77, %78, %79, %80, %81, %82, %83, %84, %85, %86, %87, %88, %89, %90, %91, %92, %93, %94, %95}, %96, %97, p, 1, 1, 0, 1;\n}\n"
    : "=f"(d[0]), "=f"(d[1]), "=f"(d[2]), "=f"(d[3]), "=f"(d[4]), "=f"(d[5]), "=f"(d[6]), "=f"(d[7]), "=f"(d[8]), "=f"(d[9]), "=f"(d[10]), "=f"(d[11]), "=f"(d[12]), "=f"(d[13]), "=f"(d[14]), "=f"(d[15]), "=f"(d[16]), "=f"(d[17]), "=f"(d[18]), "=f"(d[19]), "=f"(d[20]), "=f"(d[21]), "=f"(d[22]), "=f"(d[23]), "=f"(d[24]), "=f"(d[25]), "=f"(d[26]), "=f"(d[27]), "=f"(d[28]), "=f"(d[29]), "=f"(d[30]), "=f"(d[31]), "=f"(d[32]), "=f"(d[33]), "=f"(d[34]), "=f"(d[35]), "=f"(d[36]), "=f"(d[37]), "=f"(d[38]), "=f"(d[39]), "=f"(d[40]), "=f"(d[41]), "=f"(d[42]), "=f"(d[43]), "=f"(d[44]), "=f"(d[45]), "=f"(d[46]), "=f"(d[47]), "=f"(d[48]), "=f"(d[49]), "=f"(d[50]), "=f"(d[51]), "=f"(d[52]), "=f"(d[53]), "=f"(d[54]), "=f"(d[55]), "=f"(d[56]), "=f"(d[57]), "=f"(d[58]), "=f"(d[59]), "=f"(d[60]), "=f"(d[61]), "=f"(d[62]), "=f"(d[63]), "=f"(d[64]), "=f"(d[65]), "=f"(d[66]), "=f"(d[67]), "=f"(d[68]), "=f"(d[69]), "=f"(d[70]), "=f"(d[71]), "=f"(d[72]), "=f"(d[73]), "=f"(d[74]), "=f"(d[75]), "=f"(d[76]), "=f"(d[77]), "=f"(d[78]), "=f"(d[79]), "=f"(d[80]), "=f"(d[81]), "=f"(d[82]), "=f"(d[83]), "=f"(d[84]), "=f"(d[85]), "=f"(d[86]), "=f"(d[87]), "=f"(d[88]), "=f"(d[89]), "=f"(d[90]), "=f"(d[91]), "=f"(d[92]), "=f"(d[93]), "=f"(d[94]), "=f"(d[95])
    : "l"(descA), "l"(descB));
}

__device__ __forceinline__ void wgmma_n192_rs_tb1(float* d, uint32_t a0, uint32_t a1, uint64_t descB) {
  asm volatile("{\n.reg .pred p;\nsetp.eq.b32 p, 0, 0;\n"
    "wgmma.mma_async.sync.aligned.m64n192k16.f32.bf16.bf16 {%0, %1, %2, %3, %4, %5, %6, %7, %8, %9, %10, %11, %12, %13, %14, %15, %16, %17, %18, %19, %20, %21, %22, %23, %24, %25, %26, %27, %28, %29, %30, %31, %32, %33, %34, %35, %36, %37, %38, %39, %40, %41, %42, %43, %44, %45, %46, %47, %48, %49, %50, %51, %52, %53, %54, %55, %56, %57, %58, %59, %60, %61, %62, %63, %64, %65, %66, %67, %68, %69, %70, %71, %72, %73, %74, %75, %76, %77, %78, %79, %80, %81, %82, %83, %84, %85, %86, %87, %88, %89, %90, %91, %92, %93, %94, %95}, {%96, %97, %98, %98}, %99, p, 1, 1, 1;\n}\n"
    : "+f"(d[0]), "+f"(d[1]), "+f"(d[2]), "+f"(d[3]), "+f"(d[4]), "+f"(d[5]), "+f"(d[6]), "+f"(d[7]), "+f"(d[8]), "+f"(d[9]), "+f"(d[10]), "+f"(d[11]), "+f"(d[12]), "+f"(d[13]), "+f"(d[14]), "+f"(d[15]), "+f"(d[16]), "+f"(d[17]), "+f"(d[18]), "+f"(d[19]), "+f"(d[20]), "+f"(d[21]), "+f"(d[22]), "+f"(d[23]), "+f"(d[24]), "+f"(d[25]), "+f"(d[26]), "+f"(d[27]), "+f"(d[28]), "+f"(d[29]), "+f"(d[30]), "+f"(d[31]), "+f"(d[32]), "+f"(d[33]), "+f"(d[34]), "+f"(d[35]), "+f"(d[36]), "+f"(d[37]), "+f"(d[38]), "+f"(d[39]), "+f"(d[40]), "+f"(d[41]), "+f"(d[42]), "+f"(d[43]), "+f"(d[44]), "+f"(d[45]), "+f"(d[46]), "+f"(d[47]), "+f"(d[48]), "+f"(d[49]), "+f"(d[50]), "+f"(d[51]), "+f"(d[52]), "+f"(d[53]), "+f"(d[54]), "+f"(d[55]), "+f"(d[56]), "+f"(d[57]), "+f"(d[58]), "+f"(d[59]), "+f"(d[60]), "+f"(d[61]), "+f"(d[62]), "+f"(d[63]), "+f"(d[64]), "+f"(d[65]), "+f"(d[66]), "+f"(d[67]), "+f"(d[68]), "+f"(d[69]), "+f"(d[70]), "+f"(d[71]), "+f"(d[72]), "+f"(d[73]), "+f"(d[74]), "+f"(d[75]), "+f"(d[76]), "+f"(d[77]), "+f"(d[78]), "+f"(d[79]), "+f"(d[80]), "+f"(d[81]), "+f"(d[82]), "+f"(d[83]), "+f"(d[84]), "+f"(d[85]), "+f"(d[86]), "+f"(d[87]), "+f"(d[88]), "+f"(d[89]), "+f"(d[90]), "+f"(d[91]), "+f"(d[92]), "+f"(d[93]), "+f"(d[94]), "+f"(d[95])
    : "r"(a0), "r"(a1), "r"(0u), "l"(descB));
}

__device__ __forceinline__ void wgmma_n128_ssz_ta0_tb1(float* d, uint64_t descA, uint64_t descB) {
  asm volatile("{\n.reg .pred p;\nsetp.ne.b32 p, 0, 0;\n"
    "wgmma.mma_async.sync.aligned.m64n128k16.f32.bf16.bf16 {%0, %1, %2, %3, %4, %5, %6, %7, %8, %9, %10, %11, %12, %13, %14, %15, %16, %17, %18, %19, %20, %21, %22, %23, %24, %25, %26, %27, %28, %29, %30, %31, %32, %33, %34, %35, %36, %37, %38, %39, %40, %41, %42, %43, %44, %45, %46, %47, %48, %49, %50, %51, %52, %53, %54, %55, %56, %57, %58, %59, %60, %61, %62, %63}, %64, %65, p, 1, 1, 0, 1;\n}\n"
    : "=f"(d[0]), "=f"(d[1]), "=f"(d[2]), "=f"(d[3]), "=f"(d[4]), "=f"(d[5]), "=f"(d[6]), "=f"(d[7]), "=f"(d[8]), "=f"(d[9]), "=f"(d[10]), "=f"(d[11]), "=f"(d[12]), "=f"(d[13]), "=f"(d[14]), "=f"(d[15]), "=f"(d[16]), "=f"(d[17]), "=f"(d[18]), "=f"(d[19]), "=f"(d[20]), "=f"(d[21]), "=f"(d[22]), "=f"(d[23]), "=f"(d[24]), "=f"(d[25]), "=f"(d[26]), "=f"(d[27]), "=f"(d[28]), "=f"(d[29]), "=f"(d[30]), "=f"(d[31]), "=f"(d[32]), "=f"(d[33]), "=f"(d[34]), "=f"(d[35]), "=f"(d[36]), "=f"(d[37]), "=f"(d[38]), "=f"(d[39]), "=f"(d[40]), "=f"(d[41]), "=f"(d[42]), "=f"(d[43]), "=f"(d[44]), "=f"(d[45]), "=f"(d[46]), "=f"(d[47]), "=f"(d[48]), "=f"(d[49]), "=f"(d[50]), "=f"(d[51]), "=f"(d[52]), "=f"(d[53]), "=f"(d[54]), "=f"(d[55]), "=f"(d[56]), "=f"(d[57]), "=f"(d[58]), "=f"(d[59]), "=f"(d[60]), "=f"(d[61]), "=f"(d[62]), "=f"(d[63])
    : "l"(descA), "l"(descB));
}

__device__ __forceinline__ void wgmma_n64_ss_ta0_tb0(float* d, uint64_t descA, uint64_t descB, int scaleD) {
  asm volatile("{\n.reg .pred p;\nsetp.ne.b32 p, %34, 0;\n"
    "wgmma.mma_async.sync.aligned.m64n64k16.f32.bf16.bf16 {%0, %1, %2, %3, %4, %5, %6, %7, %8, %9, %10, %11, %12, %13, %14, %15, %16, %17, %18, %19, %20, %21, %22, %23, %24, %25, %26, %27, %28, %29, %30, %31}, %32, %33, p, 1, 1, 0, 0;\n}\n"
    : "+f"(d[0]), "+f"(d[1]), "+f"(d[2]), "+f"(d[3]), "+f"(d[4]), "+f"(d[5]), "+f"(d[6]), "+f"(d[7]), "+f"(d[8]), "+f"(d[9]), "+f"(d[10]), "+f"(d[11]), "+f"(d[12]), "+f"(d[13]), "+f"(d[14]), "+f"(d[15]), "+f"(d[16]), "+f"(d[17]), "+f"(d[18]), "+f"(d[19]), "+f"(d[20]), "+f"(d[21]), "+f"(d[22]), "+f"(d[23]), "+f"(d[24]), "+f"(d[25]), "+f"(d[26]), "+f"(d[27]), "+f"(d[28]), "+f"(d[29]), "+f"(d[30]), "+f"(d[31])
    : "l"(descA), "l"(descB), "r"(scaleD));
}

__device__ __forceinline__ void wgmma_n64_ssz_ta0_tb0(float* d, uint64_t descA, uint64_t descB) {
  asm volatile("{\n.reg .pred p;\nsetp.ne.b32 p, 0, 0;\n"
    "wgmma.mma_async.sync.aligned.m64n64k16.f32.bf16.bf16 {%0, %1, %2, %3, %4, %5, %6, %7, %8, %9, %10, %11, %12, %13, %14, %15, %16, %17, %18, %19, %20, %21, %22, %23, %24, %25, %26, %27, %28, %29, %30, %31}, %32, %33, p, 1, 1, 0, 0;\n}\n"
    : "=f"(d[0]), "=f"(d[1]), "=f"(d[2]), "=f"(d[3]), "=f"(d[4]), "=f"(d[5]), "=f"(d[6]), "=f"(d[7]), "=f"(d[8]), "=f"(d[9]), "=f"(d[10]), "=f"(d[11]), "=f"(d[12]), "=f"(d[13]), "=f"(d[14]), "=f"(d[15]), "=f"(d[16]), "=f"(d[17]), "=f"(d[18]), "=f"(d[19]), "=f"(d[20]), "=f"(d[21]), "=f"(d[22]), "=f"(d[23]), "=f"(d[24]), "=f"(d[25]), "=f"(d[26]), "=f"(d[27]), "=f"(d[28]), "=f"(d[29]), "=f"(d[30]), "=f"(d[31])
    : "l"(descA), "l"(descB));
}

__device__ __forceinline__ void wgmma_n80_ss_ta0_tb0(float* d, uint64_t descA, uint64_t descB, int scaleD) {
  asm volatile("{\n.reg .pred p;\nsetp.ne.b32 p, %42, 0;\n"
    "wgmma.mma_async.sync.aligned.m64n80k16.f32.bf16.bf16 {%0, %1, %2, %3, %4, %5, %6, %7, %8, %9, %10, %11, %12, %13, %14, %15, %16, %17, %18, %19, %20, %21, %22, %23, %24, %25, %26, %27, %28, %29, %30, %31, %32, %33, %34, %35, %36, %37, %38, %39}, %40, %41, p, 1, 1, 0, 0;\n}\n"
    : "+f"(d[0]), "+f"(d[1]), "+f"(d[2]), "+f"(d[3]), "+f"(d[4]), "+f"(d[5]), "+f"(d[6]), "+f"(d[7]), "+f"(d[8]), "+f"(d[9]), "+f"(d[10]), "+f"(d[11]), "+f"(d[12]), "+f"(d[13]), "+f"(d[14]), "+f"(d[15]), "+f"(d[16]), "+f"(d[17]), "+f"(d[18]), "+f"(d[19]), "+f"(d[20]), "+f"(d[21]), "+f"(d[22]), "+f"(d[23]), "+f"(d[24]), "+f"(d[25]), "+f"(d[26]), "+f"(d[27]), "+f"(d[28]), "+f"(d[29]), "+f"(d[30]), "+f"(d[31]), "+f"(d[32]), "+f"(d[33]), "+f"(d[34]), "+f"(d[35]), "+f"(d[36]), "+f"(d[37]), "+f"(d[38]), "+f"(d[39])
    : "l"(descA), "l"(descB), "r"(scaleD));
}

__device__ __forceinline__ void wgmma_n32_rs_tb1(float* d, const uint32_t* a, uint64_t descB, int scaleD) {
  asm volatile("{\n.reg .pred p;\nsetp.ne.b32 p, %21, 0;\n"
    "wgmma.mma_async.sync.aligned.m64n32k16.f32.bf16.bf16 {%0, %1, %2, %3, %4, %5, %6, %7, %8, %9, %10, %11, %12, %13, %14, %15}, {%16, %17, %18, %19}, %20, p, 1, 1, 1;\n}\n"
    : "+f"(d[0]), "+f"(d[1]), "+f"(d[2]), "+f"(d[3]), "+f"(d[4]), "+f"(d[5]), "+f"(d[6]), "+f"(d[7]), "+f"(d[8]), "+f"(d[9]), "+f"(d[10]), "+f"(d[11]), "+f"(d[12]), "+f"(d[13]), "+f"(d[14]), "+f"(d[15])
    : "r"(a[0]), "r"(a[1]), "r"(a[2]), "r"(a[3]), "l"(descB), "r"(scaleD));
}

__device__ __forceinline__ uint32_t pack_bf16x2(float lo, float hi) {
  uint32_t r;
  asm("cvt.rn.bf16x2.f32 %0, %1, %2;" : "=r"(r) : "f"(hi), "f"(lo));
  return r;
}
__device__ __forceinline__ float bf_lo(uint32_t p) { return __uint_as_float(p << 16); }
__device__ __forceinline__ float bf_hi(uint32_t p) { return __uint_as_float(p & 0xffff0000u); }
__device__ __forceinline__ float bf16_round(float v) { return __bfloat162float(__float2bfloat16_rn(v)); }
__device__ __forceinline__ float ex2_approx(float x) {
  float r;
  asm("ex2.approx.ftz.f32 %0, %1;" : "=f"(r) : "f"(x));
  return r;
}
__device__ __forceinline__ float rcp_fast(float x) {
  float r;
  asm("rcp.approx.ftz.f32 %0, %1;" : "=f"(r) : "f"(x));
  return r;
}
__device__ __forceinline__ void ldmatrix_x4(uint32_t (&r)[4], uint32_t addr) {
  asm volatile("ldmatrix.sync.aligned.m8n8.x4.shared.b16 {%0,%1,%2,%3}, [%4];"
               : "=r"(r[0]), "=r"(r[1]), "=r"(r[2]), "=r"(r[3])
               : "r"(addr)
               : "memory");
}
__device__ __forceinline__ void stmatrix_x4(uint32_t addr, uint32_t r0, uint32_t r1, uint32_t r2, uint32_t r3) {
  asm volatile("stmatrix.sync.aligned.m8n8.x4.shared.b16 [%0], {%1,%2,%3,%4};" ::"r"(addr), "r"(r0), "r"(r1), "r"(r2),
               "r"(r3));
}
__device__ __forceinline__ uint32_t add_bf16x2(uint32_t a, uint32_t b) {
  uint32_t r;
  asm("add.rn.bf16x2 %0, %1, %2;" : "=r"(r) : "r"(a), "r"(b));
  return r;
}
__device__ __forceinline__ uint4 lds128(uint32_t addr) {
  uint4 v;
  asm volatile("ld.shared.v4.b32 {%0,%1,%2,%3}, [%4];" : "=r"(v.x), "=r"(v.y), "=r"(v.z), "=r"(v.w) : "r"(addr) : "memory");
  return v;
}
__device__ __forceinline__ uint32_t lds32(uint32_t addr) {
  uint32_t v;
  asm volatile("ld.shared.b32 %0, [%1];" : "=r"(v) : "r"(addr) : "memory");
  return v;
}
__device__ __forceinline__ void sts32(uint32_t addr, uint32_t v) {
  asm volatile("st.shared.b32 [%0], %1;" ::"r"(addr), "r"(v) : "memory");
}

__device__ __forceinline__ unsigned ld_acquire_u32(const unsigned* p) {
  unsigned v;
  asm volatile("ld.acquire.gpu.global.u32 %0, [%1];" : "=r"(v) : "l"(p) : "memory");
  return v;
}
__device__ __forceinline__ void red_relaxed_add(unsigned* p, unsigned v) {
  asm volatile("red.relaxed.gpu.global.add.u32 [%0], %1;" ::"l"(p), "r"(v) : "memory");
}
__device__ __forceinline__ void wait_ge(const unsigned* p, unsigned target) {
#pragma unroll 1
  for (uint32_t it = 0; it < (1u << 17); ++it) {
    if ((int)(ld_acquire_u32(p) - target) >= 0) return;
  }
}

__device__ __forceinline__ void wait_ge2(const unsigned* p, unsigned t0, unsigned t1) {
#pragma unroll 1
  for (uint32_t it = 0; it < (1u << 17); ++it) {
    unsigned long long v;
    asm volatile("ld.acquire.gpu.global.u64 %0, [%1];" : "=l"(v) : "l"(p) : "memory");
    if ((int)((unsigned)v - t0) >= 0 && (int)((unsigned)(v >> 32) - t1) >= 0) return;
  }
}

template <bool SLOW>
__device__ __forceinline__ void wait_mask(const unsigned* f, int cnt, unsigned target, uint32_t need, uint32_t& seen, int lane) {
  if ((seen & need) == need) return;
  const unsigned* fp = f + (lane & (cnt - 1));
#pragma unroll 1
  for (uint32_t it = 0; it < (1u << 17); ++it) {
    seen = __ballot_sync(0xffffffffu, (int)(ld_acquire_u32(fp) - target) >= 0);
    if ((seen & need) == need) break;
    if (SLOW) __nanosleep(400);
  }
  fence_proxy_async_all();
}
__device__ __forceinline__ float4 ld_rec(const float4* p) {
  float4 v;
  asm volatile("ld.relaxed.gpu.global.v4.f32 {%0,%1,%2,%3}, [%4];" : "=f"(v.x), "=f"(v.y), "=f"(v.z), "=f"(v.w) : "l"(p) : "memory");
  return v;
}
__device__ __forceinline__ void st_rec(float4* p, float a, float b, float c, unsigned tag) {
  asm volatile("st.relaxed.gpu.global.v4.f32 [%0], {%1,%2,%3,%4};" ::"l"(p), "f"(a), "f"(b), "f"(c), "f"(__uint_as_float(tag)) : "memory");
}
template <int N>
__device__ __forceinline__ float4 sum_recs(const float4* p, int stride, unsigned tag) {
  float4 s;
#pragma unroll 1
  for (uint32_t it = 0; it < (1u << 17); ++it) {
    float4 v[N];
#pragma unroll
    for (int t = 0; t < N; t++) v[t] = ld_rec(p + t * stride);
    bool ok = true;
    s = make_float4(0.f, 0.f, 0.f, 0.f);
#pragma unroll
    for (int t = 0; t < N; t++) {
      ok &= __float_as_uint(v[t].w) == tag;
      s.x += v[t].x;
      s.y += v[t].y;
      s.z += v[t].z;
    }
    if (ok) break;
    __nanosleep(200);
  }
  return s;
}

__device__ __forceinline__ int fresh_tid() {
  int t;
  asm volatile("mov.u32 %0, %%tid.x;" : "=r"(t));
  return t;
}
#define PHASE_IDS                                  \
  const int tid_ = fresh_tid();                    \
  const int lane = tid_ & 31, wwarp = __shfl_sync(0xffffffffu, (tid_ >> 5) & 3, 0), tid = tid_ & 127; \
  const int g = lane >> 2, c = lane & 3;           \
  (void)tid; (void)g; (void)c; (void)wwarp;

#define STAMPW(cond, i) do { } while (0)
#define STAMP(cond, i) do { } while (0)
#define STA(i) do { } while (0)
#define GTL(i) do { } while (0)
#define GTLX(c, i) do { } while (0)
#define TGET(v) do { } while (0)
#define TPUT(c, i, v) do { } while (0)

constexpr float SM_C = 0.17677669529663687f * 1.4426950408889634f;

constexpr uint32_t OA_TILE = SBASE + OFF_SLOT + 16384;

__device__ __forceinline__ void sched_fence(uint32_t never) {
  asm volatile("{\n.reg .pred p;\nsetp.ne.u32 p, %0, 0;\n@p exit;\n}\n" ::"r"(never) : "memory");
}

template <int K0, int K1>
__device__ __forceinline__ void attn_exp(float (&s)[32]) {
#pragma unroll
  for (int k = K0; k < K1; k++) s[k] = ex2_approx(s[k]);
}
#define ASPL 16
#define ASPM 6
template <int MODE, bool NEXT>
__device__ __forceinline__ void attn_unit(float (&s)[32], float (&sn)[32], float (&o)[16], float (&l)[2], bool valid,
                                          uint32_t vdesc, uint32_t qdesc, uint32_t kdesc, uint32_t tri, int w,
                                          uint32_t hbar, uint32_t hpar, uint32_t rel, uint32_t zero, bool stampon = false) {
  float x[9][2];
  if (MODE == 0) {
    attn_exp<0, ASPL>(s);
  } else {
#pragma unroll
    for (int e = 0; e < 2; e++) {
#pragma unroll
      for (int j = 0; j < 4; j++) x[j][e] = MODE == 1 ? s[4 * j + 2 + e] : s[16 + 4 * j + e];
      x[4][e] = MODE == 1 ? s[e] : s[30 + e];
      x[5][e] = MODE == 1 ? s[18 + e] : s[12 + e];
#pragma unroll
      for (int u = 1; u < 4; u++)
        x[5 + u][e] = MODE == 1 ? (w >= u ? s[4 * u + e] : s[4 * (8 - u) + 2 + e]) : (w >= u ? s[4 * (7 - u) + 2 + e] : s[4 * (u - 1) + e]);
    }
#pragma unroll
    for (int k = 0; k < 2 * ASPM; k++) x[k >> 1][k & 1] = ex2_approx(x[k >> 1][k & 1]);
  }
  sched_fence(zero);
  if (hbar) mbar_wait(hbar, hpar);
  wgmma_wait<0>();
  if (rel) mbar_arrive(rel);
  if (NEXT) {
    wgmma_fence();
    wgmma_n64_ssz_ta0_tb0(sn, desc_lo(qdesc), desc_lo(kdesc));
    wgmma_n64_ss_ta0_tb0(sn, desc_lo(qdesc + 2), desc_lo(kdesc + 2), 1);
    wgmma_commit();
    sched_fence(zero);
  }
  uint32_t p[16];
  if (MODE == 0) {
    attn_exp<ASPL, 32>(s);
#pragma unroll
    for (int k = 0; k < 16; k++) p[k] = pack_bf16x2(s[2 * k], s[2 * k + 1]);
  } else {
#pragma unroll
    for (int k = 2 * ASPM; k < 18; k++) x[k >> 1][k & 1] = ex2_approx(x[k >> 1][k & 1]);
    const uint32_t tm = MODE == 1 ? tri : ~tri;
#pragma unroll
    for (int j = 0; j < 4; j++) {
      p[MODE == 1 ? 2 * j + 1 : 8 + 2 * j] = pack_bf16x2(x[j][0], x[j][1]);
      p[MODE == 1 ? 8 + 2 * j : 2 * j + 1] = 0u;
    }
    p[MODE == 1 ? 0 : 15] = pack_bf16x2(x[4][0], x[4][1]) & (w == 0 ? tm : 0xffffffffu);
    p[MODE == 1 ? 9 : 6] = pack_bf16x2(x[5][0], x[5][1]) & (w == 3 ? tm : 0xffffffffu);
#pragma unroll
    for (int u = 1; u < 4; u++) {
      const uint32_t q = pack_bf16x2(x[5 + u][0], x[5 + u][1]);
      p[MODE == 1 ? 2 * u : 2 * (7 - u) + 1] = q & (w > u ? 0xffffffffu : (w == u ? tm : 0u));
      p[MODE == 1 ? 2 * (8 - u) + 1 : 2 * (u - 1)] = q & (w < u - 1 ? 0xffffffffu : (w == u - 1 ? tm : 0u));
    }
  }
  wgmma_fence();
#pragma unroll
  for (int k = 0; k < 4; k++) wgmma_n32_rs_tb1(o, p + 4 * k, desc_lo(vdesc + k * 128), 1);
  wgmma_commit();
#pragma unroll
  for (int r = 0; r < 2; r++) {
    float t = 0.f;
#pragma unroll
    for (int hf = 0; hf < 2; hf++) {
      if (MODE != 0 && r == MODE - 1 && hf == 2 - MODE) continue;
      const uint32_t* q = p + 8 * hf + r;
      const uint32_t v = add_bf16x2(add_bf16x2(q[0], q[2]), add_bf16x2(q[4], q[6]));
      t = (MODE != 0 && r == MODE - 1) || hf == 0 ? bf_lo(v) + bf_hi(v) : t + (bf_lo(v) + bf_hi(v));
    }
    if (valid) l[r] += t;
  }
  if (NEXT) {
    wgmma_wait<1>();
    reg_fence<32>(sn);
  }
}

__device__ __forceinline__ void attn_a_slow(const uint8_t* __restrict__ kvimg, int L, int gb, int hp,
                                         int hh, int wwarp, int lane) {
  constexpr uint32_t sq = SBASE + OFF_SLOT + 3 * 16384;
  const unsigned ep = (*(volatile unsigned*)(g_flags + F_DONE)) / NCTA;
  wait_ge2(g_flags + F_KV + (gb * 16 + hp) * KSTR, 4u * ep + L + 1u, 2u * ep + (L >> 1) + 1u);
#pragma unroll 1
  for (int t = 0; t < 32; t++) {
    const int row = (t >> 4) * 64 + ((t & 8) ? 7 - wwarp : wwarp) * 8 + (t & 7);
    const int qpos = gb * 128 + row;
    const uint32_t qaddr = sq + ((t >> 4) * 64 + wwarp * 16 + (t & 15)) * 128;
    float mx = -INFINITY, sum = 0.f, acc = 0.f;
#pragma unroll 1
    for (int pass = 0; pass < 2; pass++) {
#pragma unroll 1
      for (int j = 0; j < 8; j++) {
        const int kp = qpos - (lane + 32 * j);
        const uint8_t* kr = kvimg + ((size_t)((kp >> 7) * 16 + hp) * 2 + ((kp >> 6) & 1)) * 16384 + (kp & 63) * 128;
        float d = -INFINITY;
        if (kp >= 0) {
          d = 0.f;
#pragma unroll 1
          for (int q = 0; q < 4; q++) {
            const uint4 kv = __ldcg(reinterpret_cast<const uint4*>(kr + (((hh * 4 + q) ^ (kp & 7)) << 4)));
            const uint4 qv = lds128(qaddr + (((hh * 4 + q) ^ (row & 7)) << 4));
            const uint32_t kw[4] = {kv.x, kv.y, kv.z, kv.w}, qw[4] = {qv.x, qv.y, qv.z, qv.w};
#pragma unroll
            for (int e = 0; e < 4; e++) d = fmaf(bf_lo(kw[e]), bf_lo(qw[e]), fmaf(bf_hi(kw[e]), bf_hi(qw[e]), d));
          }
        }
        if (pass == 0) {
          mx = fmaxf(mx, d);
        } else {
          const float ev = ex2_approx(d - mx);
          sum += ev;
          const float pv = bf16_round(ev);
#pragma unroll 1
          for (int kk = 0; kk < 32; kk++) {
            const float pk = __shfl_sync(0xffffffffu, pv, kk);
            const int k2 = qpos - (kk + 32 * j);
            if (k2 >= 0) {
              const uint8_t* vr = kvimg + ((size_t)((k2 >> 7) * 16 + hp) * 2 + ((k2 >> 6) & 1)) * 16384 + 8192 + (k2 & 63) * 128;
              const unsigned short vv =
                  __ldcg(reinterpret_cast<const unsigned short*>(vr + (((hh * 4 + (lane >> 3)) ^ (k2 & 7)) << 4) + (lane & 7) * 2));
              acc = fmaf(pk, __uint_as_float((uint32_t)vv << 16), acc);
            }
          }
        }
      }
      if (pass == 0) {
#pragma unroll
        for (int o = 16; o > 0; o >>= 1) mx = fmaxf(mx, __shfl_xor_sync(0xffffffffu, mx, o));
      }
    }
#pragma unroll
    for (int o = 16; o > 0; o >>= 1) sum += __shfl_xor_sync(0xffffffffu, sum, o);
    acc *= rcp_fast(sum);
    const float hi = __shfl_down_sync(0xffffffffu, acc, 1);
    __syncwarp();
    if ((lane & 1) == 0)
      sts32(OA_TILE + row * 128 + (((hh * 4 + (lane >> 3)) ^ (row & 7)) << 4) + (lane & 7) * 2, pack_bf16x2(acc, hi));
    __syncwarp();
  }
}

__device__ __forceinline__ void store_o(const float (&o)[16], const float (&inv)[2], uint32_t rowaddr, int hh, int lane) {
  const int mat = lane >> 3, r7 = lane & 7;
#pragma unroll
  for (int jp = 0; jp < 2; jp++)
    stmatrix_x4(rowaddr + (((hh * 4 + 2 * jp + (mat >> 1)) ^ r7) << 4),
                pack_bf16x2(o[8 * jp] * inv[0], o[8 * jp + 1] * inv[0]),
                pack_bf16x2(o[8 * jp + 2] * inv[1], o[8 * jp + 3] * inv[1]),
                pack_bf16x2(o[8 * jp + 4] * inv[0], o[8 * jp + 5] * inv[0]),
                pack_bf16x2(o[8 * jp + 6] * inv[1], o[8 * jp + 7] * inv[1]));
}

__device__ __forceinline__ void attention_a(int HH, int L, int gb, int hp, uint32_t par0, uint32_t parA, int wwarp, int lane,
                                            uint32_t zero) {
  constexpr uint32_t bars = SBASE + OFF_BAR;
  const uint32_t dslot = ((SBASE + OFF_SLOT) >> 4) + 0x10000u + HH * 4;
  const uint32_t dq = dslot + 3 * 1024;
  float sa[32], sb[32], o[2][16], l[2][2];
  auto dch = [&](int n) { return dslot + 1024u * (n % 3 == 0 ? 1 : (n % 3 == 1 ? 0 : 2)); };
  wgmma_fence();
  wgmma_n64_ssz_ta0_tb0(sa, desc_lo(dq + 512), desc_lo(dch(0)));
  wgmma_n64_ss_ta0_tb0(sa, desc_lo(dq + 512 + 2), desc_lo(dch(0) + 2), 1);
  wgmma_commit();
#pragma unroll
  for (int h = 0; h < 2; h++) {
#pragma unroll
    for (int i = 0; i < 16; i++) o[h][i] = 0.f;
    l[h][0] = l[h][1] = 0.f;
  }
  const int dg = (lane >> 2) - 2 * (lane & 3);
  const uint32_t tri = (dg >= 0 ? 0xffffu : 0u) | (dg >= 1 ? 0xffff0000u : 0u);
  const int nmax = 2 * gb + 1;
  wgmma_wait<0>();
  reg_fence<32>(sa);
#define STON false
#define ATT_STEP(i, MODE)                                                                                            \
  attn_unit<MODE, true>(sa, sb, o[1], l[1], i <= nmax, dch(i) + 512, dq, dch(i + 1), tri, wwarp,                     \
                        i >= 1 ? bars + 8u * (B_HALO + i - 1) : 0u, i == 1 ? par0 : parA, 0u, zero, STON);                \
  attn_unit<MODE, (i < 4)>(sb, sa, o[0], l[0], i + 1 <= nmax, dch(i + 1) + 512, dq + 512, dch(i + 1), tri, wwarp, 0u, \
                           0u, i < 3 && lane == 0 ? bars + 8u * (B_REL + i) : 0u, zero);
  ATT_STEP(0, 1)
  ATT_STEP(1, 0)
  ATT_STEP(2, 0)
  ATT_STEP(3, 0)
  ATT_STEP(4, 2)
#undef ATT_STEP
  const uint32_t ra = OA_TILE + (((lane & 8) ? 7 - wwarp : wwarp) * 8 + (lane & 7)) * 128;
  bool bad = false;
#pragma unroll
  for (int h = 1; h >= 0; h--) {
    float inv[2];
#pragma unroll
    for (int r = 0; r < 2; r++) {
      float v = l[h][r];
      v += __shfl_xor_sync(0xffffffffu, v, 1);
      v += __shfl_xor_sync(0xffffffffu, v, 2);
      bad |= !(v <= 1.152921504606846976e18f && v >= 8.673617379884035e-19f);
      inv[r] = rcp_fast(v);
    }
    if (h == 0) wgmma_wait<0>();
    reg_fence<16>(o[h]);
    store_o(o[h], inv, ra + h * 8192, HH, lane);
  }
  if (HH == 0) GTL(45);
  if (__any_sync(0xffffffffu, bad)) attn_a_slow(g_kvA[L >> 1][0][0][0], L, gb, hp, HH, wwarp, lane);
}

constexpr uint32_t KB_ROW0 = SBASE + OFF_SLOT + 2048, VB_ROW0 = SBASE + OFF_SLOT + 24576 + 2048;

__device__ __forceinline__ void attnB_soft(const float (&s)[40], int wwarp, int D, bool edge, bool odd,
                                           uint32_t (&p)[5][4], float (&sum)[2]) {
  float z[2][3];
#define GATHER_(W)                                                                                  \
  _Pragma("unroll") for (int r = 0; r < 2; r++) _Pragma("unroll") for (int t = 0; t < 3; t++)       \
      z[r][t] = odd ? s[4 * (2 * W + r + t) + 2 * r + 1] : s[4 * (2 * W + r + t) + 2 * r];
  if (wwarp < 2) {
    if (wwarp == 0) { GATHER_(0) } else { GATHER_(1) }
  } else {
    if (wwarp == 2) { GATHER_(2) } else { GATHER_(3) }
  }
#undef GATHER_
  float y[2];
  y[0] = D >= 2 ? z[0][0] : z[0][2];
  y[1] = D >= 2 ? z[1][0] : z[1][2];
  if (edge) {
    z[0][1] = -INFINITY;
    if (D >= 2) y[0] = y[1] = -INFINITY;
  }
  float m0 = fmaxf(z[0][1], y[0]), m1 = fmaxf(z[1][1], y[1]);
  m0 = fmaxf(m0, __shfl_xor_sync(0xffffffffu, m0, 1));
  m1 = fmaxf(m1, __shfl_xor_sync(0xffffffffu, m1, 1));
  m0 = fmaxf(m0, __shfl_xor_sync(0xffffffffu, m0, 2));
  m1 = fmaxf(m1, __shfl_xor_sync(0xffffffffu, m1, 2));
  const float e00 = ex2_approx(z[0][1] - m0), e01 = ex2_approx(y[0] - m0);
  const float e10 = ex2_approx(z[1][1] - m1), e11 = ex2_approx(y[1] - m1);
  sum[0] = e00 + e01;
  sum[1] = e10 + e11;
  const int sh = odd ? 16 : 0;
  const uint32_t a0 = pack_bf16x2(e00, 0.f) << sh, a1 = pack_bf16x2(e10, 0.f) << sh;
  const uint32_t b0 = pack_bf16x2(e01, 0.f) << sh, b1 = pack_bf16x2(e11, 0.f) << sh;
  const int kb = wwarp + (D >= 2 ? 0 : 1);
#pragma unroll
  for (int k = 0; k < 5; k++) {
    p[k][0] = k == kb ? b0 : 0u;
    p[k][1] = k == wwarp + 1 ? a1 : 0u;
    p[k][2] = k == wwarp ? a0 : 0u;
    p[k][3] = k == kb ? b1 : 0u;
#pragma unroll
    for (int q = 0; q < 4; q++) asm volatile("" : "+r"(p[k][q]));
  }
}

__device__ __forceinline__ void attnB_s(float (&s)[40], int HH, int h) {
  constexpr uint32_t sq = SBASE + OFF_SLOT + 3 * 16384;
#pragma unroll
  for (int ks = 0; ks < 2; ks++)
    wgmma_n80_ss_ta0_tb0(s, make_desc(sq + h * 8192 + HH * 64 + ks * 32, 16),
                         make_desc(KB_ROW0 + h * 8192 - 2048 + HH * 64 + ks * 32, 16), ks);
}
__device__ __forceinline__ void attnB_pv(float (&o)[16], const uint32_t (&p)[5][4], int HH, int h) {
#pragma unroll
  for (int k = 0; k < 5; k++)
    wgmma_n32_rs_tb1(o, p[k], make_desc(VB_ROW0 + h * 8192 - 2048 + k * 2048 + HH * 64, 16), k);
}

__device__ __forceinline__ void attention_b(int HH, int gb, uint32_t par0, int wwarp, int lane) {
  constexpr uint32_t bars = SBASE + OFF_BAR, sq = SBASE + OFF_SLOT + 3 * 16384;
  float s[40];
  reg_define<40>(s);
  wgmma_fence();
  attnB_s(s, HH, 1);
  wgmma_commit();
  const int g = lane >> 2;
  const bool odd = g & 1;
  const int D = 2 * (lane & 3) + (g & 1) - g;
  const uint32_t ra = sq + (wwarp * 16 + ((lane >> 3) & 1) * 8 + (lane & 7)) * 128;
  wgmma_wait<0>();
  reg_fence<40>(s);
#pragma unroll 1
  for (int h = 1; h >= 0; h--) {
    float o[16], inv[2];
    uint32_t p[5][4];
    reg_define<16>(o);
    attnB_soft(s, wwarp, D, h == 0 && gb == 0 && wwarp == 0, odd, p, inv);
    if (h == 1) {
      mbar_wait(bars + 8u * B_HALO, par0);
      wgmma_fence();
      attnB_s(s, HH, 0);
    }
    wgmma_fence();
    attnB_pv(o, p, HH, h);
    wgmma_commit();
#pragma unroll
    for (int r = 0; r < 2; r++) {
      inv[r] += __shfl_xor_sync(0xffffffffu, inv[r], 1);
      inv[r] += __shfl_xor_sync(0xffffffffu, inv[r], 2);
      inv[r] = rcp_fast(inv[r]);
    }
    wgmma_wait<0>();
    reg_fence<40>(s);
    reg_fence<16>(o);
    store_o(o, inv, ra + h * 8192, HH, lane);
  }
}

#define KTQM 0
#define TRICKLE 300
#define PCA 1
#define PCB 3
#define PXB 4
#define EPT -1
#define EPW1 4
#define EPW0 12
#define HPOLL 3
#define QTURN 2
struct Params {
  CUtensorMap xq[2], xr[3], o, wqkv[2], wo[2];
  const __nv_bfloat16* in_x;
  const __nv_bfloat16* wqkv_p[2];
  const __nv_bfloat16* wo_p[2];
  __nv_bfloat16* out;
  uint32_t zero;
};

__device__ __forceinline__ void colsum_part(const CUtensorMap* wmap, int ty, int qr, int hp) {
  constexpr uint32_t bars = SBASE + OFF_BAR, slots = SBASE + OFF_SLOT;
  PHASE_IDS
  const unsigned ep1 = (*(volatile unsigned*)(g_flags + F_DONE)) / NCTA + 1u;
  if (wwarp == 0 && elect_one()) {
    mbar_expect_tx(bars + 8u * B_CS, 6 * UNIT);
#pragma unroll 1
    for (int j = 0; j < 2; j++) {
      if (ty == 0) mbar_pace(bars + 8u * (B_EMPTY + PCA + PCB * j), 0);
      else __nanosleep(1000);
      tma_load_3d(slots + j * 3 * UNIT, wmap, bars + 8u * B_CS, hp * 64, qr * 128 + j * 64, 0);
    }
  }
  mbar_wait(bars + 8u * B_CS, ty);
  STAMP(KSQ == 0 && ty == 0, 49);
  const uint32_t src = slots + (tid >> 3) * 128 + (((tid & 7) ^ ((tid >> 3) & 7)) << 4);
#pragma unroll 1
  for (int p = 0; p < 3; p++) {
    float s[8];
#pragma unroll
    for (int e = 0; e < 8; e++) s[e] = 0.f;
#pragma unroll
    for (int j = 0; j < 8; j++) {
      const uint4 v = lds128(src + p * UNIT + (j >> 2) * 3 * UNIT + (j & 3) * 2048);
      const uint32_t x[4] = {v.x, v.y, v.z, v.w};
#pragma unroll
      for (int e = 0; e < 4; e++) {
        s[2 * e] += bf_lo(x[e]);
        s[2 * e + 1] += bf_hi(x[e]);
      }
    }
#pragma unroll
    for (int st = 0; st < 2; st++) {
      const bool up = (lane >> (st + 3)) & 1;
#pragma unroll
      for (int e = 0; e < (4 >> st); e++) {
        const float keep = up ? s[e + (4 >> st)] : s[e], give = up ? s[e] : s[e + (4 >> st)];
        s[e] = keep + __shfl_xor_sync(0xffffffffu, give, 8 << st);
      }
    }
    const uint32_t dst = slots + 6 * UNIT + ((wwarp * 3 + p) * 64 + (lane & 7) * 8 + ((lane >> 3) & 1) * 4 + (lane >> 4) * 2) * 4;
    sts32(dst, __float_as_uint(s[0]));
    sts32(dst + 4, __float_as_uint(s[1]));
  }
  named_bar_sync(6, 128);
  if (tid < 64) {
    float r[3] = {0.f, 0.f, 0.f};
#pragma unroll
    for (int e = 0; e < 12; e++) r[e % 3] += __uint_as_float(lds32(slots + 6 * UNIT + (e * 64 + tid) * 4));
    st_rec(&g_cs[ty][hp][qr][tid], r[0], r[1], r[2], ep1);
    STAMP(KSQ == 0 && ty == 0, 50);
  }
  named_bar_sync(6, 128);
}

__device__ __forceinline__ void cs_put(int blk, int ty, int col, float v) {
  const uint32_t hi = pack_bf16x2(v, 0.f), lo = pack_bf16x2(v - bf_lo(hi), 0.f);
  const uint32_t a = SBASE + OFF_CS + blk * 512 + ty * 256 + col * 2;
  asm volatile("st.shared.b16 [%0], %1;" ::"r"(a ^ (((a >> 7) & 7) << 4)), "h"((unsigned short)hi) : "memory");
  asm volatile("st.shared.b16 [%0], %1;" ::"r"((a + 128) ^ ((((a >> 7) + 1) & 7) << 4)), "h"((unsigned short)lo) : "memory");
}

__device__ __forceinline__ uint32_t ln_params(float s1, float s2) {
  const float mean = s1 * (1.0f / DM);
  const float var = fmaxf(fmaf(-mean, mean, s2 * (1.0f / DM)), 0.f);
  float sd;
  asm("sqrt.approx.f32 %0, %1;" : "=f"(sd) : "f"(bf16_round(bf16_round(var) + 1e-5f)));
  return pack_bf16x2(mean, sd);
}

__host__ __device__ constexpr int w_ua(int kt) { return (kt == 6 ? 20 : 3 * kt) % 20; }
__host__ __device__ constexpr int w_ub(int kt) { return (kt == 6 ? 18 : 3 * kt + 1) % 20; }

constexpr int NSEG = 20;
__host__ __device__ constexpr int SEGQ(int ch, int L, int k0, int k1) { return ch | (L << 2) | ((k0 / 4) << 4) | ((k1 / 4 - 1) << 6); }
__host__ __device__ constexpr int SEGW(int ch, int L) { return ch | 2 | (L << 2); }
__host__ __device__ constexpr unsigned long long pack8(int a, int b, int c, int d, int e, int f, int g, int h) {
  return (unsigned long long)a | ((unsigned long long)b << 8) | ((unsigned long long)c << 16) | ((unsigned long long)d << 24) |
         ((unsigned long long)e << 32) | ((unsigned long long)f << 40) | ((unsigned long long)g << 48) | ((unsigned long long)h << 56);
}
#define SP2 12
#define SP3 12
#define SP4 12
#define SP6 12
__device__ __forceinline__ int seg_code(int sg) {
  constexpr unsigned long long T0 = pack8(SEGQ(0, 0, 0, 16), SEGQ(1, 0, 0, 16), SEGW(0, 0), SEGQ(0, 1, 0, SP2), SEGW(1, 0),
                                          SEGQ(0, 1, SP2, 16), SEGQ(1, 1, 0, SP3), SEGW(0, 1));
  constexpr unsigned long long T1 = pack8(SEGQ(1, 1, SP3, 16), SEGQ(0, 2, 0, SP4), SEGW(1, 1), SEGQ(0, 2, SP4, 16),
                                          SEGQ(1, 2, 0, 16), SEGW(0, 2), SEGQ(0, 3, 0, SP6), SEGW(1, 2));
  constexpr unsigned long long T2 = pack8(SEGQ(0, 3, SP6, 16), SEGQ(1, 3, 0, 16), SEGW(0, 3), SEGW(1, 3), 0, 0, 0, 0);
  return (int)(((sg < 8 ? T0 : (sg < 16 ? T1 : T2)) >> (8 * (sg & 7))) & 255ull);
}
__device__ __forceinline__ int q_first(int inst) { return (int)((pack8(0, 16, 48, 80, 112, 144, 176, 208) >> (8 * inst)) & 255ull); }
__device__ __forceinline__ int w_first(int inst) {
  return (int)((pack8(32, 48 + SP2, 80 + SP3, 112 + SP4, 160, 176 + SP6, 224, 240) >> (8 * inst)) & 255ull);
}
#define PREMASK 0x2Cu
#define PRE0 3
#define PRESH 2
__host__ __device__ constexpr int pre_idx(int kt) {
  const int d = kt - PRE0;
  return (d >= 0 && (d & ((1 << PRESH) - 1)) == 0 && (d >> PRESH) < 4) ? d >> PRESH : -1;
}
__device__ __forceinline__ bool w_pre(int inst) { return (PREMASK >> inst) & 1u; }
__device__ __forceinline__ int q_split(int inst) { return (int)(((0x40400044u | ((SP2 / 4) << 8) | ((SP3 / 4) << 12) | ((SP4 / 4) << 16) | ((SP6 / 4) << 24)) >> (4 * inst)) & 15u); }

__global__ void __launch_bounds__(512, 1) fused_kernel(const __grid_constant__ Params P) {
  extern __shared__ __align__(1024) uint8_t smem_raw[];
  constexpr uint32_t base = SBASE, bars = base + OFF_BAR, slots = base + OFF_SLOT;
  if (smem_u32(smem_raw) != base) __trap();
  const int warp = __shfl_sync(0xffffffffu, threadIdx.x >> 5, 0), lane = threadIdx.x & 31;
  const int b = blockIdx.x;
#define QS 0
#define WS 1
  const int qr = ((b & ((8 << QS) - 1)) >> QS) ^ (((b >> (3 + QS)) & 1) * 7);
  const int hp = ((b >> (3 + QS)) << QS) + (b & ((1 << QS) - 1));
  const int rt = ((b & ((16 << WS) - 1)) >> WS) ^ (((b >> (4 + WS)) & 1) * 15);
  const int ct = ((b >> (4 + WS)) << WS) + (b & ((1 << WS) - 1));

  if (warp == 12) {
    if (elect_one()) {
#pragma unroll
      for (int s = 0; s < 8; s++) {
        mbar_init(bars + 8u * (B_FULL + s), 2);
        mbar_init(bars + 8u * (B_EMPTY + s), 4);
      }
      mbar_init(bars + 8u * B_GO, 1);
      fence_barrier_init();
    }
    __syncwarp();
    named_bar_arrive(0, 512);
  }
  if (threadIdx.x == 0) {
    mbar_init(bars + 8u * B_PREP, 1);
    mbar_init(bars + 8u * (B_PREP + 1), 1);
    for (int s = 0; s < 4; s++) mbar_init(bars + 8u * (B_HALO + s), 1);
    for (int s = 0; s < 3; s++) mbar_init(bars + 8u * (B_REL + s), 8);
    mbar_init(bars + 8u * B_AFREE, 2);
    mbar_init(bars + 8u * B_TURN, 4);
    mbar_init(bars + 8u * (B_TURN + 1), 4);
    mbar_init(bars + 8u * B_CS, 1);
    mbar_init(bars + 8u * B_PRE, 1);
    mbar_init(bars + 8u * B_RESF, 1);
    mbar_init(bars + 8u * B_RESE, 4);
    mbar_init(bars + 8u * B_CSD, 4);
    mbar_init(bars + 8u * B_XRDY, 1);
    mbar_init(bars + 8u * (B_XRDY + 1), 1);
    fence_barrier_init();
  }
  if (warp != 12) named_bar_sync(0, 512);

  if (warp >= 12) {
    setmaxnreg_dec<32>();
    if (warp <= 13) {
      const bool act = warp == 13;
      uint32_t q = 4, dl = 0;
      bool prevw = false;
      unsigned ep1 = 0;
      if (act) {
        mbar_wait(bars + 8u * B_GO, 0);
        ep1 = __shfl_sync(0xffffffffu, (*(volatile unsigned*)(g_flags + F_DONE)) / NCTA + 1u, 0);
      } else {
#pragma unroll 1
        for (int s = 0; s < 16; s++) {
          const uint32_t fb = bars + 8u * (B_FULL + (s & 7)), sa = base + (s & 3) * 5 * UNIT;
          if (s >= 4) mbar_wait(bars + 8u * (B_EMPTY + ((s - 4) & 7)), ((s - 4) >> 3) & 1);
          if (elect_one()) {
            mbar_expect_tx(fb, 5 * UNIT);
            mbar_arrive(fb);
            tma_load_3d(sa, &P.xq[0], fb, 0, qr * 128, s);
            tma_load_3d(sa + 2 * UNIT, &P.wqkv[0], fb, hp * 64, s * 64, 0);
          }
        }
        if (elect_one()) mbar_arrive(bars + 8u * B_GO);
      }
      auto rbar = [&](int b0, int c) { return bars + 8u * b0 + ((8u * (c & 7)) ^ ((q & 1u) << 5)); };
      auto rpar = [&](int c) { return ((q + (c >> 2)) >> 1) & 1u; };
#pragma unroll 1
      for (int sg = 1; sg < NSEG; sg++) {
        const int code = seg_code(sg);
        const int L = (code >> 2) & 3, ch = code & 1;
        uint32_t seen = act ? 0u : 0xFFFFu;
        if ((code & 2) == 0) {
          const CUtensorMap* map = act ? &P.xq[L == 0 ? 0 : 1] : &P.wqkv[L & 1];
          if (act && (L == 0 || __any_sync(0xffffffffu, mbar_test(bars + 8u * (B_XRDY + ch), (L & 1) ^ 1)))) {
            seen = 0xFFFFu;
            fence_proxy_async_all();
          }
          const int k1 = ((code >> 4) & 12) + 4;
#pragma unroll 1
          for (int k4 = (code >> 2) & 12; k4 < k1; k4 += 4, q++) {
#pragma unroll
            for (int ks = 0; ks < 4; ks++) {
              const int kt = k4 + ks;
              if ((ks & 1) == 0)
                wait_mask<false>(g_flags + F_X + (ch * 8 + qr) * XSTR, 8, 6u * ep1 - 6u + 2u * L, 1u << (kt >> 1), seen, lane);
              if (ks == 0 && prevw) mbar_wait(rbar(B_EMPTY, -5), rpar(-5));
              else mbar_wait(rbar(B_EMPTY, ks - 4), rpar(-4));
              if (ks == 3 && prevw && !act) mbar_wait(bars + 8u * B_RESE, dl == 0 ? 1u : 0u);
              if (elect_one()) {
                mbar_expect_tx(rbar(B_FULL, ks), act ? 2 * UNIT : 3 * UNIT);
                tma_load_3d(base + ks * 5 * UNIT + (act ? 0 : 2 * UNIT) + (ks < 2 ? dl : 0u - dl), map, rbar(B_FULL, ks),
                            act ? 0 : hp * 64, act ? ch * 1024 + qr * 128 : kt * 64, act ? kt : 0);
              }
            }
            prevw = false;
          }
        } else {
          const CUtensorMap* map = act ? &P.o : &P.wo[L & 1];
          const bool pre = !act && w_pre(2 * L + ch);
          const int m0 = ch * 1024 + rt * 64;
#pragma unroll
          for (int kt = 0; kt < 16; kt++) {
            if (kt == 0 || kt == 1 || kt == 4 || kt == 8)
              wait_mask<false>(g_flags + F_O + (ch * 16 + rt) * OSTR, 16, 4u * ep1 - 3u + L,
                               kt == 0 ? 1u : (kt == 1 ? 0xEu : (kt == 4 ? 0xF0u : 0xFF00u)), seen, lane);
            if (kt < 4 && !prevw) mbar_wait(rbar(B_EMPTY, kt - 4 - (kt >> 1)), rpar(-4));
            else mbar_wait(rbar(B_EMPTY, kt - 6), rpar(kt - 6));
            if (kt == 6 && prevw && !act) mbar_wait(bars + 8u * B_RESE, dl == 0 ? 1u : 0u);
            if (elect_one()) {
              if (pre_idx(kt) >= 0 && pre) {
                mbar_arrive(rbar(B_FULL, kt));
              } else {
                mbar_expect_tx(rbar(B_FULL, kt), act ? UNIT : 2 * UNIT);
                const uint32_t da = base + w_ua(kt) * UNIT + (w_ua(kt) < 10 ? dl : 0u - dl);
                const uint32_t db = base + w_ub(kt) * UNIT + (w_ub(kt) < 10 ? dl : 0u - dl);
                tma_load_3d(act ? da : db, map, rbar(B_FULL, kt), 0, act ? m0 : kt * 64, act ? kt : ct * 2);
              }
            }
          }
          if (act && elect_one()) {
            mbar_expect_tx(bars + 8u * B_RESF, 2 * UNIT);
            tma_load_3d(base + 8 * UNIT + dl, &P.xr[L == 0 ? 0 : 1], bars + 8u * B_RESF, 0, m0, ct * 2);
          }
          q += 4;
          dl ^= 10u * UNIT;
          prevw = true;
        }
      }
    } else if (warp == 14) {
      const unsigned ep1 = (*(volatile unsigned*)(g_flags + F_DONE)) / NCTA + 1u;
#pragma unroll 1
      for (int inst = 0; inst < 8; inst++) {
        const int L = inst >> 1, ch = inst & 1, gb = ch * 8 + qr;
        unsigned* kvf = g_flags + F_KV;
        const unsigned kvt = 4u * ep1 - 3u + L, kvt0 = 2u * ep1 - 1u + (L >> 1);
        if (L & 1) {
          named_bar_sync(3, 192);
          named_bar_arrive(7, 160);
        } else {
          named_bar_arrive(3, 192);
          named_bar_sync(7, 160);
        }
        STA(34);
        if (elect_one()) {
          const unsigned* nf = kvf + ((gb - 1) * 16 + hp) * KSTR;
          if ((L & 1) == 0) {
            bulk_store(g_kvA[L >> 1][gb][hp][0], slots, 16384);
            bulk_commit();
            const uint32_t parA = ((L >> 1) * 2 + ch) & 1;
            const uint8_t* s1 = gb >= 1 ? g_kvA[L >> 1][gb - 1][hp][0] : g_zero;
            bool got = gb == 0;
#pragma unroll 1
            for (int it = 0; it < HPOLL && !got; it++) got = (int)(ld_acquire_u32(nf) - kvt) >= 0;
#pragma unroll 1
            for (int ph = 0; ph < 2; ph++) {
              if (got == (ph == 0)) {
                if (!got) wait_ge(nf, kvt);
                fence_proxy_async_all();
                STA(36);
                mbar_expect_tx(bars + 8u * B_HALO, 16384);
                bulk_load(slots + 2 * 16384, gb >= 1 ? s1 + 16384 : s1, 16384, bars + 8u * B_HALO);
              } else {
                bulk_wait0();
                fence_proxy_async_all();
                red_relaxed_add(kvf + (gb * 16 + hp) * KSTR + 1, 1u);
                STA(35);
              }
            }
            if (gb >= 1) {
              wait_ge(nf + 1, kvt0);
              fence_proxy_async_all();
            }
            STA(37);
            mbar_wait_lazy<100>(bars + 8u * B_REL, parA);
            STA(38);
            mbar_expect_tx(bars + 8u * (B_HALO + 1), 16384);
            bulk_load(slots + 16384, s1, 16384, bars + 8u * (B_HALO + 1));
            if (gb >= 2) {
              wait_ge2(kvf + ((gb - 2) * 16 + hp) * KSTR, kvt, kvt0);
              fence_proxy_async_all();
            }
            const uint8_t* s2 = gb >= 2 ? g_kvA[L >> 1][gb - 2][hp][0] : g_zero;
            STA(39);
            mbar_wait_lazy<100>(bars + 8u * (B_REL + 1), parA);
            STA(40);
            mbar_expect_tx(bars + 8u * (B_HALO + 2), 16384);
            bulk_load(slots, gb >= 2 ? s2 + 16384 : s2, 16384, bars + 8u * (B_HALO + 2));
            mbar_wait_lazy<100>(bars + 8u * (B_REL + 2), parA);
            STA(41);
            mbar_expect_tx(bars + 8u * (B_HALO + 3), 16384);
            bulk_load(slots + 2 * 16384, s2, 16384, bars + 8u * (B_HALO + 3));
          } else {
            const uint8_t* s1 = gb >= 1 ? g_kvB[L >> 1][gb - 1][hp] : g_zero;
            if (gb >= 1) {
              wait_ge(nf, kvt);
              fence_proxy_async_all();
            }
            mbar_expect_tx(bars + 8u * B_HALO, 4096);
            bulk_load(KB_ROW0 - 2048, s1, 2048, bars + 8u * B_HALO);
            bulk_load(VB_ROW0 - 2048, s1 + 2048, 2048, bars + 8u * B_HALO);
          }
          if (w_pre(inst)) {
            mbar_wait(bars + 8u * B_AFREE, (inst & 1) ^ 1);
            if (inst == 1) mbar_wait(bars + 8u * B_CSD, 0);
            mbar_expect_tx(bars + 8u * B_PRE, 8 * UNIT);
#pragma unroll 1
            for (int j = 0; j < 4; j++) {
              tma_load_3d(slots + j * 2 * UNIT, &P.wo[L & 1], bars + 8u * B_PRE, 0, (PRE0 + (j << PRESH)) * 64, ct * 2);
              __nanosleep(200);
            }
          }
        }
        __syncwarp();
      }
    } else {
      const unsigned ep1 = (*(volatile unsigned*)(g_flags + F_DONE)) / NCTA + 1u;
      mbar_wait(bars + 8u * B_GO, 0);
#pragma unroll 1
      for (int i = 0; i < 20; i++) {
        const char* src = i < 4 ? reinterpret_cast<const char*>(P.wo_p[0]) + (size_t)b * 16384 + i * 4096
                                : (i < 16 ? reinterpret_cast<const char*>(P.wqkv_p[1]) + (size_t)b * 49152 + (i - 4) * 4096
                                          : reinterpret_cast<const char*>(P.wo_p[1]) + (size_t)b * 16384 + (i - 16) * 4096);
        asm volatile("prefetch.global.L2 [%0];" ::"l"(src + lane * 128));
        __nanosleep(TRICKLE);
      }
#pragma unroll 1
      for (int inst = 2; inst < 8; inst++) {
        const int L = inst >> 1, ch = inst & 1, gb = ch * 8 + qr;
        uint32_t seen = 0;
        wait_mask<true>(g_flags + F_X + gb * XSTR, 8, 6u * ep1 - 6u + 2u * L, 0xFFu, seen, lane);
        if (lane == 0) mbar_arrive(bars + 8u * (B_XRDY + ch));
#pragma unroll 1
        for (int h = 0; h < 4; h++) {
          const float4* sp = &g_stats[L][0][gb * 128 + h * 32 + lane];
          const float4 s0 = sum_recs<4>(sp, S_LEN, ep1), s1 = sum_recs<4>(sp + 4 * S_LEN, S_LEN, ep1);
          sts32(base + OFF_RS + (ch * 128 + h * 32 + lane) * 4, ln_params(s0.x + s1.x, s0.y + s1.y));
        }
        if (inst == 2) {
          mbar_wait(bars + 8u * B_CSD, 0);
#pragma unroll 1
          for (int hf = 0; hf < 2; hf++) {
            const float4* cp = &g_cs[1][hp][0][hf * 32 + lane];
            const float4 s0 = sum_recs<4>(cp, 64, ep1), s1 = sum_recs<4>(cp + 4 * 64, 64, ep1);
            cs_put(0, 1, hf * 32 + lane, s0.x + s1.x);
            cs_put(1, 1, hf * 32 + lane, s0.y + s1.y);
            cs_put(2, 1, hf * 32 + lane, s0.z + s1.z);
          }
          fence_proxy_async_smem();
        }
        __syncwarp();
        if (lane == 0) mbar_arrive(bars + 8u * (B_PREP + ch));
      }
    }
  } else {
    const bool asst = warp >= 8;
    const bool lane0 = lane == 0;
    uint32_t tpar = 0;
    GTL(0);
    if (asst) {
      colsum_part(&P.wqkv[0], 0, qr, hp);
      if ((threadIdx.x & 127) < 2) mbar_arrive(bars + 8u * B_AFREE);
    } else if (warp >= 4) {
      PHASE_IDS
      {
        const unsigned ep1 = (*(volatile unsigned*)(g_flags + F_DONE)) / NCTA + 1u;
        const int row = b * 16 + (tid >> 3);
        const uint4* src = reinterpret_cast<const uint4*>(P.in_x + (size_t)row * DM) + (tid & 7);
        float s1 = 0.f, s2 = 0.f;
#pragma unroll 1
        for (int k = 0; k < 4; k++) {
          mbar_pace(bars + 8u * (B_EMPTY + PXB * k / 2), 0);
          uint4 v[4];
#pragma unroll
          for (int j = 0; j < 4; j++) v[j] = __ldg(src + (k * 4 + j) * 8);
#pragma unroll
          for (int j = 0; j < 4; j++) {
            const uint32_t w[4] = {v[j].x, v[j].y, v[j].z, v[j].w};
#pragma unroll
            for (int e = 0; e < 4; e++) {
              const float x0 = bf_lo(w[e]), x1 = bf_hi(w[e]);
              s1 += x0 + x1;
              s2 = fmaf(x0, x0, fmaf(x1, x1, s2));
            }
          }
        }
#pragma unroll
        for (int o = 1; o < 8; o <<= 1) {
          s1 += __shfl_xor_sync(0xffffffffu, s1, o);
          s2 += __shfl_xor_sync(0xffffffffu, s2, o);
        }
        if ((tid & 7) == 0) st_rec(&g_stats[0][0][row], s1, s2, 0.f, ep1);
        if (tid == 0) sts32(base + OFF_EPOCH, ep1);
        STAMP(KSQ == 0, 51);
        float4 v[6];
#pragma unroll 1
        for (uint32_t it = 0; it < (1u << 17); ++it) {
          bool ok = true;
#pragma unroll
          for (int t = 0; t < 6; t++) {
            v[t] = ld_rec(t < 2 ? &g_stats[0][0][(t * 8 + qr) * 128 + tid] : &g_cs[0][hp][(tid & 1) * 4 + t - 2][tid >> 1]);
            ok &= __float_as_uint(v[t].w) == ep1;
          }
          STAMP(KSQ == 0 && it == 0, 18);
          if (ok) break;
          __nanosleep(100);
        }
        STAMP(KSQ == 0, 17);
        __syncwarp();
        STAMP(KSQ == 0, 19);
#pragma unroll
        for (int cc = 0; cc < 2; cc++) sts32(base + OFF_RS + (cc * 128 + tid) * 4, ln_params(v[cc].x, v[cc].y));
        const float cs[3] = {(v[2].x + v[3].x) + (v[4].x + v[5].x), (v[2].y + v[3].y) + (v[4].y + v[5].y),
                             (v[2].z + v[3].z) + (v[4].z + v[5].z)};
#pragma unroll
        for (int blk = 0; blk < 3; blk++) {
          const float t = cs[blk] + __shfl_xor_sync(0xffffffffu, cs[blk], 1);
          cs_put(blk, tid & 1, tid >> 1, (tid & 1) ? 0.f : t);
        }
        fence_proxy_async_smem();
        named_bar_sync(2, 128);
        if (tid < 2) mbar_arrive(bars + 8u * (B_PREP + tid));
        STAMP(KSQ == 0, 48);
      }
    }
#pragma unroll 1
    for (int inst = asst ? 0 : warp >> 2; inst < 8; inst += asst ? 1 : 2) {
      const int L = inst >> 1, ch = inst & 1, gb = ch * 8 + qr;
      if (asst) {
        setmaxnreg_dec<24>();
        if (warp == 8) {
          named_bar_sync(3, 192);
          STA(32);
          if (elect_one()) {
            if ((L & 1) == 0) {
              bulk_store(g_kvA[L >> 1][gb][hp][1], slots + 16384, 16384);
            } else {
              bulk_store(g_kvB[L >> 1][gb][hp], KB_ROW0 + 112 * 128, 2048);
              bulk_store(g_kvB[L >> 1][gb][hp] + 2048, VB_ROW0 + 112 * 128, 2048);
            }
            bulk_commit();
            bulk_wait0();
            fence_proxy_async_all();
            red_relaxed_add(g_flags + F_KV + (gb * 16 + hp) * KSTR, 1u);
            STA(33);
          }
          __syncwarp();
        }
        named_bar_sync(4, 256);
        setmaxnreg_inc<128>();
      } else {
      setmaxnreg_inc<224>();
      {
        float acc[2][96];
        const int ksp = q_split(inst);
        int n = q_first(inst);
        uint32_t dlt = (ch == 0 && L > 0) ? 10u * (UNIT >> 4) : 0u;
        if (inst != 0 && inst != 2 && inst != 6) {
          mbar_wait_lazy<100>(bars + 8u * (B_TURN + ch), tpar);
          tpar ^= 1u;
        }
        if (L == 3) GTL(37);
        mbar_wait(bars + 8u * (B_FULL + (n & 7)), (n >> 3) & 1);
        GTL(1 + L * 8);
        {
          const uint32_t da = (base >> 4) + 0x10000u + dlt;
          const uint64_t db = desc_lo(da - 0x10000u + ((UNIT >> 4) << 16) + 2 * (UNIT >> 4));
          wgmma_fence();
          wgmma_n192_ssz_ta0_tb1(acc[0], desc_lo(da), db);
          wgmma_commit();
          wgmma_n192_ssz_ta0_tb1(acc[1], desc_lo(da + (UNIT >> 4)), db);
          wgmma_commit();
        }
#pragma unroll 1
        for (int k4 = 0; k4 < 4; k4++) {
          const bool brk = k4 + 1 == ksp && k4 < 3;
#pragma unroll
          for (int ks = 0; ks < 4; ks++, n++) {
            if (ks == 2 && k4 == 3) break;
            STAMP(inst == KSQ, k4 * 4 + ks);
            const uint32_t da = ((base + ks * 5 * UNIT) >> 4) + 0x10000u + (ks < 2 ? dlt : 0u - dlt);
            const uint32_t dbb = da - 0x10000u + ((UNIT >> 4) << 16) + 2 * (UNIT >> 4);
#pragma unroll
            for (int k16 = 0; k16 < 4; k16++) {
              if (ks == 0 && k16 == 0 && k4 == 0) continue;
              const uint64_t db = desc_lo(dbb + k16 * 128);
              wgmma_fence();
              wgmma_n192_ss_ta0_tb1(acc[0], desc_lo(da + k16 * 2), db, 1);
              wgmma_commit();
              wgmma_wait<1>();
              if (k16 == 0 && lane0 && (ks != 0 || k4 != ksp)) mbar_arrive(bars + 8u * (B_EMPTY + ((n - 1) & 7)));
              wgmma_fence();
              wgmma_n192_ss_ta0_tb1(acc[1], desc_lo(da + (UNIT >> 4) + k16 * 2), db, 1);
              wgmma_commit();
              bool ok = true;
              if (k16 == 2) ok = mbar_test(bars + 8u * (B_FULL + ((n + 1) & 7)), ((n + 1) >> 3) & 1) || (ks == 3 && brk);
              if (k16 == QTURN && ks == 3 && brk && lane0) mbar_arrive(bars + 8u * (B_TURN + (ch ^ 1)));
              if ((ks & 1) == 0 || k16 < 3) wgmma_wait<1>();
              if (k16 == 2 && !ok) mbar_wait(bars + 8u * (B_FULL + ((n + 1) & 7)), ((n + 1) >> 3) & 1);
            }
          }
          if (brk) {
            wgmma_wait<0>();
            if (lane0) mbar_arrive(bars + 8u * (B_EMPTY + ((n - 1) & 7)));
            n += 16;
            dlt ^= 10u * (UNIT >> 4);
            mbar_wait_lazy<100>(bars + 8u * (B_TURN + ch), tpar);
            tpar ^= 1u;
            STAMP(inst == KSQ, 17);
            mbar_wait(bars + 8u * (B_FULL + (n & 7)), (n >> 3) & 1);
          }
        }
        auto tail_group = [&](int u) {
          const uint32_t da = ((base + (2 + (u & 1)) * 5 * UNIT) >> 4) + 0x10000u - dlt;
          const uint32_t dbb = da - 0x10000u + ((UNIT >> 4) << 16) + 2 * (UNIT >> 4);
          if (u < 3) wgmma_fence();
#pragma unroll
          for (int k16 = 0; k16 < 4; k16++)
            wgmma_n192_ss_ta0_tb1(acc[u < 2], desc_lo(da + (u < 2 ? UNIT >> 4 : 0) + k16 * 2), desc_lo(dbb + k16 * 128), 1);
          wgmma_commit();
        };
        STAMP(inst == KSQ, 14);
        tail_group(0);
        wgmma_wait<1>();
        STAMP(inst == KSQ, 42);
        if (lane0) mbar_arrive(bars + 8u * (B_EMPTY + ((n - 1) & 7)));
        PHASE_IDS
        mbar_wait(bars + 8u * (B_PREP + ch), L & 1);
        STAMP(inst == KSQ, 43);
        uint32_t rs[4];
#pragma unroll
        for (int i = 0; i < 4; i++)
          rs[i] = lds32(base + OFF_RS + (ch * 128 + (i >> 1) * 64 + wwarp * 16 + g + 8 * (i & 1)) * 4);
        auto fold = [&](int h) {
          uint32_t a[2];
#pragma unroll
          for (int r = 0; r < 2; r++) a[r] = c == (L & 1) ? __byte_perm(rs[2 * h + r], 0, 0x1010) ^ 0x80008000u : 0u;
          uint64_t d;
          asm("mov.b64 %0, {%1, %2};" : "=l"(d) : "r"(((base + OFF_CS) >> 4) + ((512 >> 4) << 16)), "r"(0x40000000u));
          wgmma_fence();
          wgmma_n192_rs_tb1(acc[h], a[0], a[1], d);
        };
        fold(1);
        wgmma_commit();
        mbar_wait(bars + 8u * (B_FULL + ((n + 1) & 7)), ((n + 1) >> 3) & 1);
        STAMP(inst == KSQ, 44);
        tail_group(1);
        tail_group(2);
        STAMP(inst == KSQ, 45);
        const bool afree = mbar_test(bars + 8u * B_AFREE, inst & 1);
        float rinv[2][2];
#pragma unroll
        for (int i = 0; i < 4; i++) rinv[i >> 1][i & 1] = rcp_fast(bf_hi(rs[i]));
        const int mat = lane >> 3;
        const uint32_t soff = (wwarp * 16 + (mat & 1) * 8 + (lane & 7)) * 128;
        const uint32_t kdst = ((L & 1) ? KB_ROW0 : slots) + soff, vdst = ((L & 1) ? VB_ROW0 : slots + 8192) + soff;
        const uint32_t hs = (L & 1) ? 8192 : 16384;
        const int rg = 2 * wwarp + (mat & 1);
        const uint32_t qdst = slots + 3 * 16384 + ((L & 1) ? soff : ((rg < 4 ? 2 * rg : 15 - 2 * rg) * 8 + (lane & 7)) * 128);
        wgmma_wait<2>();
        STAMP(inst == KSQ, 46);
        fold(0);
        tail_group(3);
        STAMP(inst == KSQ, 47);
        if (EPT < 0 && lane0) mbar_arrive(bars + 8u * (B_TURN + (ch ^ 1)));
        if (!afree) {
          if (EPT >= 0 && lane0) mbar_arrive(bars + 8u * (B_TURN + (ch ^ 1)));
          wgmma_wait<1>();
          if (lane0) mbar_arrive(bars + 8u * (B_EMPTY + (n & 7)));
          wgmma_wait<0>();
          if (lane0) mbar_arrive(bars + 8u * (B_EMPTY + ((n + 1) & 7)));
          mbar_wait(bars + 8u * B_AFREE, inst & 1);
        }
        wgmma_wait<2>();
        reg_fence<96>(acc[1]);
        STAMP(inst == KSQ, 15);
#pragma unroll
        for (int t = 0; t < 24; t++) {
          const int h = t < 12 ? 1 : 0, p = (t % 12 / 4 + 1) % 3, jp = t & 3;
          if (t == EPT && lane0 && afree) mbar_arrive(bars + 8u * (B_TURN + (ch ^ 1)));
          if (t == EPW1) {
            wgmma_wait<1>();
            if (lane0 && afree) mbar_arrive(bars + 8u * (B_EMPTY + (n & 7)));
          }
          if (t == EPW0) {
            wgmma_wait<0>();
            reg_fence<96>(acc[0]);
            if (lane0 && afree) mbar_arrive(bars + 8u * (B_EMPTY + ((n + 1) & 7)));
            STAMP(inst == KSQ, 16);
            GTL(2 + L * 8);
          }
          if (t % 12 == 8) {
            rinv[h][0] *= SM_C;
            rinv[h][1] *= SM_C;
          }
          const uint32_t sw = ((2 * jp + (mat >> 1)) ^ (lane & 7)) << 4;
          const float* a = &acc[h][32 * p + 8 * jp];
          const uint32_t dst = p == 0 ? qdst + h * 8192 : (p == 1 ? kdst : vdst) + h * hs;
          stmatrix_x4(dst + sw, pack_bf16x2(a[0] * rinv[h][0], a[1] * rinv[h][0]), pack_bf16x2(a[2] * rinv[h][1], a[3] * rinv[h][1]),
                      pack_bf16x2(a[4] * rinv[h][0], a[5] * rinv[h][0]), pack_bf16x2(a[6] * rinv[h][1], a[7] * rinv[h][1]));
          if (t % 12 == 7) {
            fence_proxy_async_smem();
            named_bar_arrive(t == 7 ? 3 : 7, t == 7 ? 192 : 160);
            if (t > EPW0) sched_fence(P.zero);
          }
        }
      }
      fence_proxy_async_smem();
      setmaxnreg_dec<128>();
      named_bar_sync(4, 256);
      }
      GTL(3 + L * 8);
      {
        PHASE_IDS
        if ((L & 1) == 0) attention_a(asst, L, gb, hp, inst & 1, ch, (tid_ >> 5) & 3, lane, P.zero);
        else attention_b(asst, gb, inst & 1, wwarp, lane);
        GTL(4 + L * 8);
        fence_proxy_async_smem();
      }
      if (asst) {
        named_bar_arrive(5, 256);
        if (inst == 1) {
          mbar_wait(bars + 8u * B_AFREE, 0);
          colsum_part(&P.wqkv[1], 1, qr, hp);
          if (lane0) mbar_arrive(bars + 8u * B_CSD);
        }
        continue;
      }
      {
        named_bar_sync(5, 256);
        const int wwarp = warp & 3;
        if (wwarp < 2 && elect_one()) {
          tma_store_3d(&P.o, ((L & 1) ? slots + 3 * 16384 : OA_TILE) + wwarp * 8192, 0, gb * 128 + wwarp * 64, hp);
          bulk_commit();
          bulk_wait0();
          mbar_arrive(bars + 8u * B_AFREE);
          fence_proxy_async_all();
          red_relaxed_add(g_flags + F_O + (gb * 2 + wwarp) * OSTR + hp, 1u);
        }
        __syncwarp();
      }
      GTL(5 + L * 8);

      {
        float acc[64];
        const int n0 = w_first(inst);
        const bool pre = w_pre(inst);
        const uint32_t dl = ch * 10u * (UNIT >> 4);
        mbar_wait_lazy<100>(bars + 8u * (B_TURN + ch), tpar);
        tpar ^= 1u;
        mbar_wait(bars + 8u * (B_FULL + (n0 & 7)), (n0 >> 3) & 1);
        GTL(6 + L * 8);
#pragma unroll
        for (int kt = 0; kt < 16; kt++) {
          const int n = n0 + kt;
          STAMP(inst == KSW, 20 + kt);
          const uint32_t da = ((base + w_ua(kt) * UNIT) >> 4) + 0x10000u + (w_ua(kt) < 10 ? dl : 0u - dl);
          uint32_t db = ((base + w_ub(kt) * UNIT) >> 4) + ((UNIT >> 4) << 16) + (w_ub(kt) < 10 ? dl : 0u - dl);
          if (pre_idx(kt) >= 0 && pre) db = ((slots + pre_idx(kt) * 2 * UNIT) >> 4) + ((UNIT >> 4) << 16);
          if (kt == PRE0 && pre) mbar_wait(bars + 8u * B_PRE, __popc(PREMASK & ((1u << inst) - 1u)) & 1);
          if (kt == 15 && lane0 && (inst & 3) != 0) mbar_arrive(bars + 8u * (B_TURN + (ch ^ 1)));
          wgmma_fence();
          if (kt == 0) wgmma_n128_ssz_ta0_tb1(acc, desc_lo(da), desc_lo(db));
#pragma unroll
          for (int k16 = kt == 0 ? 1 : 0; k16 < 4; k16++) wgmma_n128_ss_ta0_tb1(acc, desc_lo(da + 2 * k16), desc_lo(db + 128 * k16), 1);
          wgmma_commit();
          const uint32_t nb = bars + 8u * (kt == 15 ? B_RESF : B_FULL + ((n + 1) & 7)), np = kt == 15 ? ch : ((n + 1) >> 3) & 1;
          const bool ok = mbar_test(nb, np);
          if (kt > 0) {
            wgmma_wait<1>();
            if (lane0) mbar_arrive(bars + 8u * (B_EMPTY + ((n - 1) & 7)));
          }
          if (!ok) mbar_wait(nb, np);
        }
        PHASE_IDS
        const uint32_t xb = base + (8 + ch * 10) * UNIT;
        const int mat = lane >> 3;
        const uint32_t xrow = xb + (wwarp * 16 + (mat & 1) * 8 + (lane & 7)) * 128;
        uint32_t xv[8][4];
#pragma unroll
        for (int jp = 0; jp < 8; jp++)
          ldmatrix_x4(xv[jp], xrow + (jp >> 2) * UNIT + (((2 * (jp & 3) + (mat >> 1)) ^ (lane & 7)) << 4));
        wgmma_wait<0>();
        reg_fence<64>(acc);
        if (lane0) mbar_arrive(bars + 8u * (B_EMPTY + ((n0 + 15) & 7)));
        STAMP(inst == KSW, 36);
        GTL(7 + L * 8);
#pragma unroll
        for (int jp = 0; jp < 8; jp++) {
#pragma unroll
          for (int q = 0; q < 4; q++) xv[jp][q] = add_bf16x2(xv[jp][q], pack_bf16x2(acc[8 * jp + 2 * q], acc[8 * jp + 2 * q + 1]));
          stmatrix_x4(xrow + (jp >> 2) * UNIT + (((2 * (jp & 3) + (mat >> 1)) ^ (lane & 7)) << 4), xv[jp][0], xv[jp][1],
                      xv[jp][2], xv[jp][3]);
        }
        fence_proxy_async_smem();
        named_bar_sync(1 + ch, 128);
        const int grow = ch * 1024 + rt * 64;
        if (wwarp == 0) {
          if (elect_one()) {
            tma_store_3d(&P.xr[L == 3 ? 2 : 1], xb, 0, grow, ct * 2);
            bulk_commit();
            bulk_wait_read0();
            mbar_arrive(bars + 8u * B_RESE);
            bulk_wait0();
            TGET(t35);
            fence_proxy_async_all();
            if (L < 3) red_relaxed_add(g_flags + F_X + (ch * 8 + (rt >> 1)) * XSTR + ct, 1u);
            if (L == 2) TPUT(ch, 35, t35);
          }
          __syncwarp();
        } else if (lane == 0) {
          mbar_arrive(bars + 8u * B_RESE);
        }
        if (L < 3) {
          const unsigned ep1 = lds32(base + OFF_EPOCH);
          float s1[2] = {0.f, 0.f}, s2[2] = {0.f, 0.f};
#pragma unroll
          for (int jp = 0; jp < 8; jp++)
#pragma unroll
            for (int q = 0; q < 4; q++) {
              const float x0 = bf_lo(xv[jp][q]), x1 = bf_hi(xv[jp][q]);
              s1[q & 1] += x0 + x1;
              s2[q & 1] = fmaf(x0, x0, fmaf(x1, x1, s2[q & 1]));
            }
#pragma unroll
          for (int r = 0; r < 2; r++) {
            s1[r] += __shfl_xor_sync(0xffffffffu, s1[r], 1);
            s2[r] += __shfl_xor_sync(0xffffffffu, s2[r], 1);
            s1[r] += __shfl_xor_sync(0xffffffffu, s1[r], 2);
            s2[r] += __shfl_xor_sync(0xffffffffu, s2[r], 2);
            if (c == 0) st_rec(&g_stats[L + 1][ct][grow + wwarp * 16 + g + 8 * r], s1[r], s2[r], 0.f, ep1);
          }
        }
        GTL(8 + L * 8);
      }
    }
    if (threadIdx.x == 128) atomicAdd(g_flags + F_DONE, 1u);
  }
}

typedef CUresult (*PFN_tmEncode)(CUtensorMap*, CUtensorMapDataType, cuuint32_t, void*, const cuuint64_t*,
                                 const cuuint64_t*, const cuuint32_t*, const cuuint32_t*, CUtensorMapInterleave,
                                 CUtensorMapSwizzle, CUtensorMapL2promotion, CUtensorMapFloatOOBfill);

PFN_tmEncode get_encode_fn() {
  static PFN_tmEncode fn = nullptr;
  if (!fn) {
    cudaDriverEntryPointQueryResult qr;
    void* p = nullptr;
    cudaGetDriverEntryPoint("cuTensorMapEncodeTiled", &p, cudaEnableDefault, &qr);
    fn = (PFN_tmEncode)p;
  }
  return fn;
}

CUtensorMap make_map(const void* ptr, int rows, int cols, int inner, int box_rows, int box_blk) {
  CUtensorMap m;
  cuuint64_t gdim[3] = {(cuuint64_t)inner, (cuuint64_t)rows, (cuuint64_t)(cols / inner)};
  cuuint64_t gstr[2] = {(cuuint64_t)cols * 2, (cuuint64_t)inner * 2};
  cuuint32_t box[3] = {64, (cuuint32_t)box_rows, (cuuint32_t)box_blk};
  cuuint32_t estr[3] = {1, 1, 1};
  get_encode_fn()(&m, CU_TENSOR_MAP_DATA_TYPE_BFLOAT16, 3, const_cast<void*>(ptr), gdim, gstr, box, estr,
                  CU_TENSOR_MAP_INTERLEAVE_NONE, CU_TENSOR_MAP_SWIZZLE_128B, CU_TENSOR_MAP_L2_PROMOTION_L2_128B,
                  CU_TENSOR_MAP_FLOAT_OOB_FILL_NONE);
  return m;
}

}

extern "C" void kernel_launch(void* const* d_in, const int* in_sizes, int n_in, void* d_out, int out_size) {
  (void)in_sizes; (void)n_in; (void)out_size;
  void *p_o, *p_x;
  cudaGetSymbolAddress(&p_o, g_o);
  cudaGetSymbolAddress(&p_x, g_x);
  static bool attr_done = false;
  if (!attr_done) {
    cudaFuncSetAttribute(fused_kernel, cudaFuncAttributeMaxDynamicSharedMemorySize, SMEM_BYTES);
    attr_done = true;
  }
  Params P;
  P.in_x = (const __nv_bfloat16*)d_in[0];
  P.wqkv_p[0] = (const __nv_bfloat16*)d_in[1];
  P.wo_p[0] = (const __nv_bfloat16*)d_in[2];
  P.wqkv_p[1] = (const __nv_bfloat16*)d_in[4];
  P.wo_p[1] = (const __nv_bfloat16*)d_in[5];
  P.out = (__nv_bfloat16*)d_out;
  P.zero = 0;
  P.xq[0] = make_map(P.in_x, S_LEN, DM, 64, 128, 1);
  P.xq[1] = make_map(p_x, S_LEN, DM, 64, 128, 1);
  P.xr[0] = make_map(P.in_x, S_LEN, DM, 64, 64, 2);
  P.xr[1] = make_map(p_x, S_LEN, DM, 64, 64, 2);
  P.xr[2] = make_map(d_out, S_LEN, DM, 64, 64, 2);
  P.o = make_map(p_o, S_LEN, DM, 64, 64, 1);
  for (int t = 0; t < 2; t++) {
    P.wqkv[t] = make_map(P.wqkv_p[t], DM, NQKV, 1024, 64, 3);
    P.wo[t] = make_map(P.wo_p[t], DM, DM, 64, 64, 2);
  }
  fused_kernel<<<NCTA, 512, SMEM_BYTES>>>(P);
}
```

```cpp
#include <cuda_runtime.h>
#include <cuda_bf16.h>
#include <cuda.h>
#include <stdint.h>

namespace {

constexpr int S_LEN = 2048;
constexpr int DM = 1024;
constexpr int NQKV = 3072;
constexpr int NCTA = 128;

__device__ __align__(1024) uint8_t g_kvA[2][16][16][2][16384];
__device__ __align__(1024) uint8_t g_kvB[2][16][16][4096];
__device__ __align__(1024) uint8_t g_zero[16384];
__device__ __align__(1024) __nv_bfloat16 g_o[S_LEN * DM];
__device__ __align__(1024) __nv_bfloat16 g_x[S_LEN * DM];
__device__ __align__(1024) float4 g_stats[4][8][S_LEN];
__device__ __align__(1024) float4 g_cs[2][16][8][64];
constexpr int F_X = 0;
constexpr int XSTR = 32, OSTR = 32, KSTR = 32;
constexpr int F_O = F_X + 16 * XSTR;
constexpr int F_KV = F_O + 32 * OSTR;
constexpr int F_DONE = F_KV + 256 * KSTR;
__device__ __align__(1024) unsigned g_flags[F_DONE + 32];

constexpr uint32_t SBASE = 1024;
constexpr int UNIT = 8192;
constexpr int NUNITS = 20;
constexpr int OFF_SLOT = NUNITS * UNIT;
constexpr int OFF_CS = OFF_SLOT + 4 * 16384;
constexpr int OFF_RS = OFF_CS + 1536;
constexpr int OFF_BAR = OFF_RS + 1024;
constexpr int OFF_EPOCH = OFF_BAR + 296;
constexpr int OFF_TS = OFF_BAR + 304;
constexpr int SMEM_BYTES = OFF_TS;
constexpr int B_FULL = 0, B_EMPTY = 8, B_PREP = 16, B_HALO = 18, B_REL = 22, B_AFREE = 25, B_TURN = 26, B_XRDY = 28,
              B_CS = 30, B_CSD = 31, B_GO = 32, B_PRE = 33, B_RESF = 34, B_RESE = 35;

__device__ __forceinline__ uint32_t smem_u32(const void* p) { return (uint32_t)__cvta_generic_to_shared(p); }

__device__ __forceinline__ void mbar_init(uint32_t bar, uint32_t cnt) {
  asm volatile("mbarrier.init.shared::cta.b64 [%0], %1;" ::"r"(bar), "r"(cnt));
}
__device__ __forceinline__ void mbar_expect_tx(uint32_t bar, uint32_t bytes) {
  asm volatile("mbarrier.arrive.expect_tx.shared::cta.b64 _, [%0], %1;" ::"r"(bar), "r"(bytes) : "memory");
}
__device__ __forceinline__ void mbar_arrive(uint32_t bar) {
  asm volatile("mbarrier.arrive.shared::cta.b64 _, [%0];" ::"r"(bar) : "memory");
}
__device__ __forceinline__ bool mbar_try_wait(uint32_t bar, uint32_t parity) {
  uint32_t ok;
  asm volatile(
      "{\n.reg .pred p;\nmbarrier.try_wait.parity.shared::cta.b64 p, [%1], %2;\nselp.b32 %0, 1, 0, p;\n}\n"
      : "=r"(ok)
      : "r"(bar), "r"(parity)
      : "memory");
  return ok != 0;
}
__device__ __forceinline__ bool mbar_test(uint32_t bar, uint32_t parity) {
  uint32_t ok;
  asm volatile(
      "{\n.reg .pred p;\nmbarrier.test_wait.parity.shared::cta.b64 p, [%1], %2;\nselp.b32 %0, 1, 0, p;\n}\n"
      : "=r"(ok)
      : "r"(bar), "r"(parity)
      : "memory");
  return ok != 0;
}
__device__ __forceinline__ void mbar_wait(uint32_t bar, uint32_t parity) {
#pragma unroll 1
  for (uint32_t it = 0; it < (1u << 18); ++it) {
    if (mbar_try_wait(bar, parity)) return;
  }
}
__device__ __forceinline__ void mbar_pace(uint32_t bar, uint32_t parity) {
#pragma unroll 1
  for (uint32_t it = 0; it < 24; ++it) {
    if (mbar_try_wait(bar, parity)) return;
  }
}
template <int NS>
__device__ __forceinline__ void mbar_wait_lazy(uint32_t bar, uint32_t parity) {
#pragma unroll 1
  for (uint32_t it = 0; it < (1u << 18); ++it) {
    if (mbar_try_wait(bar, parity)) return;
    __nanosleep(NS);
  }
}
__device__ __forceinline__ bool elect_one() {
  uint32_t ok;
  asm volatile("{\n.reg .pred p;\nelect.sync _|p, 0xffffffff;\nselp.b32 %0, 1, 0, p;\n}\n" : "=r"(ok));
  return ok != 0;
}
__device__ __forceinline__ void fence_barrier_init() { asm volatile("fence.mbarrier_init.release.cluster;" ::: "memory"); }
__device__ __forceinline__ void fence_proxy_async_smem() { asm volatile("fence.proxy.async.shared::cta;" ::: "memory"); }
__device__ __forceinline__ void fence_proxy_async_all() { asm volatile("fence.proxy.async.global;" ::: "memory"); }

__device__ __forceinline__ void tma_load_3d(uint32_t dst, const CUtensorMap* map, uint32_t bar, int c0, int c1, int c2) {
  asm volatile(
      "cp.async.bulk.tensor.3d.shared::cluster.global.mbarrier::complete_tx::bytes [%0], [%1, {%3, %4, %5}], [%2];" ::"r"(dst),
      "l"(map), "r"(bar), "r"(c0), "r"(c1), "r"(c2)
      : "memory");
}
__device__ __forceinline__ void bulk_load(uint32_t dst, const void* src, uint32_t bytes, uint32_t bar) {
  asm volatile("cp.async.bulk.shared::cluster.global.mbarrier::complete_tx::bytes [%0], [%1], %2, [%3];" ::"r"(dst),
               "l"(src), "r"(bytes), "r"(bar)
               : "memory");
}
__device__ __forceinline__ void bulk_store(void* dst, uint32_t src, uint32_t bytes) {
  asm volatile("cp.async.bulk.global.shared::cta.bulk_group [%0], [%1], %2;" ::"l"(dst), "r"(src), "r"(bytes) : "memory");
}
__device__ __forceinline__ void tma_store_3d(const CUtensorMap* map, uint32_t src, int c0, int c1, int c2) {
  asm volatile("cp.async.bulk.tensor.3d.global.shared::cta.bulk_group [%0, {%2, %3, %4}], [%1];" ::"l"(map), "r"(src),
               "r"(c0), "r"(c1), "r"(c2)
               : "memory");
}
__device__ __forceinline__ void bulk_commit() { asm volatile("cp.async.bulk.commit_group;" ::: "memory"); }
__device__ __forceinline__ void bulk_wait_read0() { asm volatile("cp.async.bulk.wait_group.read 0;" ::: "memory"); }
__device__ __forceinline__ void bulk_wait0() { asm volatile("cp.async.bulk.wait_group 0;" ::: "memory"); }
__device__ __forceinline__ void named_bar_sync(int id, int nthreads) {
  asm volatile("bar.sync %0, %1;" ::"r"(id), "r"(nthreads) : "memory");
}
__device__ __forceinline__ void named_bar_arrive(int id, int nthreads) {
  asm volatile("bar.arrive %0, %1;" ::"r"(id), "r"(nthreads) : "memory");
}

__device__ __forceinline__ void wgmma_fence() { asm volatile("wgmma.fence.sync.aligned;\n" ::: "memory"); }
__device__ __forceinline__ void wgmma_commit() { asm volatile("wgmma.commit_group.sync.aligned;\n" ::: "memory"); }
template <int N>
__device__ __forceinline__ void wgmma_wait() {
  asm volatile("wgmma.wait_group.sync.aligned %0;\n" ::"n"(N) : "memory");
}
template <int R>
__device__ __forceinline__ void setmaxnreg_inc() { asm volatile("setmaxnreg.inc.sync.aligned.u32 %0;\n" ::"n"(R)); }
template <int R>
__device__ __forceinline__ void setmaxnreg_dec() { asm volatile("setmaxnreg.dec.sync.aligned.u32 %0;\n" ::"n"(R)); }
template <int N>
__device__ __forceinline__ void reg_fence(float* r) {
#pragma unroll
  for (int i = 0; i < N; i++) asm volatile("" : "+f"(r[i])::"memory");
}

template <int N>
__device__ __forceinline__ void reg_define(float* r) {
#pragma unroll
  for (int i = 0; i < N; i++) r[i] = 0.f;
}

__device__ __forceinline__ uint64_t desc_lo(uint32_t lo) {
  uint64_t d;
  asm("mov.b64 %0, {%1, %2};" : "=l"(d) : "r"(lo), "r"(0x40000040u));
  return d;
}
__device__ __forceinline__ uint64_t make_desc(uint32_t addr, uint32_t lbo_bytes) {
  return desc_lo((addr >> 4) + ((lbo_bytes >> 4) << 16));
}

__device__ __forceinline__ void wgmma_n192_ss_ta0_tb1(float* d, uint64_t descA, uint64_t descB, int scaleD) {
  asm volatile("{\n.reg .pred p;\nsetp.ne.b32 p, %98, 0;\n"
    "wgmma.mma_async.sync.aligned.m64n192k16.f32.bf16.bf16 {%0, %1, %2, %3, %4, %5, %6, %7, %8, %9, %10, %11, %12, %13, %14, %15, %16, %17, %18, %19, %20, %21, %22, %23, %24, %25, %26, %27, %28, %29, %30, %31, %32, %33, %34, %35, %36, %37, %38, %39, %40, %41, %42, %43, %44, %45, %46, %47, %48, %49, %50, %51, %52, %53, %54, %55, %56, %57, %58, %59, %60, %61, %62, %63, %64, %65, %66, %67, %68, %69, %70, %71, %72, %73, %74, %75, %76, %77, %78, %79, %80, %81, %82, %83, %84, %85, %86, %87, %88, %89, %90, %91, %92, %93, %94, %95}, %96, %97, p, 1, 1, 0, 1;\n}\n"
    : "+f"(d[0]), "+f"(d[1]), "+f"(d[2]), "+f"(d[3]), "+f"(d[4]), "+f"(d[5]), "+f"(d[6]), "+f"(d[7]), "+f"(d[8]), "+f"(d[9]), "+f"(d[10]), "+f"(d[11]), "+f"(d[12]), "+f"(d[13]), "+f"(d[14]), "+f"(d[15]), "+f"(d[16]), "+f"(d[17]), "+f"(d[18]), "+f"(d[19]), "+f"(d[20]), "+f"(d[21]), "+f"(d[22]), "+f"(d[23]), "+f"(d[24]), "+f"(d[25]), "+f"(d[26]), "+f"(d[27]), "+f"(d[28]), "+f"(d[29]), "+f"(d[30]), "+f"(d[31]), "+f"(d[32]), "+f"(d[33]), "+f"(d[34]), "+f"(d[35]), "+f"(d[36]), "+f"(d[37]), "+f"(d[38]), "+f"(d[39]), "+f"(d[40]), "+f"(d[41]), "+f"(d[42]), "+f"(d[43]), "+f"(d[44]), "+f"(d[45]), "+f"(d[46]), "+f"(d[47]), "+f"(d[48]), "+f"(d[49]), "+f"(d[50]), "+f"(d[51]), "+f"(d[52]), "+f"(d[53]), "+f"(d[54]), "+f"(d[55]), "+f"(d[56]), "+f"(d[57]), "+f"(d[58]), "+f"(d[59]), "+f"(d[60]), "+f"(d[61]), "+f"(d[62]), "+f"(d[63]), "+f"(d[64]), "+f"(d[65]), "+f"(d[66]), "+f"(d[67]), "+f"(d[68]), "+f"(d[69]), "+f"(d[70]), "+f"(d[71]), "+f"(d[72]), "+f"(d[73]), "+f"(d[74]), "+f"(d[75]), "+f"(d[76]), "+f"(d[77]), "+f"(d[78]), "+f"(d[79]), "+f"(d[80]), "+f"(d[81]), "+f"(d[82]), "+f"(d[83]), "+f"(d[84]), "+f"(d[85]), "+f"(d[86]), "+f"(d[87]), "+f"(d[88]), "+f"(d[89]), "+f"(d[90]), "+f"(d[91]), "+f"(d[92]), "+f"(d[93]), "+f"(d[94]), "+f"(d[95])
    : "l"(descA), "l"(descB), "r"(scaleD));
}

__device__ __forceinline__ void wgmma_n128_ss_ta0_tb1(float* d, uint64_t descA, uint64_t descB, int scaleD) {
  asm volatile("{\n.reg .pred p;\nsetp.ne.b32 p, %66, 0;\n"
    "wgmma.mma_async.sync.aligned.m64n128k16.f32.bf16.bf16 {%0, %1, %2, %3, %4, %5, %6, %7, %8, %9, %10, %11, %12, %13, %14, %15, %16, %17, %18, %19, %20, %21, %22, %23, %24, %25, %26, %27, %28, %29, %30, %31, %32, %33, %34, %35, %36, %37, %38, %39, %40, %41, %42, %43, %44, %45, %46, %47, %48, %49, %50, %51, %52, %53, %54, %55, %56, %57, %58, %59, %60, %61, %62, %63}, %64, %65, p, 1, 1, 0, 1;\n}\n"
    : "+f"(d[0]), "+f"(d[1]), "+f"(d[2]), "+f"(d[3]), "+f"(d[4]), "+f"(d[5]), "+f"(d[6]), "+f"(d[7]), "+f"(d[8]), "+f"(d[9]), "+f"(d[10]), "+f"(d[11]), "+f"(d[12]), "+f"(d[13]), "+f"(d[14]), "+f"(d[15]), "+f"(d[16]), "+f"(d[17]), "+f"(d[18]), "+f"(d[19]), "+f"(d[20]), "+f"(d[21]), "+f"(d[22]), "+f"(d[23]), "+f"(d[24]), "+f"(d[25]), "+f"(d[26]), "+f"(d[27]), "+f"(d[28]), "+f"(d[29]), "+f"(d[30]), "+f"(d[31]), "+f"(d[32]), "+f"(d[33]), "+f"(d[34]), "+f"(d[35]), "+f"(d[36]), "+f"(d[37]), "+f"(d[38]), "+f"(d[39]), "+f"(d[40]), "+f"(d[41]), "+f"(d[42]), "+f"(d[43]), "+f"(d[44]), "+f"(d[45]), "+f"(d[46]), "+f"(d[47]), "+f"(d[48]), "+f"(d[49]), "+f"(d[50]), "+f"(d[51]), "+f"(d[52]), "+f"(d[53]), "+f"(d[54]), "+f"(d[55]), "+f"(d[56]), "+f"(d[57]), "+f"(d[58]), "+f"(d[59]), "+f"(d[60]), "+f"(d[61]), "+f"(d[62]), "+f"(d[63])
    : "l"(descA), "l"(descB), "r"(scaleD));
}

__device__ __forceinline__ void wgmma_n192_ssz_ta0_tb1(float* d, uint64_t descA, uint64_t descB) {
  asm volatile("{\n.reg .pred p;\nsetp.ne.b32 p, 0, 0;\n"
    "wgmma.mma_async.sync.aligned.m64n192k16.f32.bf16.bf16 {%0, %1, %2, %3, %4, %5, %6, %7, %8, %9, %10, %11, %12, %13, %14, %15, %16, %17, %18, %19, %20, %21, %22, %23, %24, %25, %26, %27, %28, %29, %30, %31, %32, %33, %34, %35, %36, %37, %38, %39, %40, %41, %42, %43, %44, %45, %46, %47, %48, %49, %50, %51, %52, %53, %54, %55, %56, %57, %58, %59, %60, %61, %62, %63, %64, %65, %66, %67, %68, %69, %70, %71, %72, %73, %74, %75, %76, %77, %78, %79, %80, %81, %82, %83, %84, %85, %86, %87, %88, %89, %90, %91, %92, %93, %94, %95}, %96, %97, p, 1, 1, 0, 1;\n}\n"
    : "=f"(d[0]), "=f"(d[1]), "=f"(d[2]), "=f"(d[3]), "=f"(d[4]), "=f"(d[5]), "=f"(d[6]), "=f"(d[7]), "=f"(d[8]), "=f"(d[9]), "=f"(d[10]), "=f"(d[11]), "=f"(d[12]), "=f"(d[13]), "=f"(d[14]), "=f"(d[15]), "=f"(d[16]), "=f"(d[17]), "=f"(d[18]), "=f"(d[19]), "=f"(d[20]), "=f"(d[21]), "=f"(d[22]), "=f"(d[23]), "=f"(d[24]), "=f"(d[25]), "=f"(d[26]), "=f"(d[27]), "=f"(d[28]), "=f"(d[29]), "=f"(d[30]), "=f"(d[31]), "=f"(d[32]), "=f"(d[33]), "=f"(d[34]), "=f"(d[35]), "=f"(d[36]), "=f"(d[37]), "=f"(d[38]), "=f"(d[39]), "=f"(d[40]), "=f"(d[41]), "=f"(d[42]), "=f"(d[43]), "=f"(d[44]), "=f"(d[45]), "=f"(d[46]), "=f"(d[47]), "=f"(d[48]), "=f"(d[49]), "=f"(d[50]), "=f"(d[51]), "=f"(d[52]), "=f"(d[53]), "=f"(d[54]), "=f"(d[55]), "=f"(d[56]), "=f"(d[57]), "=f"(d[58]), "=f"(d[59]), "=f"(d[60]), "=f"(d[61]), "=f"(d[62]), "=f"(d[63]), "=f"(d[64]), "=f"(d[65]), "=f"(d[66]), "=f"(d[67]), "=f"(d[68]), "=f"(d[69]), "=f"(d[70]), "=f"(d[71]), "=f"(d[72]), "=f"(d[73]), "=f"(d[74]), "=f"(d[75]), "=f"(d[76]), "=f"(d[77]), "=f"(d[78]), "=f"(d[79]), "=f"(d[80]), "=f"(d[81]), "=f"(d[82]), "=f"(d[83]), "=f"(d[84]), "=f"(d[85]), "=f"(d[86]), "=f"(d[87]), "=f"(d[88]), "=f"(d[89]), "=f"(d[90]), "=f"(d[91]), "=f"(d[92]), "=f"(d[93]), "=f"(d[94]), "=f"(d[95])
    : "l"(descA), "l"(descB));
}

__device__ __forceinline__ void wgmma_n192_rs_tb1(float* d, uint32_t a0, uint32_t a1, uint64_t descB) {
  asm volatile("{\n.reg .pred p;\nsetp.eq.b32 p, 0, 0;\n"
    "wgmma.mma_async.sync.aligned.m64n192k16.f32.bf16.bf16 {%0, %1, %2, %3, %4, %5, %6, %7, %8, %9, %10, %11, %12, %13, %14, %15, %16, %17, %18, %19, %20, %21, %22, %23, %24, %25, %26, %27, %28, %29, %30, %31, %32, %33, %34, %35, %36, %37, %38, %39, %40, %41, %42, %43, %44, %45, %46, %47, %48, %49, %50, %51, %52, %53, %54, %55, %56, %57, %58, %59, %60, %61, %62, %63, %64, %65, %66, %67, %68, %69, %70, %71, %72, %73, %74, %75, %76, %77, %78, %79, %80, %81, %82, %83, %84, %85, %86, %87, %88, %89, %90, %91, %92, %93, %94, %95}, {%96, %97, %98, %98}, %99, p, 1, 1, 1;\n}\n"
    : "+f"(d[0]), "+f"(d[1]), "+f"(d[2]), "+f"(d[3]), "+f"(d[4]), "+f"(d[5]), "+f"(d[6]), "+f"(d[7]), "+f"(d[8]), "+f"(d[9]), "+f"(d[10]), "+f"(d[11]), "+f"(d[12]), "+f"(d[13]), "+f"(d[14]), "+f"(d[15]), "+f"(d[16]), "+f"(d[17]), "+f"(d[18]), "+f"(d[19]), "+f"(d[20]), "+f"(d[21]), "+f"(d[22]), "+f"(d[23]), "+f"(d[24]), "+f"(d[25]), "+f"(d[26]), "+f"(d[27]), "+f"(d[28]), "+f"(d[29]), "+f"(d[30]), "+f"(d[31]), "+f"(d[32]), "+f"(d[33]), "+f"(d[34]), "+f"(d[35]), "+f"(d[36]), "+f"(d[37]), "+f"(d[38]), "+f"(d[39]), "+f"(d[40]), "+f"(d[41]), "+f"(d[42]), "+f"(d[43]), "+f"(d[44]), "+f"(d[45]), "+f"(d[46]), "+f"(d[47]), "+f"(d[48]), "+f"(d[49]), "+f"(d[50]), "+f"(d[51]), "+f"(d[52]), "+f"(d[53]), "+f"(d[54]), "+f"(d[55]), "+f"(d[56]), "+f"(d[57]), "+f"(d[58]), "+f"(d[59]), "+f"(d[60]), "+f"(d[61]), "+f"(d[62]), "+f"(d[63]), "+f"(d[64]), "+f"(d[65]), "+f"(d[66]), "+f"(d[67]), "+f"(d[68]), "+f"(d[69]), "+f"(d[70]), "+f"(d[71]), "+f"(d[72]), "+f"(d[73]), "+f"(d[74]), "+f"(d[75]), "+f"(d[76]), "+f"(d[77]), "+f"(d[78]), "+f"(d[79]), "+f"(d[80]), "+f"(d[81]), "+f"(d[82]), "+f"(d[83]), "+f"(d[84]), "+f"(d[85]), "+f"(d[86]), "+f"(d[87]), "+f"(d[88]), "+f"(d[89]), "+f"(d[90]), "+f"(d[91]), "+f"(d[92]), "+f"(d[93]), "+f"(d[94]), "+f"(d[95])
    : "r"(a0), "r"(a1), "r"(0u), "l"(descB));
}

__device__ __forceinline__ void wgmma_n128_ssz_ta0_tb1(float* d, uint64_t descA, uint64_t descB) {
  asm volatile("{\n.reg .pred p;\nsetp.ne.b32 p, 0, 0;\n"
    "wgmma.mma_async.sync.aligned.m64n128k16.f32.bf16.bf16 {%0, %1, %2, %3, %4, %5, %6, %7, %8, %9, %10, %11, %12, %13, %14, %15, %16, %17, %18, %19, %20, %21, %22, %23, %24, %25, %26, %27, %28, %29, %30, %31, %32, %33, %34, %35, %36, %37, %38, %39, %40, %41, %42, %43, %44, %45, %46, %47, %48, %49, %50, %51, %52, %53, %54, %55, %56, %57, %58, %59, %60, %61, %62, %63}, %64, %65, p, 1, 1, 0, 1;\n}\n"
    : "=f"(d[0]), "=f"(d[1]), "=f"(d[2]), "=f"(d[3]), "=f"(d[4]), "=f"(d[5]), "=f"(d[6]), "=f"(d[7]), "=f"(d[8]), "=f"(d[9]), "=f"(d[10]), "=f"(d[11]), "=f"(d[12]), "=f"(d[13]), "=f"(d[14]), "=f"(d[15]), "=f"(d[16]), "=f"(d[17]), "=f"(d[18]), "=f"(d[19]), "=f"(d[20]), "=f"(d[21]), "=f"(d[22]), "=f"(d[23]), "=f"(d[24]), "=f"(d[25]), "=f"(d[26]), "=f"(d[27]), "=f"(d[28]), "=f"(d[29]), "=f"(d[30]), "=f"(d[31]), "=f"(d[32]), "=f"(d[33]), "=f"(d[34]), "=f"(d[35]), "=f"(d[36]), "=f"(d[37]), "=f"(d[38]), "=f"(d[39]), "=f"(d[40]), "=f"(d[41]), "=f"(d[42]), "=f"(d[43]), "=f"(d[44]), "=f"(d[45]), "=f"(d[46]), "=f"(d[47]), "=f"(d[48]), "=f"(d[49]), "=f"(d[50]), "=f"(d[51]), "=f"(d[52]), "=f"(d[53]), "=f"(d[54]), "=f"(d[55]), "=f"(d[56]), "=f"(d[57]), "=f"(d[58]), "=f"(d[59]), "=f"(d[60]), "=f"(d[61]), "=f"(d[62]), "=f"(d[63])
    : "l"(descA), "l"(descB));
}

__device__ __forceinline__ void wgmma_n64_ss_ta0_tb0(float* d, uint64_t descA, uint64_t descB, int scaleD) {
  asm volatile("{\n.reg .pred p;\nsetp.ne.b32 p, %34, 0;\n"
    "wgmma.mma_async.sync.aligned.m64n64k16.f32.bf16.bf16 {%0, %1, %2, %3, %4, %5, %6, %7, %8, %9, %10, %11, %12, %13, %14, %15, %16, %17, %18, %19, %20, %21, %22, %23, %24, %25, %26, %27, %28, %29, %30, %31}, %32, %33, p, 1, 1, 0, 0;\n}\n"
    : "+f"(d[0]), "+f"(d[1]), "+f"(d[2]), "+f"(d[3]), "+f"(d[4]), "+f"(d[5]), "+f"(d[6]), "+f"(d[7]), "+f"(d[8]), "+f"(d[9]), "+f"(d[10]), "+f"(d[11]), "+f"(d[12]), "+f"(d[13]), "+f"(d[14]), "+f"(d[15]), "+f"(d[16]), "+f"(d[17]), "+f"(d[18]), "+f"(d[19]), "+f"(d[20]), "+f"(d[21]), "+f"(d[22]), "+f"(d[23]), "+f"(d[24]), "+f"(d[25]), "+f"(d[26]), "+f"(d[27]), "+f"(d[28]), "+f"(d[29]), "+f"(d[30]), "+f"(d[31])
    : "l"(descA), "l"(descB), "r"(scaleD));
}

__device__ __forceinline__ void wgmma_n64_ssz_ta0_tb0(float* d, uint64_t descA, uint64_t descB) {
  asm volatile("{\n.reg .pred p;\nsetp.ne.b32 p, 0, 0;\n"
    "wgmma.mma_async.sync.aligned.m64n64k16.f32.bf16.bf16 {%0, %1, %2, %3, %4, %5, %6, %7, %8, %9, %10, %11, %12, %13, %14, %15, %16, %17, %18, %19, %20, %21, %22, %23, %24, %25, %26, %27, %28, %29, %30, %31}, %32, %33, p, 1, 1, 0, 0;\n}\n"
    : "=f"(d[0]), "=f"(d[1]), "=f"(d[2]), "=f"(d[3]), "=f"(d[4]), "=f"(d[5]), "=f"(d[6]), "=f"(d[7]), "=f"(d[8]), "=f"(d[9]), "=f"(d[10]), "=f"(d[11]), "=f"(d[12]), "=f"(d[13]), "=f"(d[14]), "=f"(d[15]), "=f"(d[16]), "=f"(d[17]), "=f"(d[18]), "=f"(d[19]), "=f"(d[20]), "=f"(d[21]), "=f"(d[22]), "=f"(d[23]), "=f"(d[24]), "=f"(d[25]), "=f"(d[26]), "=f"(d[27]), "=f"(d[28]), "=f"(d[29]), "=f"(d[30]), "=f"(d[31])
    : "l"(descA), "l"(descB));
}

__device__ __forceinline__ void wgmma_n80_ss_ta0_tb0(float* d, uint64_t descA, uint64_t descB, int scaleD) {
  asm volatile("{\n.reg .pred p;\nsetp.ne.b32 p, %42, 0;\n"
    "wgmma.mma_async.sync.aligned.m64n80k16.f32.bf16.bf16 {%0, %1, %2, %3, %4, %5, %6, %7, %8, %9, %10, %11, %12, %13, %14, %15, %16, %17, %18, %19, %20, %21, %22, %23, %24, %25, %26, %27, %28, %29, %30, %31, %32, %33, %34, %35, %36, %37, %38, %39}, %40, %41, p, 1, 1, 0, 0;\n}\n"
    : "+f"(d[0]), "+f"(d[1]), "+f"(d[2]), "+f"(d[3]), "+f"(d[4]), "+f"(d[5]), "+f"(d[6]), "+f"(d[7]), "+f"(d[8]), "+f"(d[9]), "+f"(d[10]), "+f"(d[11]), "+f"(d[12]), "+f"(d[13]), "+f"(d[14]), "+f"(d[15]), "+f"(d[16]), "+f"(d[17]), "+f"(d[18]), "+f"(d[19]), "+f"(d[20]), "+f"(d[21]), "+f"(d[22]), "+f"(d[23]), "+f"(d[24]), "+f"(d[25]), "+f"(d[26]), "+f"(d[27]), "+f"(d[28]), "+f"(d[29]), "+f"(d[30]), "+f"(d[31]), "+f"(d[32]), "+f"(d[33]), "+f"(d[34]), "+f"(d[35]), "+f"(d[36]), "+f"(d[37]), "+f"(d[38]), "+f"(d[39])
    : "l"(descA), "l"(descB), "r"(scaleD));
}

__device__ __forceinline__ void wgmma_n32_rs_tb1(float* d, const uint32_t* a, uint64_t descB, int scaleD) {
  asm volatile("{\n.reg .pred p;\nsetp.ne.b32 p, %21, 0;\n"
    "wgmma.mma_async.sync.aligned.m64n32k16.f32.bf16.bf16 {%0, %1, %2, %3, %4, %5, %6, %7, %8, %9, %10, %11, %12, %13, %14, %15}, {%16, %17, %18, %19}, %20, p, 1, 1, 1;\n}\n"
    : "+f"(d[0]), "+f"(d[1]), "+f"(d[2]), "+f"(d[3]), "+f"(d[4]), "+f"(d[5]), "+f"(d[6]), "+f"(d[7]), "+f"(d[8]), "+f"(d[9]), "+f"(d[10]), "+f"(d[11]), "+f"(d[12]), "+f"(d[13]), "+f"(d[14]), "+f"(d[15])
    : "r"(a[0]), "r"(a[1]), "r"(a[2]), "r"(a[3]), "l"(descB), "r"(scaleD));
}

__device__ __forceinline__ uint32_t pack_bf16x2(float lo, float hi) {
  uint32_t r;
  asm("cvt.rn.bf16x2.f32 %0, %1, %2;" : "=r"(r) : "f"(hi), "f"(lo));
  return r;
}
__device__ __forceinline__ float bf_lo(uint32_t p) { return __uint_as_float(p << 16); }
__device__ __forceinline__ float bf_hi(uint32_t p) { return __uint_as_float(p & 0xffff0000u); }
__device__ __forceinline__ float bf16_round(float v) { return __bfloat162float(__float2bfloat16_rn(v)); }
__device__ __forceinline__ float ex2_approx(float x) {
  float r;
  asm("ex2.approx.ftz.f32 %0, %1;" : "=f"(r) : "f"(x));
  return r;
}
__device__ __forceinline__ float rcp_fast(float x) {
  float r;
  asm("rcp.approx.ftz.f32 %0, %1;" : "=f"(r) : "f"(x));
  return r;
}
__device__ __forceinline__ void ldmatrix_x4(uint32_t (&r)[4], uint32_t addr) {
  asm volatile("ldmatrix.sync.aligned.m8n8.x4.shared.b16 {%0,%1,%2,%3}, [%4];"
               : "=r"(r[0]), "=r"(r[1]), "=r"(r[2]), "=r"(r[3])
               : "r"(addr)
               : "memory");
}
__device__ __forceinline__ void stmatrix_x4(uint32_t addr, uint32_t r0, uint32_t r1, uint32_t r2, uint32_t r3) {
  asm volatile("stmatrix.sync.aligned.m8n8.x4.shared.b16 [%0], {%1,%2,%3,%4};" ::"r"(addr), "r"(r0), "r"(r1), "r"(r2),
               "r"(r3));
}
__device__ __forceinline__ uint32_t add_bf16x2(uint32_t a, uint32_t b) {
  uint32_t r;
  asm("add.rn.bf16x2 %0, %1, %2;" : "=r"(r) : "r"(a), "r"(b));
  return r;
}
__device__ __forceinline__ uint4 lds128(uint32_t addr) {
  uint4 v;
  asm volatile("ld.shared.v4.b32 {%0,%1,%2,%3}, [%4];" : "=r"(v.x), "=r"(v.y), "=r"(v.z), "=r"(v.w) : "r"(addr) : "memory");
  return v;
}
__device__ __forceinline__ uint32_t lds32(uint32_t addr) {
  uint32_t v;
  asm volatile("ld.shared.b32 %0, [%1];" : "=r"(v) : "r"(addr) : "memory");
  return v;
}
__device__ __forceinline__ void sts32(uint32_t addr, uint32_t v) {
  asm volatile("st.shared.b32 [%0], %1;" ::"r"(addr), "r"(v) : "memory");
}

__device__ __forceinline__ unsigned ld_acquire_u32(const unsigned* p) {
  unsigned v;
  asm volatile("ld.acquire.gpu.global.u32 %0, [%1];" : "=r"(v) : "l"(p) : "memory");
  return v;
}
__device__ __forceinline__ void red_relaxed_add(unsigned* p, unsigned v) {
  asm volatile("red.relaxed.gpu.global.add.u32 [%0], %1;" ::"l"(p), "r"(v) : "memory");
}
__device__ __forceinline__ void wait_ge(const unsigned* p, unsigned target) {
#pragma unroll 1
  for (uint32_t it = 0; it < (1u << 17); ++it) {
    if ((int)(ld_acquire_u32(p) - target) >= 0) return;
  }
}

__device__ __forceinline__ void wait_ge2(const unsigned* p, unsigned t0, unsigned t1) {
#pragma unroll 1
  for (uint32_t it = 0; it < (1u << 17); ++it) {
    unsigned long long v;
    asm volatile("ld.acquire.gpu.global.u64 %0, [%1];" : "=l"(v) : "l"(p) : "memory");
    if ((int)((unsigned)v - t0) >= 0 && (int)((unsigned)(v >> 32) - t1) >= 0) return;
  }
}

#define PDEPTH 1
#define RELNS 100
#define HDELAY 500
#define PUBPOS 0
#define PGAP 100
template <bool SLOW>
__device__ __forceinline__ void wait_mask(const unsigned* f, int cnt, unsigned target, uint32_t need, uint32_t& seen, int lane) {
  if ((seen & need) == need) return;
  const unsigned* fp = f + (lane & (cnt - 1));
#pragma unroll 1
  for (uint32_t it = 0; it < (1u << 17); ++it) {
    seen = __ballot_sync(0xffffffffu, (int)(ld_acquire_u32(fp) - target) >= 0);
    if ((seen & need) == need) break;
    if (SLOW) __nanosleep(400);
  }
  fence_proxy_async_all();
}
__device__ __forceinline__ void wait_lanes(const unsigned* fp, unsigned target, uint32_t need, uint32_t& seen) {
  if ((seen & need) == need) return;
  unsigned v[PDEPTH];
#pragma unroll
  for (int i = 0; i < PDEPTH; i++) {
    asm volatile("ld.relaxed.gpu.global.u32 %0, [%1];" : "=r"(v[i]) : "l"(fp) : "memory");
    if (i + 1 < PDEPTH) __nanosleep(PGAP);
  }
#pragma unroll 1
  for (uint32_t it = 0; it < (1u << 16); ++it) {
#pragma unroll
    for (int i = 0; i < PDEPTH; i++) {
      seen |= __ballot_sync(0xffffffffu, (int)(v[i] - target) >= 0);
      if ((seen & need) == need) goto done;
      asm volatile("ld.relaxed.gpu.global.u32 %0, [%1];" : "=r"(v[i]) : "l"(fp) : "memory");
    }
  }
done:
  fence_proxy_async_all();
}
__device__ __forceinline__ float4 ld_rec(const float4* p) {
  float4 v;
  asm volatile("ld.relaxed.gpu.global.v4.f32 {%0,%1,%2,%3}, [%4];" : "=f"(v.x), "=f"(v.y), "=f"(v.z), "=f"(v.w) : "l"(p) : "memory");
  return v;
}
__device__ __forceinline__ void st_rec(float4* p, float a, float b, float c, unsigned tag) {
  asm volatile("st.relaxed.gpu.global.v4.f32 [%0], {%1,%2,%3,%4};" ::"l"(p), "f"(a), "f"(b), "f"(c), "f"(__uint_as_float(tag)) : "memory");
}
template <int N>
__device__ __forceinline__ float4 sum_recs(const float4* p, int stride, unsigned tag) {
  float4 s;
#pragma unroll 1
  for (uint32_t it = 0; it < (1u << 17); ++it) {
    float4 v[N];
#pragma unroll
    for (int t = 0; t < N; t++) v[t] = ld_rec(p + t * stride);
    bool ok = true;
    s = make_float4(0.f, 0.f, 0.f, 0.f);
#pragma unroll
    for (int t = 0; t < N; t++) {
      ok &= __float_as_uint(v[t].w) == tag;
      s.x += v[t].x;
      s.y += v[t].y;
      s.z += v[t].z;
    }
    if (ok) break;
    __nanosleep(200);
  }
  return s;
}

__device__ __forceinline__ int fresh_tid() {
  int t;
  asm volatile("mov.u32 %0, %%tid.x;" : "=r"(t));
  return t;
}
#define PHASE_IDS                                  \
  const int tid_ = fresh_tid();                    \
  const int lane = tid_ & 31, wwarp = __shfl_sync(0xffffffffu, (tid_ >> 5) & 3, 0), tid = tid_ & 127; \
  const int g = lane >> 2, c = lane & 3;           \
  (void)tid; (void)g; (void)c; (void)wwarp;

#define STAMPW(cond, i) do { } while (0)
#define STAMP(cond, i) do { } while (0)
#define STA(i) do { } while (0)
#define GTL(i) do { } while (0)
#define GTLX(c, i) do { } while (0)
#define TGET(v) do { } while (0)
#define TPUT(c, i, v) do { } while (0)

constexpr float SM_C = 0.17677669529663687f * 1.4426950408889634f;

constexpr uint32_t OA_TILE = SBASE + OFF_SLOT + 16384;

__device__ __forceinline__ void sched_fence(uint32_t never) {
  asm volatile("{\n.reg .pred p;\nsetp.ne.u32 p, %0, 0;\n@p exit;\n}\n" ::"r"(never) : "memory");
}

template <int K0, int K1>
__device__ __forceinline__ void attn_exp(float (&s)[32]) {
#pragma unroll
  for (int k = K0; k < K1; k++) s[k] = ex2_approx(s[k]);
}
#define ASPL 16
#define ASPM 6
template <int MODE, bool NEXT>
__device__ __forceinline__ void attn_unit(float (&s)[32], float (&sn)[32], float (&o)[16], float (&l)[2], bool valid,
                                          uint32_t vdesc, uint32_t qdesc, uint32_t kdesc, uint32_t tri, int w,
                                          uint32_t hbar, uint32_t hpar, uint32_t rel, uint32_t zero, bool stampon = false) {
  float x[9][2];
  if (MODE == 0) {
    attn_exp<0, ASPL>(s);
  } else {
#pragma unroll
    for (int e = 0; e < 2; e++) {
#pragma unroll
      for (int j = 0; j < 4; j++) x[j][e] = MODE == 1 ? s[4 * j + 2 + e] : s[16 + 4 * j + e];
      x[4][e] = MODE == 1 ? s[e] : s[30 + e];
      x[5][e] = MODE == 1 ? s[18 + e] : s[12 + e];
#pragma unroll
      for (int u = 1; u < 4; u++)
        x[5 + u][e] = MODE == 1 ? (w >= u ? s[4 * u + e] : s[4 * (8 - u) + 2 + e]) : (w >= u ? s[4 * (7 - u) + 2 + e] : s[4 * (u - 1) + e]);
    }
#pragma unroll
    for (int k = 0; k < 2 * ASPM; k++) x[k >> 1][k & 1] = ex2_approx(x[k >> 1][k & 1]);
  }
  sched_fence(zero);
  if (hbar) mbar_wait(hbar, hpar);
  wgmma_wait<0>();
  if (rel) mbar_arrive(rel);
  if (NEXT) {
    wgmma_fence();
    wgmma_n64_ssz_ta0_tb0(sn, desc_lo(qdesc), desc_lo(kdesc));
    wgmma_n64_ss_ta0_tb0(sn, desc_lo(qdesc + 2), desc_lo(kdesc + 2), 1);
    wgmma_commit();
    sched_fence(zero);
  }
  uint32_t p[16];
  if (MODE == 0) {
    attn_exp<ASPL, 32>(s);
#pragma unroll
    for (int k = 0; k < 16; k++) p[k] = pack_bf16x2(s[2 * k], s[2 * k + 1]);
  } else {
#pragma unroll
    for (int k = 2 * ASPM; k < 18; k++) x[k >> 1][k & 1] = ex2_approx(x[k >> 1][k & 1]);
    const uint32_t tm = MODE == 1 ? tri : ~tri;
#pragma unroll
    for (int j = 0; j < 4; j++) {
      p[MODE == 1 ? 2 * j + 1 : 8 + 2 * j] = pack_bf16x2(x[j][0], x[j][1]);
      p[MODE == 1 ? 8 + 2 * j : 2 * j + 1] = 0u;
    }
    p[MODE == 1 ? 0 : 15] = pack_bf16x2(x[4][0], x[4][1]) & (w == 0 ? tm : 0xffffffffu);
    p[MODE == 1 ? 9 : 6] = pack_bf16x2(x[5][0], x[5][1]) & (w == 3 ? tm : 0xffffffffu);
#pragma unroll
    for (int u = 1; u < 4; u++) {
      const uint32_t q = pack_bf16x2(x[5 + u][0], x[5 + u][1]);
      p[MODE == 1 ? 2 * u : 2 * (7 - u) + 1] = q & (w > u ? 0xffffffffu : (w == u ? tm : 0u));
      p[MODE == 1 ? 2 * (8 - u) + 1 : 2 * (u - 1)] = q & (w < u - 1 ? 0xffffffffu : (w == u - 1 ? tm : 0u));
    }
  }
  wgmma_fence();
#pragma unroll
  for (int k = 0; k < 4; k++) wgmma_n32_rs_tb1(o, p + 4 * k, desc_lo(vdesc + k * 128), 1);
  wgmma_commit();
#pragma unroll
  for (int r = 0; r < 2; r++) {
    float t = 0.f;
#pragma unroll
    for (int hf = 0; hf < 2; hf++) {
      if (MODE != 0 && r == MODE - 1 && hf == 2 - MODE) continue;
      const uint32_t* q = p + 8 * hf + r;
      const uint32_t v = add_bf16x2(add_bf16x2(q[0], q[2]), add_bf16x2(q[4], q[6]));
      t = (MODE != 0 && r == MODE - 1) || hf == 0 ? bf_lo(v) + bf_hi(v) : t + (bf_lo(v) + bf_hi(v));
    }
    if (valid) l[r] += t;
  }
  if (NEXT) {
    wgmma_wait<1>();
    reg_fence<32>(sn);
  }
}

__device__ __forceinline__ void attn_a_slow(const uint8_t* __restrict__ kvimg, int L, int gb, int hp,
                                         int hh, int wwarp, int lane) {
  constexpr uint32_t sq = SBASE + OFF_SLOT + 3 * 16384;
  const unsigned ep = (*(volatile unsigned*)(g_flags + F_DONE)) / NCTA;
  wait_ge2(g_flags + F_KV + (gb * 16 + hp) * KSTR, 4u * ep + L + 1u, 2u * ep + (L >> 1) + 1u);
#pragma unroll 1
  for (int t = 0; t < 32; t++) {
    const int row = (t >> 4) * 64 + ((t & 8) ? 7 - wwarp : wwarp) * 8 + (t & 7);
    const int qpos = gb * 128 + row;
    const uint32_t qaddr = sq + ((t >> 4) * 64 + wwarp * 16 + (t & 15)) * 128;
    float mx = -INFINITY, sum = 0.f, acc = 0.f;
#pragma unroll 1
    for (int pass = 0; pass < 2; pass++) {
#pragma unroll 1
      for (int j = 0; j < 8; j++) {
        const int kp = qpos - (lane + 32 * j);
        const uint8_t* kr = kvimg + ((size_t)((kp >> 7) * 16 + hp) * 2 + ((kp >> 6) & 1)) * 16384 + (kp & 63) * 128;
        float d = -INFINITY;
        if (kp >= 0) {
          d = 0.f;
#pragma unroll 1
          for (int q = 0; q < 4; q++) {
            const uint4 kv = __ldcg(reinterpret_cast<const uint4*>(kr + (((hh * 4 + q) ^ (kp & 7)) << 4)));
            const uint4 qv = lds128(qaddr + (((hh * 4 + q) ^ (row & 7)) << 4));
            const uint32_t kw[4] = {kv.x, kv.y, kv.z, kv.w}, qw[4] = {qv.x, qv.y, qv.z, qv.w};
#pragma unroll
            for (int e = 0; e < 4; e++) d = fmaf(bf_lo(kw[e]), bf_lo(qw[e]), fmaf(bf_hi(kw[e]), bf_hi(qw[e]), d));
          }
        }
        if (pass == 0) {
          mx = fmaxf(mx, d);
        } else {
          const float ev = ex2_approx(d - mx);
          sum += ev;
          const float pv = bf16_round(ev);
#pragma unroll 1
          for (int kk = 0; kk < 32; kk++) {
            const float pk = __shfl_sync(0xffffffffu, pv, kk);
            const int k2 = qpos - (kk + 32 * j);
            if (k2 >= 0) {
              const uint8_t* vr = kvimg + ((size_t)((k2 >> 7) * 16 + hp) * 2 + ((k2 >> 6) & 1)) * 16384 + 8192 + (k2 & 63) * 128;
              const unsigned short vv =
                  __ldcg(reinterpret_cast<const unsigned short*>(vr + (((hh * 4 + (lane >> 3)) ^ (k2 & 7)) << 4) + (lane & 7) * 2));
              acc = fmaf(pk, __uint_as_float((uint32_t)vv << 16), acc);
            }
          }
        }
      }
      if (pass == 0) {
#pragma unroll
        for (int o = 16; o > 0; o >>= 1) mx = fmaxf(mx, __shfl_xor_sync(0xffffffffu, mx, o));
      }
    }
#pragma unroll
    for (int o = 16; o > 0; o >>= 1) sum += __shfl_xor_sync(0xffffffffu, sum, o);
    acc *= rcp_fast(sum);
    const float hi = __shfl_down_sync(0xffffffffu, acc, 1);
    __syncwarp();
    if ((lane & 1) == 0)
      sts32(OA_TILE + row * 128 + (((hh * 4 + (lane >> 3)) ^ (row & 7)) << 4) + (lane & 7) * 2, pack_bf16x2(acc, hi));
    __syncwarp();
  }
}

__device__ __forceinline__ void store_o(const float (&o)[16], const float (&inv)[2], uint32_t rowaddr, int hh, int lane) {
  const int mat = lane >> 3, r7 = lane & 7;
#pragma unroll
  for (int jp = 0; jp < 2; jp++)
    stmatrix_x4(rowaddr + (((hh * 4 + 2 * jp + (mat >> 1)) ^ r7) << 4),
                pack_bf16x2(o[8 * jp] * inv[0], o[8 * jp + 1] * inv[0]),
                pack_bf16x2(o[8 * jp + 2] * inv[1], o[8 * jp + 3] * inv[1]),
                pack_bf16x2(o[8 * jp + 4] * inv[0], o[8 * jp + 5] * inv[0]),
                pack_bf16x2(o[8 * jp + 6] * inv[1], o[8 * jp + 7] * inv[1]));
}

__device__ __forceinline__ void attention_a(int HH, int L, int gb, int hp, uint32_t par0, uint32_t parA, int wwarp, int lane,
                                            uint32_t zero) {
  constexpr uint32_t bars = SBASE + OFF_BAR;
  const uint32_t dslot = ((SBASE + OFF_SLOT) >> 4) + 0x10000u + HH * 4;
  const uint32_t dq = dslot + 3 * 1024;
  float sa[32], sb[32], o[2][16], l[2][2];
  auto dch = [&](int n) { return dslot + 1024u * (n % 3 == 0 ? 1 : (n % 3 == 1 ? 0 : 2)); };
  wgmma_fence();
  wgmma_n64_ssz_ta0_tb0(sa, desc_lo(dq + 512), desc_lo(dch(0)));
  wgmma_n64_ss_ta0_tb0(sa, desc_lo(dq + 512 + 2), desc_lo(dch(0) + 2), 1);
  wgmma_commit();
#pragma unroll
  for (int h = 0; h < 2; h++) {
#pragma unroll
    for (int i = 0; i < 16; i++) o[h][i] = 0.f;
    l[h][0] = l[h][1] = 0.f;
  }
  const int dg = (lane >> 2) - 2 * (lane & 3);
  const uint32_t tri = (dg >= 0 ? 0xffffu : 0u) | (dg >= 1 ? 0xffff0000u : 0u);
  const int nmax = 2 * gb + 1;
  wgmma_wait<0>();
  reg_fence<32>(sa);
#define STON false
  auto publish = [&]() {
    if (HH && wwarp == 1 && lane == 0) {
      bulk_wait0();
      fence_proxy_async_all();
      red_relaxed_add(g_flags + F_KV + (gb * 16 + hp) * KSTR + 1, 1u);
    }
    __syncwarp();
  };
#define ATT_STEP(i, MODE)                                                                                            \
  attn_unit<MODE, true>(sa, sb, o[1], l[1], i <= nmax, dch(i) + 512, dq, dch(i + 1), tri, wwarp,                     \
                        i >= 1 ? bars + 8u * (B_HALO + i - 1) : 0u, i == 1 ? par0 : parA, 0u, zero, STON); if (i == 0 && PUBPOS == 0) publish();                \
  attn_unit<MODE, (i < 4)>(sb, sa, o[0], l[0], i + 1 <= nmax, dch(i + 1) + 512, dq + 512, dch(i + 1), tri, wwarp, 0u, \
                           0u, i < 3 && lane == 0 ? bars + 8u * (B_REL + i) : 0u, zero);
  ATT_STEP(0, 1)
  if (PUBPOS == 1) publish();
  ATT_STEP(1, 0)
  ATT_STEP(2, 0)
  ATT_STEP(3, 0)
  ATT_STEP(4, 2)
#undef ATT_STEP
  const uint32_t ra = OA_TILE + (((lane & 8) ? 7 - wwarp : wwarp) * 8 + (lane & 7)) * 128;
  bool bad = false;
#pragma unroll
  for (int h = 1; h >= 0; h--) {
    float inv[2];
#pragma unroll
    for (int r = 0; r < 2; r++) {
      float v = l[h][r];
      v += __shfl_xor_sync(0xffffffffu, v, 1);
      v += __shfl_xor_sync(0xffffffffu, v, 2);
      bad |= !(v <= 1.152921504606846976e18f && v >= 8.673617379884035e-19f);
      inv[r] = rcp_fast(v);
    }
    if (h == 0) wgmma_wait<0>();
    reg_fence<16>(o[h]);
    store_o(o[h], inv, ra + h * 8192, HH, lane);
  }
  if (HH == 0) GTL(45);
  if (__any_sync(0xffffffffu, bad)) attn_a_slow(g_kvA[L >> 1][0][0][0], L, gb, hp, HH, wwarp, lane);
}

constexpr uint32_t KB_ROW0 = SBASE + OFF_SLOT + 2048, VB_ROW0 = SBASE + OFF_SLOT + 24576 + 2048;

__device__ __forceinline__ void attnB_soft(const float (&s)[40], int wwarp, int D, bool edge, bool odd,
                                           uint32_t (&p)[5][4], float (&sum)[2]) {
  float z[2][3];
#define GATHER_(W)                                                                                  \
  _Pragma("unroll") for (int r = 0; r < 2; r++) _Pragma("unroll") for (int t = 0; t < 3; t++)       \
      z[r][t] = odd ? s[4 * (2 * W + r + t) + 2 * r + 1] : s[4 * (2 * W + r + t) + 2 * r];
  if (wwarp < 2) {
    if (wwarp == 0) { GATHER_(0) } else { GATHER_(1) }
  } else {
    if (wwarp == 2) { GATHER_(2) } else { GATHER_(3) }
  }
#undef GATHER_
  float y[2];
  y[0] = D >= 2 ? z[0][0] : z[0][2];
  y[1] = D >= 2 ? z[1][0] : z[1][2];
  if (edge) {
    z[0][1] = -INFINITY;
    if (D >= 2) y[0] = y[1] = -INFINITY;
  }
  float m0 = fmaxf(z[0][1], y[0]), m1 = fmaxf(z[1][1], y[1]);
  m0 = fmaxf(m0, __shfl_xor_sync(0xffffffffu, m0, 1));
  m1 = fmaxf(m1, __shfl_xor_sync(0xffffffffu, m1, 1));
  m0 = fmaxf(m0, __shfl_xor_sync(0xffffffffu, m0, 2));
  m1 = fmaxf(m1, __shfl_xor_sync(0xffffffffu, m1, 2));
  const float e00 = ex2_approx(z[0][1] - m0), e01 = ex2_approx(y[0] - m0);
  const float e10 = ex2_approx(z[1][1] - m1), e11 = ex2_approx(y[1] - m1);
  sum[0] = e00 + e01;
  sum[1] = e10 + e11;
  const int sh = odd ? 16 : 0;
  const uint32_t a0 = pack_bf16x2(e00, 0.f) << sh, a1 = pack_bf16x2(e10, 0.f) << sh;
  const uint32_t b0 = pack_bf16x2(e01, 0.f) << sh, b1 = pack_bf16x2(e11, 0.f) << sh;
  const int kb = wwarp + (D >= 2 ? 0 : 1);
#pragma unroll
  for (int k = 0; k < 5; k++) {
    p[k][0] = k == kb ? b0 : 0u;
    p[k][1] = k == wwarp + 1 ? a1 : 0u;
    p[k][2] = k == wwarp ? a0 : 0u;
    p[k][3] = k == kb ? b1 : 0u;
#pragma unroll
    for (int q = 0; q < 4; q++) asm volatile("" : "+r"(p[k][q]));
  }
}

__device__ __forceinline__ void attnB_s(float (&s)[40], int HH, int h) {
  constexpr uint32_t sq = SBASE + OFF_SLOT + 3 * 16384;
#pragma unroll
  for (int ks = 0; ks < 2; ks++)
    wgmma_n80_ss_ta0_tb0(s, make_desc(sq + h * 8192 + HH * 64 + ks * 32, 16),
                         make_desc(KB_ROW0 + h * 8192 - 2048 + HH * 64 + ks * 32, 16), ks);
}
__device__ __forceinline__ void attnB_pv(float (&o)[16], const uint32_t (&p)[5][4], int HH, int h) {
#pragma unroll
  for (int k = 0; k < 5; k++)
    wgmma_n32_rs_tb1(o, p[k], make_desc(VB_ROW0 + h * 8192 - 2048 + k * 2048 + HH * 64, 16), k);
}

__device__ __forceinline__ void attention_b(int HH, int gb, uint32_t par0, int wwarp, int lane) {
  constexpr uint32_t bars = SBASE + OFF_BAR, sq = SBASE + OFF_SLOT + 3 * 16384;
  float s[40];
  reg_define<40>(s);
  wgmma_fence();
  attnB_s(s, HH, 1);
  wgmma_commit();
  const int g = lane >> 2;
  const bool odd = g & 1;
  const int D = 2 * (lane & 3) + (g & 1) - g;
  const uint32_t ra = sq + (wwarp * 16 + ((lane >> 3) & 1) * 8 + (lane & 7)) * 128;
  wgmma_wait<0>();
  reg_fence<40>(s);
#pragma unroll 1
  for (int h = 1; h >= 0; h--) {
    float o[16], inv[2];
    uint32_t p[5][4];
    reg_define<16>(o);
    attnB_soft(s, wwarp, D, h == 0 && gb == 0 && wwarp == 0, odd, p, inv);
    if (h == 1) {
      mbar_wait(bars + 8u * B_HALO, par0);
      wgmma_fence();
      attnB_s(s, HH, 0);
    }
    wgmma_fence();
    attnB_pv(o, p, HH, h);
    wgmma_commit();
#pragma unroll
    for (int r = 0; r < 2; r++) {
      inv[r] += __shfl_xor_sync(0xffffffffu, inv[r], 1);
      inv[r] += __shfl_xor_sync(0xffffffffu, inv[r], 2);
      inv[r] = rcp_fast(inv[r]);
    }
    wgmma_wait<0>();
    reg_fence<40>(s);
    reg_fence<16>(o);
    store_o(o, inv, ra + h * 8192, HH, lane);
  }
}

#define KTQM 0
#define TRICKLE 300
#define CSI 0
#define PCA 1
#define PCB 3
#define PXB 4
#define EPT -1
#define EPW1 4
#define EPW0 12
#define QTURN 2
struct Params {
  CUtensorMap xq[2], xr[3], o, wqkv[2], wo[2];
  const __nv_bfloat16* in_x;
  const __nv_bfloat16* wqkv_p[2];
  const __nv_bfloat16* wo_p[2];
  __nv_bfloat16* out;
  uint32_t zero;
};

__device__ __forceinline__ void colsum_part(const CUtensorMap* wmap, int ty, int qr, int hp) {
  constexpr uint32_t bars = SBASE + OFF_BAR, slots = SBASE + OFF_SLOT;
  PHASE_IDS
  const unsigned ep1 = (*(volatile unsigned*)(g_flags + F_DONE)) / NCTA + 1u;
  if (wwarp == 0 && elect_one()) {
    mbar_expect_tx(bars + 8u * B_CS, 6 * UNIT);
#pragma unroll 1
    for (int j = 0; j < 2; j++) {
      if (ty == 0) mbar_pace(bars + 8u * (B_EMPTY + PCA + PCB * j), 0);
      else __nanosleep(1000);
      tma_load_3d(slots + j * 3 * UNIT, wmap, bars + 8u * B_CS, hp * 64, qr * 128 + j * 64, 0);
    }
  }
  mbar_wait(bars + 8u * B_CS, ty);
  STAMP(KSQ == 0 && ty == 0, 49);
  const uint32_t src = slots + (tid >> 3) * 128 + (((tid & 7) ^ ((tid >> 3) & 7)) << 4);
#pragma unroll 1
  for (int p = 0; p < 3; p++) {
    float s[8];
#pragma unroll
    for (int e = 0; e < 8; e++) s[e] = 0.f;
#pragma unroll
    for (int j = 0; j < 8; j++) {
      const uint4 v = lds128(src + p * UNIT + (j >> 2) * 3 * UNIT + (j & 3) * 2048);
      const uint32_t x[4] = {v.x, v.y, v.z, v.w};
#pragma unroll
      for (int e = 0; e < 4; e++) {
        s[2 * e] += bf_lo(x[e]);
        s[2 * e + 1] += bf_hi(x[e]);
      }
    }
#pragma unroll
    for (int st = 0; st < 2; st++) {
      const bool up = (lane >> (st + 3)) & 1;
#pragma unroll
      for (int e = 0; e < (4 >> st); e++) {
        const float keep = up ? s[e + (4 >> st)] : s[e], give = up ? s[e] : s[e + (4 >> st)];
        s[e] = keep + __shfl_xor_sync(0xffffffffu, give, 8 << st);
      }
    }
    const uint32_t dst = slots + 6 * UNIT + ((wwarp * 3 + p) * 64 + (lane & 7) * 8 + ((lane >> 3) & 1) * 4 + (lane >> 4) * 2) * 4;
    sts32(dst, __float_as_uint(s[0]));
    sts32(dst + 4, __float_as_uint(s[1]));
  }
  named_bar_sync(6, 128);
  if (tid < 64) {
    float r[3] = {0.f, 0.f, 0.f};
#pragma unroll
    for (int e = 0; e < 12; e++) r[e % 3] += __uint_as_float(lds32(slots + 6 * UNIT + (e * 64 + tid) * 4));
    st_rec(&g_cs[ty][hp][qr][tid], r[0], r[1], r[2], ep1);
    STAMP(KSQ == 0 && ty == 0, 50);
  }
  named_bar_sync(6, 128);
}

__device__ __forceinline__ void cs_put(int blk, int ty, int col, float v) {
  const uint32_t hi = pack_bf16x2(v, 0.f), lo = pack_bf16x2(v - bf_lo(hi), 0.f);
  const uint32_t a = SBASE + OFF_CS + blk * 512 + ty * 256 + col * 2;
  asm volatile("st.shared.b16 [%0], %1;" ::"r"(a ^ (((a >> 7) & 7) << 4)), "h"((unsigned short)hi) : "memory");
  asm volatile("st.shared.b16 [%0], %1;" ::"r"((a + 128) ^ ((((a >> 7) + 1) & 7) << 4)), "h"((unsigned short)lo) : "memory");
}

__device__ __forceinline__ uint32_t ln_params(float s1, float s2) {
  const float mean = s1 * (1.0f / DM);
  const float var = fmaxf(fmaf(-mean, mean, s2 * (1.0f / DM)), 0.f);
  float sd;
  asm("sqrt.approx.f32 %0, %1;" : "=f"(sd) : "f"(bf16_round(bf16_round(var) + 1e-5f)));
  return pack_bf16x2(mean, sd);
}

__host__ __device__ constexpr int w_ua(int kt) { return (kt == 6 ? 20 : 3 * kt) % 20; }
__host__ __device__ constexpr int w_ub(int kt) { return (kt == 6 ? 18 : 3 * kt + 1) % 20; }

#define SPLITS 0x043333334ull
__device__ __forceinline__ int q_split(int inst) { return (int)((SPLITS >> (4 * inst)) & 15ull); }
__device__ __forceinline__ int q_first(int inst) { return inst == 0 ? 0 : 32 * inst - 16; }
__device__ __forceinline__ int w_first(int inst) { return 32 * inst + 16 + 4 * q_split(inst + 1); }
#define PREMASK 0x3Eu
#define PRE0 3
#define PRESH 2
__host__ __device__ constexpr int pre_idx(int kt) {
  const int d = kt - PRE0;
  return (d >= 0 && (d & ((1 << PRESH) - 1)) == 0 && (d >> PRESH) < 4) ? d >> PRESH : -1;
}
__device__ __forceinline__ bool w_pre(int inst) { return (PREMASK >> inst) & 1u; }

__global__ void __launch_bounds__(512, 1) fused_kernel(const __grid_constant__ Params P) {
  extern __shared__ __align__(1024) uint8_t smem_raw[];
  constexpr uint32_t base = SBASE, bars = base + OFF_BAR, slots = base + OFF_SLOT;
  if (smem_u32(smem_raw) != base) __trap();
  const int warp = __shfl_sync(0xffffffffu, threadIdx.x >> 5, 0), lane = threadIdx.x & 31;
  const int b = blockIdx.x;
#define QS 0
#define WS 1
  const int qr = ((b & ((8 << QS) - 1)) >> QS) ^ (((b >> (3 + QS)) & 1) * 7);
  const int hp = ((b >> (3 + QS)) << QS) + (b & ((1 << QS) - 1));
  const int rt = ((b & ((16 << WS) - 1)) >> WS) ^ (((b >> (4 + WS)) & 1) * 15);
  const int ct = ((b >> (4 + WS)) << WS) + (b & ((1 << WS) - 1));

  if (warp == 12) {
    if (elect_one()) {
#pragma unroll
      for (int s = 0; s < 8; s++) {
        mbar_init(bars + 8u * (B_FULL + s), 2);
        mbar_init(bars + 8u * (B_EMPTY + s), 4);
      }
      mbar_init(bars + 8u * B_GO, 1);
      fence_barrier_init();
    }
    __syncwarp();
    named_bar_arrive(0, 512);
  }
  if (threadIdx.x == 0) {
    mbar_init(bars + 8u * B_PREP, 1);
    mbar_init(bars + 8u * (B_PREP + 1), 1);
    for (int s = 0; s < 4; s++) mbar_init(bars + 8u * (B_HALO + s), 1);
    for (int s = 0; s < 3; s++) mbar_init(bars + 8u * (B_REL + s), 8);
    mbar_init(bars + 8u * B_AFREE, 2);
    mbar_init(bars + 8u * B_TURN, 4);
    mbar_init(bars + 8u * (B_TURN + 1), 4);
    mbar_init(bars + 8u * B_CS, 1);
    mbar_init(bars + 8u * B_PRE, 1);
    mbar_init(bars + 8u * B_RESF, 1);
    mbar_init(bars + 8u * B_RESE, 4);
    mbar_init(bars + 8u * B_CSD, 4);
    mbar_init(bars + 8u * B_XRDY, 1);
    mbar_init(bars + 8u * (B_XRDY + 1), 1);
    fence_barrier_init();
  }
  if (warp != 12) named_bar_sync(0, 512);

  if (warp >= 12) {
    setmaxnreg_dec<32>();
    if (warp <= 13) {
      const bool act = warp == 13;
      uint32_t q = 4, dl = 0;
      bool prevw = false;
      unsigned ep1 = 0;
      if (act) {
        mbar_wait(bars + 8u * B_GO, 0);
        ep1 = __shfl_sync(0xffffffffu, (*(volatile unsigned*)(g_flags + F_DONE)) / NCTA + 1u, 0);
      } else {
#pragma unroll 1
        for (int s = 0; s < 16; s++) {
          const uint32_t fb = bars + 8u * (B_FULL + (s & 7)), sa = base + (s & 3) * 5 * UNIT;
          if (s >= 4) mbar_wait(bars + 8u * (B_EMPTY + ((s - 4) & 7)), ((s - 4) >> 3) & 1);
          if (elect_one()) {
            mbar_expect_tx(fb, 5 * UNIT);
            mbar_arrive(fb);
            tma_load_3d(sa, &P.xq[0], fb, 0, qr * 128, s);
            tma_load_3d(sa + 2 * UNIT, &P.wqkv[0], fb, hp * 64, s * 64, 0);
          }
        }
        if (elect_one()) mbar_arrive(bars + 8u * B_GO);
      }
      auto rbar = [&](int b0, int c) { return bars + 8u * b0 + ((8u * (c & 7)) ^ ((q & 1u) << 5)); };
      auto rpar = [&](int c) { return ((q + (c >> 2)) >> 1) & 1u; };
#pragma unroll 1
      for (int sg = 4; sg < 34; sg++) {
        const int part = sg & 3, si = (sg >> 2) - (part & 1), L = si >> 1, ch = si & 1;
        const int k0 = part == 0 ? 0 : 4 * q_split(si), k1 = part == 0 ? 4 * q_split(si) : 16;
        if (part == 3 || (part != 1 && k0 == k1)) continue;
        uint32_t seen = act ? 0u : 0xFFFFu;
        if (part != 1) {
          const CUtensorMap* map = act ? &P.xq[L == 0 ? 0 : 1] : &P.wqkv[L & 1];
          if (act && (L == 0 || __any_sync(0xffffffffu, mbar_test(bars + 8u * (B_XRDY + ch), (L & 1) ^ 1)))) {
            seen = 0xFFFFu;
            fence_proxy_async_all();
          }
#pragma unroll 1
          for (int k4 = k0; k4 < k1; k4 += 4, q++) {
#pragma unroll
            for (int ks = 0; ks < 4; ks++) {
              const int kt = k4 + ks;
              if ((ks & 1) == 0)
                wait_mask<false>(g_flags + F_X + (ch * 8 + qr) * XSTR, 8, 6u * ep1 - 6u + 2u * L, 1u << (kt >> 1), seen, lane);
              if (ks == 0 && prevw) mbar_wait(rbar(B_EMPTY, -5), rpar(-5));
              else mbar_wait(rbar(B_EMPTY, ks - 4), rpar(-4));
              if (ks == 3 && prevw && !act) mbar_wait(bars + 8u * B_RESE, dl == 0 ? 1u : 0u);
              if (elect_one()) {
                mbar_expect_tx(rbar(B_FULL, ks), act ? 2 * UNIT : 3 * UNIT);
                tma_load_3d(base + ks * 5 * UNIT + (act ? 0 : 2 * UNIT) + (ks < 2 ? dl : 0u - dl), map, rbar(B_FULL, ks),
                            act ? 0 : hp * 64, act ? ch * 1024 + qr * 128 : kt * 64, act ? kt : 0);
              }
            }
            prevw = false;
          }
        } else {
          const CUtensorMap* map = act ? &P.o : &P.wo[L & 1];
          const bool pre = !act && w_pre(2 * L + ch);
          const int m0 = ch * 1024 + rt * 64;
#pragma unroll
          for (int kt = 0; kt < 16; kt++) {
            if (kt == 0 || kt == 1 || kt == 4 || kt == 8)
              wait_mask<false>(g_flags + F_O + (ch * 16 + rt) * OSTR, 16, 4u * ep1 - 3u + L,
                               kt == 0 ? 1u : (kt == 1 ? 0xEu : (kt == 4 ? 0xF0u : 0xFF00u)), seen, lane);
            if (kt < 4 && !prevw) mbar_wait(rbar(B_EMPTY, kt - 4 - (kt >> 1)), rpar(-4));
            else mbar_wait(rbar(B_EMPTY, kt - 6), rpar(kt - 6));
            if (kt == 6 && prevw && !act) mbar_wait(bars + 8u * B_RESE, dl == 0 ? 1u : 0u);
            if (elect_one()) {
              if (pre_idx(kt) >= 0 && pre) {
                mbar_arrive(rbar(B_FULL, kt));
              } else {
                mbar_expect_tx(rbar(B_FULL, kt), act ? UNIT : 2 * UNIT);
                const uint32_t da = base + w_ua(kt) * UNIT + (w_ua(kt) < 10 ? dl : 0u - dl);
                const uint32_t db = base + w_ub(kt) * UNIT + (w_ub(kt) < 10 ? dl : 0u - dl);
                tma_load_3d(act ? da : db, map, rbar(B_FULL, kt), 0, act ? m0 : kt * 64, act ? kt : ct * 2);
              }
            }
          }
          if (act && elect_one()) {
            mbar_expect_tx(bars + 8u * B_RESF, 2 * UNIT);
            tma_load_3d(base + 8 * UNIT + dl, &P.xr[L == 0 ? 0 : 1], bars + 8u * B_RESF, 0, m0, ct * 2);
          }
          q += 4;
          dl ^= 10u * UNIT;
          prevw = true;
        }
      }
    } else if (warp == 14) {
      const unsigned ep1 = (*(volatile unsigned*)(g_flags + F_DONE)) / NCTA + 1u;
#pragma unroll 1
      for (int inst = 0; inst < 8; inst++) {
        const int L = inst >> 1, ch = inst & 1, gb = ch * 8 + qr;
        const unsigned* fp = g_flags + F_KV + (max(gb - 1 - ((lane >> 1) & 1), 0) * 16 + hp) * KSTR + (lane & 1);
        const unsigned target = (lane & 1) ? 2u * ep1 - 1u + (L >> 1) : 4u * ep1 - 3u + L;
        uint32_t seen = gb == 0 ? 15u : (gb == 1 ? 12u : 0u);
        named_bar_sync(3, 192);
        STA(34);
        __nanosleep(HDELAY);
        if ((L & 1) == 0) {
#pragma unroll 1
          for (int i = 0; i < 4; i++) {
            wait_lanes(fp, target, 1u << i, seen);
            STA(36 + i);
            if (i > 0) mbar_wait_lazy<RELNS>(bars + 8u * (B_REL + i - 1), ch);
            if (elect_one()) {
              mbar_expect_tx(bars + 8u * (B_HALO + i), 16384);
              bulk_load(slots + (i == 3 ? 2 : 2 - i) * 16384, gb > (i >> 1) ? g_kvA[L >> 1][gb - 1 - (i >> 1)][hp][(i & 1) ^ 1] : g_zero,
                        16384, bars + 8u * (B_HALO + i));
            }
          }
        } else {
          wait_lanes(fp, target, 1u, seen);
        }
        if (elect_one()) {
          if (L & 1) {
            const uint8_t* s1 = gb >= 1 ? g_kvB[L >> 1][gb - 1][hp] : g_zero;
            mbar_expect_tx(bars + 8u * B_HALO, 4096);
            bulk_load(KB_ROW0 - 2048, s1, 2048, bars + 8u * B_HALO);
            bulk_load(VB_ROW0 - 2048, s1 + 2048, 2048, bars + 8u * B_HALO);
          }
          if (w_pre(inst)) {
            mbar_wait(bars + 8u * B_AFREE, (inst & 1) ^ 1);
            if (inst == CSI) mbar_wait(bars + 8u * B_CSD, 0);
            mbar_expect_tx(bars + 8u * B_PRE, 8 * UNIT);
#pragma unroll 1
            for (int j = 0; j < 4; j++) {
              tma_load_3d(slots + j * 2 * UNIT, &P.wo[L & 1], bars + 8u * B_PRE, 0, (PRE0 + (j << PRESH)) * 64, ct * 2);
              __nanosleep(200);
            }
          }
        }
        __syncwarp();
      }
    } else {
      const unsigned ep1 = (*(volatile unsigned*)(g_flags + F_DONE)) / NCTA + 1u;
      mbar_wait(bars + 8u * B_GO, 0);
#pragma unroll 1
      for (int i = 0; i < 20; i++) {
        const char* src = i < 4 ? reinterpret_cast<const char*>(P.wo_p[0]) + (size_t)b * 16384 + i * 4096
                                : (i < 16 ? reinterpret_cast<const char*>(P.wqkv_p[1]) + (size_t)b * 49152 + (i - 4) * 4096
                                          : reinterpret_cast<const char*>(P.wo_p[1]) + (size_t)b * 16384 + (i - 16) * 4096);
        asm volatile("prefetch.global.L2 [%0];" ::"l"(src + lane * 128));
        __nanosleep(TRICKLE);
      }
#pragma unroll 1
      for (int inst = 2; inst < 8; inst++) {
        const int L = inst >> 1, ch = inst & 1, gb = ch * 8 + qr;
        uint32_t seen = 0;
        wait_mask<true>(g_flags + F_X + gb * XSTR, 8, 6u * ep1 - 6u + 2u * L, 0xFFu, seen, lane);
        if (lane == 0) mbar_arrive(bars + 8u * (B_XRDY + ch));
#pragma unroll 1
        for (int h = 0; h < 4; h++) {
          const float4* sp = &g_stats[L][0][gb * 128 + h * 32 + lane];
          const float4 s0 = sum_recs<4>(sp, S_LEN, ep1), s1 = sum_recs<4>(sp + 4 * S_LEN, S_LEN, ep1);
          sts32(base + OFF_RS + (ch * 128 + h * 32 + lane) * 4, ln_params(s0.x + s1.x, s0.y + s1.y));
        }
        if (inst == 2) {
          mbar_wait(bars + 8u * B_CSD, 0);
#pragma unroll 1
          for (int hf = 0; hf < 2; hf++) {
            const float4* cp = &g_cs[1][hp][0][hf * 32 + lane];
            const float4 s0 = sum_recs<4>(cp, 64, ep1), s1 = sum_recs<4>(cp + 4 * 64, 64, ep1);
            cs_put(0, 1, hf * 32 + lane, s0.x + s1.x);
            cs_put(1, 1, hf * 32 + lane, s0.y + s1.y);
            cs_put(2, 1, hf * 32 + lane, s0.z + s1.z);
          }
          fence_proxy_async_smem();
        }
        __syncwarp();
        if (lane == 0) mbar_arrive(bars + 8u * (B_PREP + ch));
      }
    }
  } else {
    const bool asst = warp >= 8;
    const bool lane0 = lane == 0;
    uint32_t tpar = 0;
    GTL(0);
    if (asst) {
      colsum_part(&P.wqkv[0], 0, qr, hp);
      if ((threadIdx.x & 127) < 2) mbar_arrive(bars + 8u * B_AFREE);
    } else if (warp >= 4) {
      PHASE_IDS
      {
        const unsigned ep1 = (*(volatile unsigned*)(g_flags + F_DONE)) / NCTA + 1u;
        const int row = b * 16 + (tid >> 3);
        const uint4* src = reinterpret_cast<const uint4*>(P.in_x + (size_t)row * DM) + (tid & 7);
        float s1 = 0.f, s2 = 0.f;
#pragma unroll 1
        for (int k = 0; k < 4; k++) {
          mbar_pace(bars + 8u * (B_EMPTY + PXB * k / 2), 0);
          uint4 v[4];
#pragma unroll
          for (int j = 0; j < 4; j++) v[j] = __ldg(src + (k * 4 + j) * 8);
#pragma unroll
          for (int j = 0; j < 4; j++) {
            const uint32_t w[4] = {v[j].x, v[j].y, v[j].z, v[j].w};
#pragma unroll
            for (int e = 0; e < 4; e++) {
              const float x0 = bf_lo(w[e]), x1 = bf_hi(w[e]);
              s1 += x0 + x1;
              s2 = fmaf(x0, x0, fmaf(x1, x1, s2));
            }
          }
        }
#pragma unroll
        for (int o = 1; o < 8; o <<= 1) {
          s1 += __shfl_xor_sync(0xffffffffu, s1, o);
          s2 += __shfl_xor_sync(0xffffffffu, s2, o);
        }
        if ((tid & 7) == 0) st_rec(&g_stats[0][0][row], s1, s2, 0.f, ep1);
        if (tid == 0) sts32(base + OFF_EPOCH, ep1);
        STAMP(KSQ == 0, 51);
        float4 v[6];
#pragma unroll 1
        for (uint32_t it = 0; it < (1u << 17); ++it) {
          bool ok = true;
#pragma unroll
          for (int t = 0; t < 6; t++) {
            v[t] = ld_rec(t < 2 ? &g_stats[0][0][(t * 8 + qr) * 128 + tid] : &g_cs[0][hp][(tid & 1) * 4 + t - 2][tid >> 1]);
            ok &= __float_as_uint(v[t].w) == ep1;
          }
          STAMP(KSQ == 0 && it == 0, 18);
          if (ok) break;
          __nanosleep(100);
        }
        STAMP(KSQ == 0, 17);
        __syncwarp();
        STAMP(KSQ == 0, 19);
#pragma unroll
        for (int cc = 0; cc < 2; cc++) sts32(base + OFF_RS + (cc * 128 + tid) * 4, ln_params(v[cc].x, v[cc].y));
        const float cs[3] = {(v[2].x + v[3].x) + (v[4].x + v[5].x), (v[2].y + v[3].y) + (v[4].y + v[5].y),
                             (v[2].z + v[3].z) + (v[4].z + v[5].z)};
#pragma unroll
        for (int blk = 0; blk < 3; blk++) {
          const float t = cs[blk] + __shfl_xor_sync(0xffffffffu, cs[blk], 1);
          cs_put(blk, tid & 1, tid >> 1, (tid & 1) ? 0.f : t);
        }
        fence_proxy_async_smem();
        named_bar_sync(2, 128);
        if (tid < 2) mbar_arrive(bars + 8u * (B_PREP + tid));
        STAMP(KSQ == 0, 48);
      }
    }
#pragma unroll 1
    for (int inst = asst ? 0 : warp >> 2; inst < 8; inst += asst ? 1 : 2) {
      const int L = inst >> 1, ch = inst & 1, gb = ch * 8 + qr;
      if (asst) {
        setmaxnreg_dec<24>();
        if (warp == 8) {
          named_bar_sync(3, 192);
          STA(32);
          if (elect_one()) {
            if ((L & 1) == 0) {
              bulk_store(g_kvA[L >> 1][gb][hp][1], slots + 16384, 16384);
            } else {
              bulk_store(g_kvB[L >> 1][gb][hp], KB_ROW0 + 112 * 128, 2048);
              bulk_store(g_kvB[L >> 1][gb][hp] + 2048, VB_ROW0 + 112 * 128, 2048);
            }
            bulk_commit();
            bulk_wait0();
            fence_proxy_async_all();
            red_relaxed_add(g_flags + F_KV + (gb * 16 + hp) * KSTR, 1u);
            STA(33);
          }
          __syncwarp();
        } else if (warp == 9 && (L & 1) == 0) {
          named_bar_sync(7, 160);
          if (lane0) {
            bulk_store(g_kvA[L >> 1][gb][hp][0], slots, 16384);
            bulk_commit();
          }
          __syncwarp();
        }
        named_bar_sync(4, 256);
        setmaxnreg_inc<128>();
      } else {
      setmaxnreg_inc<224>();
      {
        float acc[2][96];
        const int ksp = q_split(inst);
        int n = q_first(inst);
        uint32_t dlt = (ch == 0 && L > 0) ? 10u * (UNIT >> 4) : 0u;
        if (inst == 1 || (inst > 1 && q_split(inst - 1) != 4)) {
          mbar_wait_lazy<100>(bars + 8u * (B_TURN + ch), tpar);
          tpar ^= 1u;
        }
        if (L == 3) GTL(37);
        mbar_wait(bars + 8u * (B_FULL + (n & 7)), (n >> 3) & 1);
        GTL(1 + L * 8);
        {
          const uint32_t da = (base >> 4) + 0x10000u + dlt;
          const uint64_t db = desc_lo(da - 0x10000u + ((UNIT >> 4) << 16) + 2 * (UNIT >> 4));
          wgmma_fence();
          wgmma_n192_ssz_ta0_tb1(acc[0], desc_lo(da), db);
          wgmma_commit();
          wgmma_n192_ssz_ta0_tb1(acc[1], desc_lo(da + (UNIT >> 4)), db);
          wgmma_commit();
        }
#pragma unroll 1
        for (int k4 = 0; k4 < 4; k4++) {
          const bool brk = k4 + 1 == ksp && k4 < 3;
#pragma unroll
          for (int ks = 0; ks < 4; ks++, n++) {
            if (ks == 2 && k4 == 3) break;
            STAMP(inst == KSQ, k4 * 4 + ks);
            const uint32_t da = ((base + ks * 5 * UNIT) >> 4) + 0x10000u + (ks < 2 ? dlt : 0u - dlt);
            const uint32_t dbb = da - 0x10000u + ((UNIT >> 4) << 16) + 2 * (UNIT >> 4);
#pragma unroll
            for (int k16 = 0; k16 < 4; k16++) {
              if (ks == 0 && k16 == 0 && k4 == 0) continue;
              const uint64_t db = desc_lo(dbb + k16 * 128);
              wgmma_fence();
              wgmma_n192_ss_ta0_tb1(acc[0], desc_lo(da + k16 * 2), db, 1);
              wgmma_commit();
              wgmma_wait<1>();
              if (k16 == 0 && lane0 && (ks != 0 || k4 != ksp)) mbar_arrive(bars + 8u * (B_EMPTY + ((n - 1) & 7)));
              wgmma_fence();
              wgmma_n192_ss_ta0_tb1(acc[1], desc_lo(da + (UNIT >> 4) + k16 * 2), db, 1);
              wgmma_commit();
              bool ok = true;
              if (k16 == 2) ok = mbar_test(bars + 8u * (B_FULL + ((n + 1) & 7)), ((n + 1) >> 3) & 1) || (ks == 3 && brk);
              if (k16 == QTURN && ks == 3 && brk && lane0) mbar_arrive(bars + 8u * (B_TURN + (ch ^ 1)));
              if ((ks & 1) == 0 || k16 < 3) wgmma_wait<1>();
              if (k16 == 2 && !ok) mbar_wait(bars + 8u * (B_FULL + ((n + 1) & 7)), ((n + 1) >> 3) & 1);
            }
          }
          if (brk) {
            wgmma_wait<0>();
            if (lane0) mbar_arrive(bars + 8u * (B_EMPTY + ((n - 1) & 7)));
            n += 16;
            dlt ^= 10u * (UNIT >> 4);
            mbar_wait_lazy<100>(bars + 8u * (B_TURN + ch), tpar);
            tpar ^= 1u;
            STAMP(inst == KSQ, 17);
            mbar_wait(bars + 8u * (B_FULL + (n & 7)), (n >> 3) & 1);
          }
        }
        auto tail_group = [&](int u) {
          const uint32_t da = ((base + (2 + (u & 1)) * 5 * UNIT) >> 4) + 0x10000u - dlt;
          const uint32_t dbb = da - 0x10000u + ((UNIT >> 4) << 16) + 2 * (UNIT >> 4);
          if (u < 3) wgmma_fence();
#pragma unroll
          for (int k16 = 0; k16 < 4; k16++)
            wgmma_n192_ss_ta0_tb1(acc[u < 2], desc_lo(da + (u < 2 ? UNIT >> 4 : 0) + k16 * 2), desc_lo(dbb + k16 * 128), 1);
          wgmma_commit();
        };
        STAMP(inst == KSQ, 14);
        tail_group(0);
        wgmma_wait<1>();
        STAMP(inst == KSQ, 42);
        if (lane0) mbar_arrive(bars + 8u * (B_EMPTY + ((n - 1) & 7)));
        PHASE_IDS
        mbar_wait(bars + 8u * (B_PREP + ch), L & 1);
        STAMP(inst == KSQ, 43);
        uint32_t rs[4];
#pragma unroll
        for (int i = 0; i < 4; i++)
          rs[i] = lds32(base + OFF_RS + (ch * 128 + (i >> 1) * 64 + wwarp * 16 + g + 8 * (i & 1)) * 4);
        auto fold = [&](int h) {
          uint32_t a[2];
#pragma unroll
          for (int r = 0; r < 2; r++) a[r] = c == (L & 1) ? __byte_perm(rs[2 * h + r], 0, 0x1010) ^ 0x80008000u : 0u;
          uint64_t d;
          asm("mov.b64 %0, {%1, %2};" : "=l"(d) : "r"(((base + OFF_CS) >> 4) + ((512 >> 4) << 16)), "r"(0x40000000u));
          wgmma_fence();
          wgmma_n192_rs_tb1(acc[h], a[0], a[1], d);
        };
        fold(1);
        wgmma_commit();
        mbar_wait(bars + 8u * (B_FULL + ((n + 1) & 7)), ((n + 1) >> 3) & 1);
        STAMP(inst == KSQ, 44);
        tail_group(1);
        tail_group(2);
        STAMP(inst == KSQ, 45);
        const bool afree = mbar_test(bars + 8u * (inst == CSI + 1 ? B_CSD : B_AFREE), inst == CSI + 1 ? 0 : inst & 1);
        float rinv[2][2];
#pragma unroll
        for (int i = 0; i < 4; i++) rinv[i >> 1][i & 1] = rcp_fast(bf_hi(rs[i]));
        const int mat = lane >> 3;
        const uint32_t soff = (wwarp * 16 + (mat & 1) * 8 + (lane & 7)) * 128;
        const uint32_t kdst = ((L & 1) ? KB_ROW0 : slots) + soff, vdst = ((L & 1) ? VB_ROW0 : slots + 8192) + soff;
        const uint32_t hs = (L & 1) ? 8192 : 16384;
        const int rg = 2 * wwarp + (mat & 1);
        const uint32_t qdst = slots + 3 * 16384 + ((L & 1) ? soff : ((rg < 4 ? 2 * rg : 15 - 2 * rg) * 8 + (lane & 7)) * 128);
        wgmma_wait<2>();
        STAMP(inst == KSQ, 46);
        fold(0);
        tail_group(3);
        STAMP(inst == KSQ, 47);
        if (EPT < 0 && lane0) mbar_arrive(bars + 8u * (B_TURN + (ch ^ 1)));
        if (!afree) {
          if (EPT >= 0 && lane0) mbar_arrive(bars + 8u * (B_TURN + (ch ^ 1)));
          wgmma_wait<1>();
          if (lane0) mbar_arrive(bars + 8u * (B_EMPTY + (n & 7)));
          wgmma_wait<0>();
          if (lane0) mbar_arrive(bars + 8u * (B_EMPTY + ((n + 1) & 7)));
          mbar_wait(bars + 8u * (inst == CSI + 1 ? B_CSD : B_AFREE), inst == CSI + 1 ? 0 : inst & 1);
        }
        wgmma_wait<2>();
        reg_fence<96>(acc[1]);
        STAMP(inst == KSQ, 15);
#pragma unroll
        for (int t = 0; t < 24; t++) {
          const int h = t < 12 ? 1 : 0, p = (t % 12 / 4 + 1) % 3, jp = t & 3;
          if (t == EPT && lane0 && afree) mbar_arrive(bars + 8u * (B_TURN + (ch ^ 1)));
          if (t == EPW1) {
            wgmma_wait<1>();
            if (lane0 && afree) mbar_arrive(bars + 8u * (B_EMPTY + (n & 7)));
          }
          if (t == EPW0) {
            wgmma_wait<0>();
            reg_fence<96>(acc[0]);
            if (lane0 && afree) mbar_arrive(bars + 8u * (B_EMPTY + ((n + 1) & 7)));
            STAMP(inst == KSQ, 16);
            GTL(2 + L * 8);
          }
          if (t % 12 == 8) {
            rinv[h][0] *= SM_C;
            rinv[h][1] *= SM_C;
          }
          const uint32_t sw = ((2 * jp + (mat >> 1)) ^ (lane & 7)) << 4;
          const float* a = &acc[h][32 * p + 8 * jp];
          const uint32_t dst = p == 0 ? qdst + h * 8192 : (p == 1 ? kdst : vdst) + h * hs;
          stmatrix_x4(dst + sw, pack_bf16x2(a[0] * rinv[h][0], a[1] * rinv[h][0]), pack_bf16x2(a[2] * rinv[h][1], a[3] * rinv[h][1]),
                      pack_bf16x2(a[4] * rinv[h][0], a[5] * rinv[h][0]), pack_bf16x2(a[6] * rinv[h][1], a[7] * rinv[h][1]));
          if (t % 12 == 7) {
            fence_proxy_async_smem();
            if (t == 7) named_bar_arrive(3, 192);
            else if ((L & 1) == 0) named_bar_arrive(7, 160);
            if (t > EPW0) sched_fence(P.zero);
          }
        }
      }
      fence_proxy_async_smem();
      setmaxnreg_dec<128>();
      named_bar_sync(4, 256);
      }
      GTL(3 + L * 8);
      {
        PHASE_IDS
        if ((L & 1) == 0) attention_a(asst, L, gb, hp, inst & 1, ch, (tid_ >> 5) & 3, lane, P.zero);
        else attention_b(asst, gb, inst & 1, wwarp, lane);
        GTL(4 + L * 8);
        fence_proxy_async_smem();
      }
      if (asst) {
        named_bar_arrive(5, 256);
        if (inst == CSI) {
          mbar_wait(bars + 8u * B_AFREE, CSI ^ 1);
          colsum_part(&P.wqkv[1], 1, qr, hp);
          if (lane0) mbar_arrive(bars + 8u * B_CSD);
        }
        continue;
      }
      {
        named_bar_sync(5, 256);
        const int wwarp = warp & 3;
        if (wwarp < 2 && elect_one()) {
          tma_store_3d(&P.o, ((L & 1) ? slots + 3 * 16384 : OA_TILE) + wwarp * 8192, 0, gb * 128 + wwarp * 64, hp);
          bulk_commit();
          bulk_wait0();
          mbar_arrive(bars + 8u * B_AFREE);
          fence_proxy_async_all();
          red_relaxed_add(g_flags + F_O + (gb * 2 + wwarp) * OSTR + hp, 1u);
        }
        __syncwarp();
      }
      GTL(5 + L * 8);

      {
        float acc[64];
        const int n0 = w_first(inst);
        const bool pre = w_pre(inst);
        const uint32_t dl = ch * 10u * (UNIT >> 4);
        mbar_wait_lazy<100>(bars + 8u * (B_TURN + ch), tpar);
        tpar ^= 1u;
        mbar_wait(bars + 8u * (B_FULL + (n0 & 7)), (n0 >> 3) & 1);
        GTL(6 + L * 8);
#pragma unroll
        for (int kt = 0; kt < 16; kt++) {
          const int n = n0 + kt;
          STAMP(inst == KSW, 20 + kt);
          const uint32_t da = ((base + w_ua(kt) * UNIT) >> 4) + 0x10000u + (w_ua(kt) < 10 ? dl : 0u - dl);
          uint32_t db = ((base + w_ub(kt) * UNIT) >> 4) + ((UNIT >> 4) << 16) + (w_ub(kt) < 10 ? dl : 0u - dl);
          if (pre_idx(kt) >= 0 && pre) db = ((slots + pre_idx(kt) * 2 * UNIT) >> 4) + ((UNIT >> 4) << 16);
          if (kt == PRE0 && pre) mbar_wait(bars + 8u * B_PRE, __popc(PREMASK & ((1u << inst) - 1u)) & 1);
          if (kt == 15 && lane0 && (inst >= 6 || q_split(inst + 1) != 4)) mbar_arrive(bars + 8u * (B_TURN + (ch ^ 1)));
          wgmma_fence();
          if (kt == 0) wgmma_n128_ssz_ta0_tb1(acc, desc_lo(da), desc_lo(db));
#pragma unroll
          for (int k16 = kt == 0 ? 1 : 0; k16 < 4; k16++) wgmma_n128_ss_ta0_tb1(acc, desc_lo(da + 2 * k16), desc_lo(db + 128 * k16), 1);
          wgmma_commit();
          const uint32_t nb = bars + 8u * (kt == 15 ? B_RESF : B_FULL + ((n + 1) & 7)), np = kt == 15 ? ch : ((n + 1) >> 3) & 1;
          const bool ok = mbar_test(nb, np);
          if (kt > 0) {
            wgmma_wait<1>();
            if (lane0) mbar_arrive(bars + 8u * (B_EMPTY + ((n - 1) & 7)));
          }
          if (!ok) mbar_wait(nb, np);
        }
        PHASE_IDS
        const uint32_t xb = base + (8 + ch * 10) * UNIT;
        const int mat = lane >> 3;
        const uint32_t xrow = xb + (wwarp * 16 + (mat & 1) * 8 + (lane & 7)) * 128;
        uint32_t xv[8][4];
#pragma unroll
        for (int jp = 0; jp < 8; jp++)
          ldmatrix_x4(xv[jp], xrow + (jp >> 2) * UNIT + (((2 * (jp & 3) + (mat >> 1)) ^ (lane & 7)) << 4));
        wgmma_wait<0>();
        reg_fence<64>(acc);
        if (lane0) mbar_arrive(bars + 8u * (B_EMPTY + ((n0 + 15) & 7)));
        STAMP(inst == KSW, 36);
        GTL(7 + L * 8);
#pragma unroll
        for (int jp = 0; jp < 8; jp++) {
#pragma unroll
          for (int q = 0; q < 4; q++) xv[jp][q] = add_bf16x2(xv[jp][q], pack_bf16x2(acc[8 * jp + 2 * q], acc[8 * jp + 2 * q + 1]));
          stmatrix_x4(xrow + (jp >> 2) * UNIT + (((2 * (jp & 3) + (mat >> 1)) ^ (lane & 7)) << 4), xv[jp][0], xv[jp][1],
                      xv[jp][2], xv[jp][3]);
        }
        fence_proxy_async_smem();
        named_bar_sync(1 + ch, 128);
        const int grow = ch * 1024 + rt * 64;
        if (wwarp == 0) {
          if (elect_one()) {
            tma_store_3d(&P.xr[L == 3 ? 2 : 1], xb, 0, grow, ct * 2);
            bulk_commit();
            bulk_wait_read0();
            mbar_arrive(bars + 8u * B_RESE);
            bulk_wait0();
            TGET(t35);
            fence_proxy_async_all();
            if (L < 3) red_relaxed_add(g_flags + F_X + (ch * 8 + (rt >> 1)) * XSTR + ct, 1u);
            if (L == 2) TPUT(ch, 35, t35);
          }
          __syncwarp();
        } else if (lane == 0) {
          mbar_arrive(bars + 8u * B_RESE);
        }
        if (L < 3) {
          const unsigned ep1 = lds32(base + OFF_EPOCH);
          float s1[2] = {0.f, 0.f}, s2[2] = {0.f, 0.f};
#pragma unroll
          for (int jp = 0; jp < 8; jp++)
#pragma unroll
            for (int q = 0; q < 4; q++) {
              const float x0 = bf_lo(xv[jp][q]), x1 = bf_hi(xv[jp][q]);
              s1[q & 1] += x0 + x1;
              s2[q & 1] = fmaf(x0, x0, fmaf(x1, x1, s2[q & 1]));
            }
#pragma unroll
          for (int r = 0; r < 2; r++) {
            s1[r] += __shfl_xor_sync(0xffffffffu, s1[r], 1);
            s2[r] += __shfl_xor_sync(0xffffffffu, s2[r], 1);
            s1[r] += __shfl_xor_sync(0xffffffffu, s1[r], 2);
            s2[r] += __shfl_xor_sync(0xffffffffu, s2[r], 2);
            if (c == 0) st_rec(&g_stats[L + 1][ct][grow + wwarp * 16 + g + 8 * r], s1[r], s2[r], 0.f, ep1);
          }
        }
        GTL(8 + L * 8);
      }
    }
    if (threadIdx.x == 128) atomicAdd(g_flags + F_DONE, 1u);
  }
}

typedef CUresult (*PFN_tmEncode)(CUtensorMap*, CUtensorMapDataType, cuuint32_t, void*, const cuuint64_t*,
                                 const cuuint64_t*, const cuuint32_t*, const cuuint32_t*, CUtensorMapInterleave,
                                 CUtensorMapSwizzle, CUtensorMapL2promotion, CUtensorMapFloatOOBfill);

PFN_tmEncode get_encode_fn() {
  static PFN_tmEncode fn = nullptr;
  if (!fn) {
    cudaDriverEntryPointQueryResult qr;
    void* p = nullptr;
    cudaGetDriverEntryPoint("cuTensorMapEncodeTiled", &p, cudaEnableDefault, &qr);
    fn = (PFN_tmEncode)p;
  }
  return fn;
}

CUtensorMap make_map(const void* ptr, int rows, int cols, int inner, int box_rows, int box_blk) {
  CUtensorMap m;
  cuuint64_t gdim[3] = {(cuuint64_t)inner, (cuuint64_t)rows, (cuuint64_t)(cols / inner)};
  cuuint64_t gstr[2] = {(cuuint64_t)cols * 2, (cuuint64_t)inner * 2};
  cuuint32_t box[3] = {64, (cuuint32_t)box_rows, (cuuint32_t)box_blk};
  cuuint32_t estr[3] = {1, 1, 1};
  get_encode_fn()(&m, CU_TENSOR_MAP_DATA_TYPE_BFLOAT16, 3, const_cast<void*>(ptr), gdim, gstr, box, estr,
                  CU_TENSOR_MAP_INTERLEAVE_NONE, CU_TENSOR_MAP_SWIZZLE_128B, CU_TENSOR_MAP_L2_PROMOTION_L2_128B,
                  CU_TENSOR_MAP_FLOAT_OOB_FILL_NONE);
  return m;
}

}

extern "C" void kernel_launch(void* const* d_in, const int* in_sizes, int n_in, void* d_out, int out_size) {
  (void)in_sizes; (void)n_in; (void)out_size;
  void *p_o, *p_x;
  cudaGetSymbolAddress(&p_o, g_o);
  cudaGetSymbolAddress(&p_x, g_x);
  static bool attr_done = false;
  if (!attr_done) {
    cudaFuncSetAttribute(fused_kernel, cudaFuncAttributeMaxDynamicSharedMemorySize, SMEM_BYTES);
    attr_done = true;
  }
  Params P;
  P.in_x = (const __nv_bfloat16*)d_in[0];
  P.wqkv_p[0] = (const __nv_bfloat16*)d_in[1];
  P.wo_p[0] = (const __nv_bfloat16*)d_in[2];
  P.wqkv_p[1] = (const __nv_bfloat16*)d_in[4];
  P.wo_p[1] = (const __nv_bfloat16*)d_in[5];
  P.out = (__nv_bfloat16*)d_out;
  P.zero = 0;
  P.xq[0] = make_map(P.in_x, S_LEN, DM, 64, 128, 1);
  P.xq[1] = make_map(p_x, S_LEN, DM, 64, 128, 1);
  P.xr[0] = make_map(P.in_x, S_LEN, DM, 64, 64, 2);
  P.xr[1] = make_map(p_x, S_LEN, DM, 64, 64, 2);
  P.xr[2] = make_map(d_out, S_LEN, DM, 64, 64, 2);
  P.o = make_map(p_o, S_LEN, DM, 64, 64, 1);
  for (int t = 0; t < 2; t++) {
    P.wqkv[t] = make_map(P.wqkv_p[t], DM, NQKV, 1024, 64, 3);
    P.wo[t] = make_map(P.wo_p[t], DM, DM, 64, 64, 2);
  }
  fused_kernel<<<NCTA, 512, SMEM_BYTES>>>(P);
}
```

```cpp
#include <cuda_runtime.h>
#include <cuda_bf16.h>
#include <cuda.h>
#include <stdint.h>

namespace {

constexpr int S_LEN = 2048;
constexpr int DM = 1024;
constexpr int NQKV = 3072;
constexpr int NCTA = 128;

__device__ __align__(1024) uint8_t g_kvA[2][16][16][2][16384];
__device__ __align__(1024) uint8_t g_kvB[2][16][16][4096];
__device__ __align__(1024) uint8_t g_zero[16384];
__device__ __align__(1024) __nv_bfloat16 g_o[S_LEN * DM];
__device__ __align__(1024) __nv_bfloat16 g_x[S_LEN * DM];
__device__ __align__(1024) float4 g_stats[4][8][S_LEN];
__device__ __align__(1024) float4 g_cs[2][16][8][64];
constexpr int F_X = 0;
constexpr int XSTR = 32, OSTR = 32, KSTR = 32;
constexpr int F_O = F_X + 16 * XSTR;
constexpr int F_KV = F_O + 32 * OSTR;
constexpr int F_DONE = F_KV + 256 * KSTR;
__device__ __align__(1024) unsigned g_flags[F_DONE + 32];

constexpr uint32_t SBASE = 1024;
constexpr int UNIT = 8192;
constexpr int NUNITS = 20;
constexpr int OFF_SLOT = NUNITS * UNIT;
constexpr int OFF_CS = OFF_SLOT + 4 * 16384;
constexpr int OFF_RS = OFF_CS + 1536;
constexpr int OFF_BAR = OFF_RS + 1024;
constexpr int OFF_EPOCH = OFF_BAR + 312;
constexpr int OFF_TS = OFF_BAR + 320;
constexpr int SMEM_BYTES = OFF_TS;
constexpr int B_FULL = 0, B_EMPTY = 8, B_PREP = 16, B_HALO = 18, B_REL = 22, B_AFREE = 25, B_TURN = 26, B_XRDY = 28,
              B_CS = 30, B_CSD = 31, B_GO = 32, B_RESF = 33, B_RESE = 34, B_PRE = 35;

__device__ __forceinline__ uint32_t smem_u32(const void* p) { return (uint32_t)__cvta_generic_to_shared(p); }

__device__ __forceinline__ void mbar_init(uint32_t bar, uint32_t cnt) {
  asm volatile("mbarrier.init.shared::cta.b64 [%0], %1;" ::"r"(bar), "r"(cnt));
}
__device__ __forceinline__ void mbar_expect_tx(uint32_t bar, uint32_t bytes) {
  asm volatile("mbarrier.arrive.expect_tx.shared::cta.b64 _, [%0], %1;" ::"r"(bar), "r"(bytes) : "memory");
}
__device__ __forceinline__ void mbar_arrive(uint32_t bar) {
  asm volatile("mbarrier.arrive.shared::cta.b64 _, [%0];" ::"r"(bar) : "memory");
}
__device__ __forceinline__ bool mbar_try_wait(uint32_t bar, uint32_t parity) {
  uint32_t ok;
  asm volatile(
      "{\n.reg .pred p;\nmbarrier.try_wait.parity.shared::cta.b64 p, [%1], %2;\nselp.b32 %0, 1, 0, p;\n}\n"
      : "=r"(ok)
      : "r"(bar), "r"(parity)
      : "memory");
  return ok != 0;
}
__device__ __forceinline__ bool mbar_test(uint32_t bar, uint32_t parity) {
  uint32_t ok;
  asm volatile(
      "{\n.reg .pred p;\nmbarrier.test_wait.parity.shared::cta.b64 p, [%1], %2;\nselp.b32 %0, 1, 0, p;\n}\n"
      : "=r"(ok)
      : "r"(bar), "r"(parity)
      : "memory");
  return ok != 0;
}
__device__ __forceinline__ void mbar_wait(uint32_t bar, uint32_t parity) {
#pragma unroll 1
  for (uint32_t it = 0; it < (1u << 18); ++it) {
    if (mbar_try_wait(bar, parity)) return;
  }
}
__device__ __forceinline__ void mbar_pace(uint32_t bar, uint32_t parity) {
#pragma unroll 1
  for (uint32_t it = 0; it < 24; ++it) {
    if (mbar_try_wait(bar, parity)) return;
  }
}
template <int NS>
__device__ __forceinline__ void mbar_wait_lazy(uint32_t bar, uint32_t parity) {
#pragma unroll 1
  for (uint32_t it = 0; it < (1u << 18); ++it) {
    if (mbar_try_wait(bar, parity)) return;
    __nanosleep(NS);
  }
}
__device__ __forceinline__ bool elect_one() {
  uint32_t ok;
  asm volatile("{\n.reg .pred p;\nelect.sync _|p, 0xffffffff;\nselp.b32 %0, 1, 0, p;\n}\n" : "=r"(ok));
  return ok != 0;
}
__device__ __forceinline__ void fence_barrier_init() { asm volatile("fence.mbarrier_init.release.cluster;" ::: "memory"); }
__device__ __forceinline__ void fence_proxy_async_smem() { asm volatile("fence.proxy.async.shared::cta;" ::: "memory"); }
__device__ __forceinline__ void fence_proxy_async_all() { asm volatile("fence.proxy.async.global;" ::: "memory"); }

__device__ __forceinline__ void tma_load_3d(uint32_t dst, const CUtensorMap* map, uint32_t bar, int c0, int c1, int c2) {
  asm volatile(
      "cp.async.bulk.tensor.3d.shared::cluster.global.mbarrier::complete_tx::bytes [%0], [%1, {%3, %4, %5}], [%2];" ::"r"(dst),
      "l"(map), "r"(bar), "r"(c0), "r"(c1), "r"(c2)
      : "memory");
}
__device__ __forceinline__ void bulk_load(uint32_t dst, const void* src, uint32_t bytes, uint32_t bar) {
  asm volatile("cp.async.bulk.shared::cluster.global.mbarrier::complete_tx::bytes [%0], [%1], %2, [%3];" ::"r"(dst),
               "l"(src), "r"(bytes), "r"(bar)
               : "memory");
}
__device__ __forceinline__ void bulk_store(void* dst, uint32_t src, uint32_t bytes) {
  asm volatile("cp.async.bulk.global.shared::cta.bulk_group [%0], [%1], %2;" ::"l"(dst), "r"(src), "r"(bytes) : "memory");
}
__device__ __forceinline__ void tma_store_3d(const CUtensorMap* map, uint32_t src, int c0, int c1, int c2) {
  asm volatile("cp.async.bulk.tensor.3d.global.shared::cta.bulk_group [%0, {%2, %3, %4}], [%1];" ::"l"(map), "r"(src),
               "r"(c0), "r"(c1), "r"(c2)
               : "memory");
}
__device__ __forceinline__ void bulk_commit() { asm volatile("cp.async.bulk.commit_group;" ::: "memory"); }
__device__ __forceinline__ void bulk_wait_read0() { asm volatile("cp.async.bulk.wait_group.read 0;" ::: "memory"); }
__device__ __forceinline__ void bulk_wait0() { asm volatile("cp.async.bulk.wait_group 0;" ::: "memory"); }
__device__ __forceinline__ void named_bar_sync(int id, int nthreads) {
  asm volatile("bar.sync %0, %1;" ::"r"(id), "r"(nthreads) : "memory");
}
__device__ __forceinline__ void named_bar_arrive(int id, int nthreads) {
  asm volatile("bar.arrive %0, %1;" ::"r"(id), "r"(nthreads) : "memory");
}

__device__ __forceinline__ void wgmma_fence() { asm volatile("wgmma.fence.sync.aligned;\n" ::: "memory"); }
__device__ __forceinline__ void wgmma_commit() { asm volatile("wgmma.commit_group.sync.aligned;\n" ::: "memory"); }
template <int N>
__device__ __forceinline__ void wgmma_wait() {
  asm volatile("wgmma.wait_group.sync.aligned %0;\n" ::"n"(N) : "memory");
}
template <int R>
__device__ __forceinline__ void setmaxnreg_inc() { asm volatile("setmaxnreg.inc.sync.aligned.u32 %0;\n" ::"n"(R)); }
template <int R>
__device__ __forceinline__ void setmaxnreg_dec() { asm volatile("setmaxnreg.dec.sync.aligned.u32 %0;\n" ::"n"(R)); }
template <int N>
__device__ __forceinline__ void reg_fence(float* r) {
#pragma unroll
  for (int i = 0; i < N; i++) asm volatile("" : "+f"(r[i])::"memory");
}

template <int N>
__device__ __forceinline__ void reg_define(float* r) {
#pragma unroll
  for (int i = 0; i < N; i++) r[i] = 0.f;
}

__device__ __forceinline__ uint64_t desc_lo(uint32_t lo) {
  uint64_t d;
  asm("mov.b64 %0, {%1, %2};" : "=l"(d) : "r"(lo), "r"(0x40000040u));
  return d;
}
__device__ __forceinline__ uint64_t make_desc(uint32_t addr, uint32_t lbo_bytes) {
  return desc_lo((addr >> 4) + ((lbo_bytes >> 4) << 16));
}

__device__ __forceinline__ void wgmma_n192_ss_ta0_tb1(float* d, uint64_t descA, uint64_t descB, int scaleD) {
  asm volatile("{\n.reg .pred p;\nsetp.ne.b32 p, %98, 0;\n"
    "wgmma.mma_async.sync.aligned.m64n192k16.f32.bf16.bf16 {%0, %1, %2, %3, %4, %5, %6, %7, %8, %9, %10, %11, %12, %13, %14, %15, %16, %17, %18, %19, %20, %21, %22, %23, %24, %25, %26, %27, %28, %29, %30, %31, %32, %33, %34, %35, %36, %37, %38, %39, %40, %41, %42, %43, %44, %45, %46, %47, %48, %49, %50, %51, %52, %53, %54, %55, %56, %57, %58, %59, %60, %61, %62, %63, %64, %65, %66, %67, %68, %69, %70, %71, %72, %73, %74, %75, %76, %77, %78, %79, %80, %81, %82, %83, %84, %85, %86, %87, %88, %89, %90, %91, %92, %93, %94, %95}, %96, %97, p, 1, 1, 0, 1;\n}\n"
    : "+f"(d[0]), "+f"(d[1]), "+f"(d[2]), "+f"(d[3]), "+f"(d[4]), "+f"(d[5]), "+f"(d[6]), "+f"(d[7]), "+f"(d[8]), "+f"(d[9]), "+f"(d[10]), "+f"(d[11]), "+f"(d[12]), "+f"(d[13]), "+f"(d[14]), "+f"(d[15]), "+f"(d[16]), "+f"(d[17]), "+f"(d[18]), "+f"(d[19]), "+f"(d[20]), "+f"(d[21]), "+f"(d[22]), "+f"(d[23]), "+f"(d[24]), "+f"(d[25]), "+f"(d[26]), "+f"(d[27]), "+f"(d[28]), "+f"(d[29]), "+f"(d[30]), "+f"(d[31]), "+f"(d[32]), "+f"(d[33]), "+f"(d[34]), "+f"(d[35]), "+f"(d[36]), "+f"(d[37]), "+f"(d[38]), "+f"(d[39]), "+f"(d[40]), "+f"(d[41]), "+f"(d[42]), "+f"(d[43]), "+f"(d[44]), "+f"(d[45]), "+f"(d[46]), "+f"(d[47]), "+f"(d[48]), "+f"(d[49]), "+f"(d[50]), "+f"(d[51]), "+f"(d[52]), "+f"(d[53]), "+f"(d[54]), "+f"(d[55]), "+f"(d[56]), "+f"(d[57]), "+f"(d[58]), "+f"(d[59]), "+f"(d[60]), "+f"(d[61]), "+f"(d[62]), "+f"(d[63]), "+f"(d[64]), "+f"(d[65]), "+f"(d[66]), "+f"(d[67]), "+f"(d[68]), "+f"(d[69]), "+f"(d[70]), "+f"(d[71]), "+f"(d[72]), "+f"(d[73]), "+f"(d[74]), "+f"(d[75]), "+f"(d[76]), "+f"(d[77]), "+f"(d[78]), "+f"(d[79]), "+f"(d[80]), "+f"(d[81]), "+f"(d[82]), "+f"(d[83]), "+f"(d[84]), "+f"(d[85]), "+f"(d[86]), "+f"(d[87]), "+f"(d[88]), "+f"(d[89]), "+f"(d[90]), "+f"(d[91]), "+f"(d[92]), "+f"(d[93]), "+f"(d[94]), "+f"(d[95])
    : "l"(descA), "l"(descB), "r"(scaleD));
}

__device__ __forceinline__ void wgmma_n128_ss_ta0_tb1(float* d, uint64_t descA, uint64_t descB, int scaleD) {
  asm volatile("{\n.reg .pred p;\nsetp.ne.b32 p, %66, 0;\n"
    "wgmma.mma_async.sync.aligned.m64n128k16.f32.bf16.bf16 {%0, %1, %2, %3, %4, %5, %6, %7, %8, %9, %10, %11, %12, %13, %14, %15, %16, %17, %18, %19, %20, %21, %22, %23, %24, %25, %26, %27, %28, %29, %30, %31, %32, %33, %34, %35, %36, %37, %38, %39, %40, %41, %42, %43, %44, %45, %46, %47, %48, %49, %50, %51, %52, %53, %54, %55, %56, %57, %58, %59, %60, %61, %62, %63}, %64, %65, p, 1, 1, 0, 1;\n}\n"
    : "+f"(d[0]), "+f"(d[1]), "+f"(d[2]), "+f"(d[3]), "+f"(d[4]), "+f"(d[5]), "+f"(d[6]), "+f"(d[7]), "+f"(d[8]), "+f"(d[9]), "+f"(d[10]), "+f"(d[11]), "+f"(d[12]), "+f"(d[13]), "+f"(d[14]), "+f"(d[15]), "+f"(d[16]), "+f"(d[17]), "+f"(d[18]), "+f"(d[19]), "+f"(d[20]), "+f"(d[21]), "+f"(d[22]), "+f"(d[23]), "+f"(d[24]), "+f"(d[25]), "+f"(d[26]), "+f"(d[27]), "+f"(d[28]), "+f"(d[29]), "+f"(d[30]), "+f"(d[31]), "+f"(d[32]), "+f"(d[33]), "+f"(d[34]), "+f"(d[35]), "+f"(d[36]), "+f"(d[37]), "+f"(d[38]), "+f"(d[39]), "+f"(d[40]), "+f"(d[41]), "+f"(d[42]), "+f"(d[43]), "+f"(d[44]), "+f"(d[45]), "+f"(d[46]), "+f"(d[47]), "+f"(d[48]), "+f"(d[49]), "+f"(d[50]), "+f"(d[51]), "+f"(d[52]), "+f"(d[53]), "+f"(d[54]), "+f"(d[55]), "+f"(d[56]), "+f"(d[57]), "+f"(d[58]), "+f"(d[59]), "+f"(d[60]), "+f"(d[61]), "+f"(d[62]), "+f"(d[63])
    : "l"(descA), "l"(descB), "r"(scaleD));
}

__device__ __forceinline__ void wgmma_n192_ssz_ta0_tb1(float* d, uint64_t descA, uint64_t descB) {
  asm volatile("{\n.reg .pred p;\nsetp.ne.b32 p, 0, 0;\n"
    "wgmma.mma_async.sync.aligned.m64n192k16.f32.bf16.bf16 {%0, %1, %2, %3, %4, %5, %6, %7, %8, %9, %10, %11, %12, %13, %14, %15, %16, %17, %18, %19, %20, %21, %22, %23, %24, %25, %26, %27, %28, %29, %30, %31, %32, %33, %34, %35, %36, %37, %38, %39, %40, %41, %42, %43, %44, %45, %46, %47, %48, %49, %50, %51, %52, %53, %54, %55, %56, %57, %58, %59, %60, %61, %62, %63, %64, %65, %66, %67, %68, %69, %70, %71, %72, %73, %74, %75, %76, %77, %78, %79, %80, %81, %82, %83, %84, %85, %86, %87, %88, %89, %90, %91, %92, %93, %94, %95}, %96, %97, p, 1, 1, 0, 1;\n}\n"
    : "=f"(d[0]), "=f"(d[1]), "=f"(d[2]), "=f"(d[3]), "=f"(d[4]), "=f"(d[5]), "=f"(d[6]), "=f"(d[7]), "=f"(d[8]), "=f"(d[9]), "=f"(d[10]), "=f"(d[11]), "=f"(d[12]), "=f"(d[13]), "=f"(d[14]), "=f"(d[15]), "=f"(d[16]), "=f"(d[17]), "=f"(d[18]), "=f"(d[19]), "=f"(d[20]), "=f"(d[21]), "=f"(d[22]), "=f"(d[23]), "=f"(d[24]), "=f"(d[25]), "=f"(d[26]), "=f"(d[27]), "=f"(d[28]), "=f"(d[29]), "=f"(d[30]), "=f"(d[31]), "=f"(d[32]), "=f"(d[33]), "=f"(d[34]), "=f"(d[35]), "=f"(d[36]), "=f"(d[37]), "=f"(d[38]), "=f"(d[39]), "=f"(d[40]), "=f"(d[41]), "=f"(d[42]), "=f"(d[43]), "=f"(d[44]), "=f"(d[45]), "=f"(d[46]), "=f"(d[47]), "=f"(d[48]), "=f"(d[49]), "=f"(d[50]), "=f"(d[51]), "=f"(d[52]), "=f"(d[53]), "=f"(d[54]), "=f"(d[55]), "=f"(d[56]), "=f"(d[57]), "=f"(d[58]), "=f"(d[59]), "=f"(d[60]), "=f"(d[61]), "=f"(d[62]), "=f"(d[63]), "=f"(d[64]), "=f"(d[65]), "=f"(d[66]), "=f"(d[67]), "=f"(d[68]), "=f"(d[69]), "=f"(d[70]), "=f"(d[71]), "=f"(d[72]), "=f"(d[73]), "=f"(d[74]), "=f"(d[75]), "=f"(d[76]), "=f"(d[77]), "=f"(d[78]), "=f"(d[79]), "=f"(d[80]), "=f"(d[81]), "=f"(d[82]), "=f"(d[83]), "=f"(d[84]), "=f"(d[85]), "=f"(d[86]), "=f"(d[87]), "=f"(d[88]), "=f"(d[89]), "=f"(d[90]), "=f"(d[91]), "=f"(d[92]), "=f"(d[93]), "=f"(d[94]), "=f"(d[95])
    : "l"(descA), "l"(descB));
}

__device__ __forceinline__ void wgmma_n192_rs_tb1(float* d, uint32_t a0, uint32_t a1, uint64_t descB) {
  asm volatile("{\n.reg .pred p;\nsetp.eq.b32 p, 0, 0;\n"
    "wgmma.mma_async.sync.aligned.m64n192k16.f32.bf16.bf16 {%0, %1, %2, %3, %4, %5, %6, %7, %8, %9, %10, %11, %12, %13, %14, %15, %16, %17, %18, %19, %20, %21, %22, %23, %24, %25, %26, %27, %28, %29, %30, %31, %32, %33, %34, %35, %36, %37, %38, %39, %40, %41, %42, %43, %44, %45, %46, %47, %48, %49, %50, %51, %52, %53, %54, %55, %56, %57, %58, %59, %60, %61, %62, %63, %64, %65, %66, %67, %68, %69, %70, %71, %72, %73, %74, %75, %76, %77, %78, %79, %80, %81, %82, %83, %84, %85, %86, %87, %88, %89, %90, %91, %92, %93, %94, %95}, {%96, %97, %98, %98}, %99, p, 1, 1, 1;\n}\n"
    : "+f"(d[0]), "+f"(d[1]), "+f"(d[2]), "+f"(d[3]), "+f"(d[4]), "+f"(d[5]), "+f"(d[6]), "+f"(d[7]), "+f"(d[8]), "+f"(d[9]), "+f"(d[10]), "+f"(d[11]), "+f"(d[12]), "+f"(d[13]), "+f"(d[14]), "+f"(d[15]), "+f"(d[16]), "+f"(d[17]), "+f"(d[18]), "+f"(d[19]), "+f"(d[20]), "+f"(d[21]), "+f"(d[22]), "+f"(d[23]), "+f"(d[24]), "+f"(d[25]), "+f"(d[26]), "+f"(d[27]), "+f"(d[28]), "+f"(d[29]), "+f"(d[30]), "+f"(d[31]), "+f"(d[32]), "+f"(d[33]), "+f"(d[34]), "+f"(d[35]), "+f"(d[36]), "+f"(d[37]), "+f"(d[38]), "+f"(d[39]), "+f"(d[40]), "+f"(d[41]), "+f"(d[42]), "+f"(d[43]), "+f"(d[44]), "+f"(d[45]), "+f"(d[46]), "+f"(d[47]), "+f"(d[48]), "+f"(d[49]), "+f"(d[50]), "+f"(d[51]), "+f"(d[52]), "+f"(d[53]), "+f"(d[54]), "+f"(d[55]), "+f"(d[56]), "+f"(d[57]), "+f"(d[58]), "+f"(d[59]), "+f"(d[60]), "+f"(d[61]), "+f"(d[62]), "+f"(d[63]), "+f"(d[64]), "+f"(d[65]), "+f"(d[66]), "+f"(d[67]), "+f"(d[68]), "+f"(d[69]), "+f"(d[70]), "+f"(d[71]), "+f"(d[72]), "+f"(d[73]), "+f"(d[74]), "+f"(d[75]), "+f"(d[76]), "+f"(d[77]), "+f"(d[78]), "+f"(d[79]), "+f"(d[80]), "+f"(d[81]), "+f"(d[82]), "+f"(d[83]), "+f"(d[84]), "+f"(d[85]), "+f"(d[86]), "+f"(d[87]), "+f"(d[88]), "+f"(d[89]), "+f"(d[90]), "+f"(d[91]), "+f"(d[92]), "+f"(d[93]), "+f"(d[94]), "+f"(d[95])
    : "r"(a0), "r"(a1), "r"(0u), "l"(descB));
}

__device__ __forceinline__ void wgmma_n128_ssz_ta0_tb1(float* d, uint64_t descA, uint64_t descB) {
  asm volatile("{\n.reg .pred p;\nsetp.ne.b32 p, 0, 0;\n"
    "wgmma.mma_async.sync.aligned.m64n128k16.f32.bf16.bf16 {%0, %1, %2, %3, %4, %5, %6, %7, %8, %9, %10, %11, %12, %13, %14, %15, %16, %17, %18, %19, %20, %21, %22, %23, %24, %25, %26, %27, %28, %29, %30, %31, %32, %33, %34, %35, %36, %37, %38, %39, %40, %41, %42, %43, %44, %45, %46, %47, %48, %49, %50, %51, %52, %53, %54, %55, %56, %57, %58, %59, %60, %61, %62, %63}, %64, %65, p, 1, 1, 0, 1;\n}\n"
    : "=f"(d[0]), "=f"(d[1]), "=f"(d[2]), "=f"(d[3]), "=f"(d[4]), "=f"(d[5]), "=f"(d[6]), "=f"(d[7]), "=f"(d[8]), "=f"(d[9]), "=f"(d[10]), "=f"(d[11]), "=f"(d[12]), "=f"(d[13]), "=f"(d[14]), "=f"(d[15]), "=f"(d[16]), "=f"(d[17]), "=f"(d[18]), "=f"(d[19]), "=f"(d[20]), "=f"(d[21]), "=f"(d[22]), "=f"(d[23]), "=f"(d[24]), "=f"(d[25]), "=f"(d[26]), "=f"(d[27]), "=f"(d[28]), "=f"(d[29]), "=f"(d[30]), "=f"(d[31]), "=f"(d[32]), "=f"(d[33]), "=f"(d[34]), "=f"(d[35]), "=f"(d[36]), "=f"(d[37]), "=f"(d[38]), "=f"(d[39]), "=f"(d[40]), "=f"(d[41]), "=f"(d[42]), "=f"(d[43]), "=f"(d[44]), "=f"(d[45]), "=f"(d[46]), "=f"(d[47]), "=f"(d[48]), "=f"(d[49]), "=f"(d[50]), "=f"(d[51]), "=f"(d[52]), "=f"(d[53]), "=f"(d[54]), "=f"(d[55]), "=f"(d[56]), "=f"(d[57]), "=f"(d[58]), "=f"(d[59]), "=f"(d[60]), "=f"(d[61]), "=f"(d[62]), "=f"(d[63])
    : "l"(descA), "l"(descB));
}

__device__ __forceinline__ void wgmma_n64_ss_ta0_tb0(float* d, uint64_t descA, uint64_t descB, int scaleD) {
  asm volatile("{\n.reg .pred p;\nsetp.ne.b32 p, %34, 0;\n"
    "wgmma.mma_async.sync.aligned.m64n64k16.f32.bf16.bf16 {%0, %1, %2, %3, %4, %5, %6, %7, %8, %9, %10, %11, %12, %13, %14, %15, %16, %17, %18, %19, %20, %21, %22, %23, %24, %25, %26, %27, %28, %29, %30, %31}, %32, %33, p, 1, 1, 0, 0;\n}\n"
    : "+f"(d[0]), "+f"(d[1]), "+f"(d[2]), "+f"(d[3]), "+f"(d[4]), "+f"(d[5]), "+f"(d[6]), "+f"(d[7]), "+f"(d[8]), "+f"(d[9]), "+f"(d[10]), "+f"(d[11]), "+f"(d[12]), "+f"(d[13]), "+f"(d[14]), "+f"(d[15]), "+f"(d[16]), "+f"(d[17]), "+f"(d[18]), "+f"(d[19]), "+f"(d[20]), "+f"(d[21]), "+f"(d[22]), "+f"(d[23]), "+f"(d[24]), "+f"(d[25]), "+f"(d[26]), "+f"(d[27]), "+f"(d[28]), "+f"(d[29]), "+f"(d[30]), "+f"(d[31])
    : "l"(descA), "l"(descB), "r"(scaleD));
}

__device__ __forceinline__ void wgmma_n64_ssz_ta0_tb0(float* d, uint64_t descA, uint64_t descB) {
  asm volatile("{\n.reg .pred p;\nsetp.ne.b32 p, 0, 0;\n"
    "wgmma.mma_async.sync.aligned.m64n64k16.f32.bf16.bf16 {%0, %1, %2, %3, %4, %5, %6, %7, %8, %9, %10, %11, %12, %13, %14, %15, %16, %17, %18, %19, %20, %21, %22, %23, %24, %25, %26, %27, %28, %29, %30, %31}, %32, %33, p, 1, 1, 0, 0;\n}\n"
    : "=f"(d[0]), "=f"(d[1]), "=f"(d[2]), "=f"(d[3]), "=f"(d[4]), "=f"(d[5]), "=f"(d[6]), "=f"(d[7]), "=f"(d[8]), "=f"(d[9]), "=f"(d[10]), "=f"(d[11]), "=f"(d[12]), "=f"(d[13]), "=f"(d[14]), "=f"(d[15]), "=f"(d[16]), "=f"(d[17]), "=f"(d[18]), "=f"(d[19]), "=f"(d[20]), "=f"(d[21]), "=f"(d[22]), "=f"(d[23]), "=f"(d[24]), "=f"(d[25]), "=f"(d[26]), "=f"(d[27]), "=f"(d[28]), "=f"(d[29]), "=f"(d[30]), "=f"(d[31])
    : "l"(descA), "l"(descB));
}

__device__ __forceinline__ void wgmma_n80_ss_ta0_tb0(float* d, uint64_t descA, uint64_t descB, int scaleD) {
  asm volatile("{\n.reg .pred p;\nsetp.ne.b32 p, %42, 0;\n"
    "wgmma.mma_async.sync.aligned.m64n80k16.f32.bf16.bf16 {%0, %1, %2, %3, %4, %5, %6, %7, %8, %9, %10, %11, %12, %13, %14, %15, %16, %17, %18, %19, %20, %21, %22, %23, %24, %25, %26, %27, %28, %29, %30, %31, %32, %33, %34, %35, %36, %37, %38, %39}, %40, %41, p, 1, 1, 0, 0;\n}\n"
    : "+f"(d[0]), "+f"(d[1]), "+f"(d[2]), "+f"(d[3]), "+f"(d[4]), "+f"(d[5]), "+f"(d[6]), "+f"(d[7]), "+f"(d[8]), "+f"(d[9]), "+f"(d[10]), "+f"(d[11]), "+f"(d[12]), "+f"(d[13]), "+f"(d[14]), "+f"(d[15]), "+f"(d[16]), "+f"(d[17]), "+f"(d[18]), "+f"(d[19]), "+f"(d[20]), "+f"(d[21]), "+f"(d[22]), "+f"(d[23]), "+f"(d[24]), "+f"(d[25]), "+f"(d[26]), "+f"(d[27]), "+f"(d[28]), "+f"(d[29]), "+f"(d[30]), "+f"(d[31]), "+f"(d[32]), "+f"(d[33]), "+f"(d[34]), "+f"(d[35]), "+f"(d[36]), "+f"(d[37]), "+f"(d[38]), "+f"(d[39])
    : "l"(descA), "l"(descB), "r"(scaleD));
}

__device__ __forceinline__ void wgmma_n32_rs_tb1(float* d, const uint32_t* a, uint64_t descB, int scaleD) {
  asm volatile("{\n.reg .pred p;\nsetp.ne.b32 p, %21, 0;\n"
    "wgmma.mma_async.sync.aligned.m64n32k16.f32.bf16.bf16 {%0, %1, %2, %3, %4, %5, %6, %7, %8, %9, %10, %11, %12, %13, %14, %15}, {%16, %17, %18, %19}, %20, p, 1, 1, 1;\n}\n"
    : "+f"(d[0]), "+f"(d[1]), "+f"(d[2]), "+f"(d[3]), "+f"(d[4]), "+f"(d[5]), "+f"(d[6]), "+f"(d[7]), "+f"(d[8]), "+f"(d[9]), "+f"(d[10]), "+f"(d[11]), "+f"(d[12]), "+f"(d[13]), "+f"(d[14]), "+f"(d[15])
    : "r"(a[0]), "r"(a[1]), "r"(a[2]), "r"(a[3]), "l"(descB), "r"(scaleD));
}

__device__ __forceinline__ uint32_t pack_bf16x2(float lo, float hi) {
  uint32_t r;
  asm("cvt.rn.bf16x2.f32 %0, %1, %2;" : "=r"(r) : "f"(hi), "f"(lo));
  return r;
}
__device__ __forceinline__ float bf_lo(uint32_t p) { return __uint_as_float(p << 16); }
__device__ __forceinline__ float bf_hi(uint32_t p) { return __uint_as_float(p & 0xffff0000u); }
__device__ __forceinline__ float bf16_round(float v) { return __bfloat162float(__float2bfloat16_rn(v)); }
__device__ __forceinline__ float ex2_approx(float x) {
  float r;
  asm("ex2.approx.ftz.f32 %0, %1;" : "=f"(r) : "f"(x));
  return r;
}
__device__ __forceinline__ float rcp_fast(float x) {
  float r;
  asm("rcp.approx.ftz.f32 %0, %1;" : "=f"(r) : "f"(x));
  return r;
}
__device__ __forceinline__ void ldmatrix_x4(uint32_t (&r)[4], uint32_t addr) {
  asm volatile("ldmatrix.sync.aligned.m8n8.x4.shared.b16 {%0,%1,%2,%3}, [%4];"
               : "=r"(r[0]), "=r"(r[1]), "=r"(r[2]), "=r"(r[3])
               : "r"(addr)
               : "memory");
}
__device__ __forceinline__ void stmatrix_x4(uint32_t addr, uint32_t r0, uint32_t r1, uint32_t r2, uint32_t r3) {
  asm volatile("stmatrix.sync.aligned.m8n8.x4.shared.b16 [%0], {%1,%2,%3,%4};" ::"r"(addr), "r"(r0), "r"(r1), "r"(r2),
               "r"(r3));
}
__device__ __forceinline__ uint32_t add_bf16x2(uint32_t a, uint32_t b) {
  uint32_t r;
  asm("add.rn.bf16x2 %0, %1, %2;" : "=r"(r) : "r"(a), "r"(b));
  return r;
}
__device__ __forceinline__ uint4 lds128(uint32_t addr) {
  uint4 v;
  asm volatile("ld.shared.v4.b32 {%0,%1,%2,%3}, [%4];" : "=r"(v.x), "=r"(v.y), "=r"(v.z), "=r"(v.w) : "r"(addr) : "memory");
  return v;
}
__device__ __forceinline__ uint32_t lds32(uint32_t addr) {
  uint32_t v;
  asm volatile("ld.shared.b32 %0, [%1];" : "=r"(v) : "r"(addr) : "memory");
  return v;
}
__device__ __forceinline__ void sts32(uint32_t addr, uint32_t v) {
  asm volatile("st.shared.b32 [%0], %1;" ::"r"(addr), "r"(v) : "memory");
}

__device__ __forceinline__ unsigned ld_acquire_u32(const unsigned* p) {
  unsigned v;
  asm volatile("ld.acquire.gpu.global.u32 %0, [%1];" : "=r"(v) : "l"(p) : "memory");
  return v;
}
__device__ __forceinline__ void red_relaxed_add(unsigned* p, unsigned v) {
  asm volatile("red.relaxed.gpu.global.add.u32 [%0], %1;" ::"l"(p), "r"(v) : "memory");
}
__device__ __forceinline__ void wait_ge(const unsigned* p, unsigned target) {
#pragma unroll 1
  for (uint32_t it = 0; it < (1u << 17); ++it) {
    if ((int)(ld_acquire_u32(p) - target) >= 0) return;
  }
}

__device__ __forceinline__ void wait_ge2(const unsigned* p, unsigned t0, unsigned t1) {
#pragma unroll 1
  for (uint32_t it = 0; it < (1u << 17); ++it) {
    unsigned long long v;
    asm volatile("ld.acquire.gpu.global.u64 %0, [%1];" : "=l"(v) : "l"(p) : "memory");
    if ((int)((unsigned)v - t0) >= 0 && (int)((unsigned)(v >> 32) - t1) >= 0) return;
  }
}

#define PDEPTH 1
#define RELNS 100
#define HDELAY 500
#define PUBPOS 0
#define PGAP 100
template <bool SLOW>
__device__ __forceinline__ void wait_mask(const unsigned* f, int cnt, unsigned target, uint32_t need, uint32_t& seen, int lane) {
  if ((seen & need) == need) return;
  const unsigned* fp = f + (lane & (cnt - 1));
#pragma unroll 1
  for (uint32_t it = 0; it < (1u << 17); ++it) {
    seen = __ballot_sync(0xffffffffu, (int)(ld_acquire_u32(fp) - target) >= 0);
    if ((seen & need) == need) break;
    if (SLOW) __nanosleep(400);
  }
  fence_proxy_async_all();
}
__device__ __forceinline__ void wait_lanes(const unsigned* fp, unsigned target, uint32_t need, uint32_t& seen) {
  if ((seen & need) == need) return;
  unsigned v[PDEPTH];
#pragma unroll
  for (int i = 0; i < PDEPTH; i++) {
    asm volatile("ld.relaxed.gpu.global.u32 %0, [%1];" : "=r"(v[i]) : "l"(fp) : "memory");
    if (i + 1 < PDEPTH) __nanosleep(PGAP);
  }
#pragma unroll 1
  for (uint32_t it = 0; it < (1u << 16); ++it) {
#pragma unroll
    for (int i = 0; i < PDEPTH; i++) {
      seen |= __ballot_sync(0xffffffffu, (int)(v[i] - target) >= 0);
      if ((seen & need) == need) goto done;
      asm volatile("ld.relaxed.gpu.global.u32 %0, [%1];" : "=r"(v[i]) : "l"(fp) : "memory");
    }
  }
done:
  fence_proxy_async_all();
}
__device__ __forceinline__ float4 ld_rec(const float4* p) {
  float4 v;
  asm volatile("ld.relaxed.gpu.global.v4.f32 {%0,%1,%2,%3}, [%4];" : "=f"(v.x), "=f"(v.y), "=f"(v.z), "=f"(v.w) : "l"(p) : "memory");
  return v;
}
__device__ __forceinline__ void st_rec(float4* p, float a, float b, float c, unsigned tag) {
  asm volatile("st.relaxed.gpu.global.v4.f32 [%0], {%1,%2,%3,%4};" ::"l"(p), "f"(a), "f"(b), "f"(c), "f"(__uint_as_float(tag)) : "memory");
}
template <int N>
__device__ __forceinline__ float4 sum_recs(const float4* p, int stride, unsigned tag) {
  float4 s;
#pragma unroll 1
  for (uint32_t it = 0; it < (1u << 17); ++it) {
    float4 v[N];
#pragma unroll
    for (int t = 0; t < N; t++) v[t] = ld_rec(p + t * stride);
    bool ok = true;
    s = make_float4(0.f, 0.f, 0.f, 0.f);
#pragma unroll
    for (int t = 0; t < N; t++) {
      ok &= __float_as_uint(v[t].w) == tag;
      s.x += v[t].x;
      s.y += v[t].y;
      s.z += v[t].z;
    }
    if (ok) break;
    __nanosleep(200);
  }
  return s;
}

__device__ __forceinline__ int fresh_tid() {
  int t;
  asm volatile("mov.u32 %0, %%tid.x;" : "=r"(t));
  return t;
}
#define PHASE_IDS                                  \
  const int tid_ = fresh_tid();                    \
  const int lane = tid_ & 31, wwarp = __shfl_sync(0xffffffffu, (tid_ >> 5) & 3, 0), tid = tid_ & 127; \
  const int g = lane >> 2, c = lane & 3;           \
  (void)tid; (void)g; (void)c; (void)wwarp;

#define STAMPW(cond, i) do { } while (0)
#define STAMP(cond, i) do { } while (0)
#define STA(i) do { } while (0)
#define GTL(i) do { } while (0)
#define GTLX(c, i) do { } while (0)
#define TGET(v) do { } while (0)
#define TPUT(c, i, v) do { } while (0)

constexpr float SM_C = 0.17677669529663687f * 1.4426950408889634f;

constexpr uint32_t OA_TILE = SBASE + OFF_SLOT + 16384;

__device__ __forceinline__ void sched_fence(uint32_t never) {
  asm volatile("{\n.reg .pred p;\nsetp.ne.u32 p, %0, 0;\n@p exit;\n}\n" ::"r"(never) : "memory");
}

template <int K0, int K1>
__device__ __forceinline__ void attn_exp(float (&s)[32]) {
#pragma unroll
  for (int k = K0; k < K1; k++) s[k] = ex2_approx(s[k]);
}
#define ASPL 16
#define ASPM 6
template <int MODE, bool NEXT>
__device__ __forceinline__ void attn_unit(float (&s)[32], float (&sn)[32], float (&o)[16], float (&l)[2], bool valid,
                                          uint32_t vdesc, uint32_t qdesc, uint32_t kdesc, uint32_t tri, int w,
                                          uint32_t hbar, uint32_t hpar, uint32_t rel, uint32_t zero, bool stampon = false) {
  float x[9][2];
  if (MODE == 0) {
    attn_exp<0, ASPL>(s);
  } else {
#pragma unroll
    for (int e = 0; e < 2; e++) {
#pragma unroll
      for (int j = 0; j < 4; j++) x[j][e] = MODE == 1 ? s[4 * j + 2 + e] : s[16 + 4 * j + e];
      x[4][e] = MODE == 1 ? s[e] : s[30 + e];
      x[5][e] = MODE == 1 ? s[18 + e] : s[12 + e];
#pragma unroll
      for (int u = 1; u < 4; u++)
        x[5 + u][e] = MODE == 1 ? (w >= u ? s[4 * u + e] : s[4 * (8 - u) + 2 + e]) : (w >= u ? s[4 * (7 - u) + 2 + e] : s[4 * (u - 1) + e]);
    }
#pragma unroll
    for (int k = 0; k < 2 * ASPM; k++) x[k >> 1][k & 1] = ex2_approx(x[k >> 1][k & 1]);
  }
  sched_fence(zero);
  if (hbar) mbar_wait(hbar, hpar);
  wgmma_wait<0>();
  if (rel) mbar_arrive(rel);
  if (NEXT) {
    wgmma_fence();
    wgmma_n64_ssz_ta0_tb0(sn, desc_lo(qdesc), desc_lo(kdesc));
    wgmma_n64_ss_ta0_tb0(sn, desc_lo(qdesc + 2), desc_lo(kdesc + 2), 1);
    wgmma_commit();
    sched_fence(zero);
  }
  uint32_t p[16];
  if (MODE == 0) {
    attn_exp<ASPL, 32>(s);
#pragma unroll
    for (int k = 0; k < 16; k++) p[k] = pack_bf16x2(s[2 * k], s[2 * k + 1]);
  } else {
#pragma unroll
    for (int k = 2 * ASPM; k < 18; k++) x[k >> 1][k & 1] = ex2_approx(x[k >> 1][k & 1]);
    const uint32_t tm = MODE == 1 ? tri : ~tri;
#pragma unroll
    for (int j = 0; j < 4; j++) {
      p[MODE == 1 ? 2 * j + 1 : 8 + 2 * j] = pack_bf16x2(x[j][0], x[j][1]);
      p[MODE == 1 ? 8 + 2 * j : 2 * j + 1] = 0u;
    }
    p[MODE == 1 ? 0 : 15] = pack_bf16x2(x[4][0], x[4][1]) & (w == 0 ? tm : 0xffffffffu);
    p[MODE == 1 ? 9 : 6] = pack_bf16x2(x[5][0], x[5][1]) & (w == 3 ? tm : 0xffffffffu);
#pragma unroll
    for (int u = 1; u < 4; u++) {
      const uint32_t q = pack_bf16x2(x[5 + u][0], x[5 + u][1]);
      p[MODE == 1 ? 2 * u : 2 * (7 - u) + 1] = q & (w > u ? 0xffffffffu : (w == u ? tm : 0u));
      p[MODE == 1 ? 2 * (8 - u) + 1 : 2 * (u - 1)] = q & (w < u - 1 ? 0xffffffffu : (w == u - 1 ? tm : 0u));
    }
  }
  wgmma_fence();
#pragma unroll
  for (int k = 0; k < 4; k++) wgmma_n32_rs_tb1(o, p + 4 * k, desc_lo(vdesc + k * 128), 1);
  wgmma_commit();
#pragma unroll
  for (int r = 0; r < 2; r++) {
    float t = 0.f;
#pragma unroll
    for (int hf = 0; hf < 2; hf++) {
      if (MODE != 0 && r == MODE - 1 && hf == 2 - MODE) continue;
      const uint32_t* q = p + 8 * hf + r;
      const uint32_t v = add_bf16x2(add_bf16x2(q[0], q[2]), add_bf16x2(q[4], q[6]));
      t = (MODE != 0 && r == MODE - 1) || hf == 0 ? bf_lo(v) + bf_hi(v) : t + (bf_lo(v) + bf_hi(v));
    }
    if (valid) l[r] += t;
  }
  if (NEXT) {
    wgmma_wait<1>();
    reg_fence<32>(sn);
  }
}

__device__ __forceinline__ void attn_a_slow(const uint8_t* __restrict__ kvimg, int L, int gb, int hp,
                                         int hh, int wwarp, int lane) {
  constexpr uint32_t sq = SBASE + OFF_SLOT + 3 * 16384;
  const unsigned ep = (*(volatile unsigned*)(g_flags + F_DONE)) / NCTA;
  wait_ge2(g_flags + F_KV + (gb * 16 + hp) * KSTR, 4u * ep + L + 1u, 2u * ep + (L >> 1) + 1u);
#pragma unroll 1
  for (int t = 0; t < 32; t++) {
    const int row = (t >> 4) * 64 + ((t & 8) ? 7 - wwarp : wwarp) * 8 + (t & 7);
    const int qpos = gb * 128 + row;
    const uint32_t qaddr = sq + ((t >> 4) * 64 + wwarp * 16 + (t & 15)) * 128;
    float mx = -INFINITY, sum = 0.f, acc = 0.f;
#pragma unroll 1
    for (int pass = 0; pass < 2; pass++) {
#pragma unroll 1
      for (int j = 0; j < 8; j++) {
        const int kp = qpos - (lane + 32 * j);
        const uint8_t* kr = kvimg + ((size_t)((kp >> 7) * 16 + hp) * 2 + ((kp >> 6) & 1)) * 16384 + (kp & 63) * 128;
        float d = -INFINITY;
        if (kp >= 0) {
          d = 0.f;
#pragma unroll 1
          for (int q = 0; q < 4; q++) {
            const uint4 kv = __ldcg(reinterpret_cast<const uint4*>(kr + (((hh * 4 + q) ^ (kp & 7)) << 4)));
            const uint4 qv = lds128(qaddr + (((hh * 4 + q) ^ (row & 7)) << 4));
            const uint32_t kw[4] = {kv.x, kv.y, kv.z, kv.w}, qw[4] = {qv.x, qv.y, qv.z, qv.w};
#pragma unroll
            for (int e = 0; e < 4; e++) d = fmaf(bf_lo(kw[e]), bf_lo(qw[e]), fmaf(bf_hi(kw[e]), bf_hi(qw[e]), d));
          }
        }
        if (pass == 0) {
          mx = fmaxf(mx, d);
        } else {
          const float ev = ex2_approx(d - mx);
          sum += ev;
          const float pv = bf16_round(ev);
#pragma unroll 1
          for (int kk = 0; kk < 32; kk++) {
            const float pk = __shfl_sync(0xffffffffu, pv, kk);
            const int k2 = qpos - (kk + 32 * j);
            if (k2 >= 0) {
              const uint8_t* vr = kvimg + ((size_t)((k2 >> 7) * 16 + hp) * 2 + ((k2 >> 6) & 1)) * 16384 + 8192 + (k2 & 63) * 128;
              const unsigned short vv =
                  __ldcg(reinterpret_cast<const unsigned short*>(vr + (((hh * 4 + (lane >> 3)) ^ (k2 & 7)) << 4) + (lane & 7) * 2));
              acc = fmaf(pk, __uint_as_float((uint32_t)vv << 16), acc);
            }
          }
        }
      }
      if (pass == 0) {
#pragma unroll
        for (int o = 16; o > 0; o >>= 1) mx = fmaxf(mx, __shfl_xor_sync(0xffffffffu, mx, o));
      }
    }
#pragma unroll
    for (int o = 16; o > 0; o >>= 1) sum += __shfl_xor_sync(0xffffffffu, sum, o);
    acc *= rcp_fast(sum);
    const float hi = __shfl_down_sync(0xffffffffu, acc, 1);
    __syncwarp();
    if ((lane & 1) == 0)
      sts32(OA_TILE + row * 128 + (((hh * 4 + (lane >> 3)) ^ (row & 7)) << 4) + (lane & 7) * 2, pack_bf16x2(acc, hi));
    __syncwarp();
  }
}

__device__ __forceinline__ void store_o(const float (&o)[16], const float (&inv)[2], uint32_t rowaddr, int hh, int lane) {
  const int mat = lane >> 3, r7 = lane & 7;
#pragma unroll
  for (int jp = 0; jp < 2; jp++)
    stmatrix_x4(rowaddr + (((hh * 4 + 2 * jp + (mat >> 1)) ^ r7) << 4),
                pack_bf16x2(o[8 * jp] * inv[0], o[8 * jp + 1] * inv[0]),
                pack_bf16x2(o[8 * jp + 2] * inv[1], o[8 * jp + 3] * inv[1]),
                pack_bf16x2(o[8 * jp + 4] * inv[0], o[8 * jp + 5] * inv[0]),
                pack_bf16x2(o[8 * jp + 6] * inv[1], o[8 * jp + 7] * inv[1]));
}

__device__ __forceinline__ void attention_a(int HH, int L, int gb, int hp, uint32_t par0, uint32_t parA, int wwarp, int lane,
                                            uint32_t zero) {
  constexpr uint32_t bars = SBASE + OFF_BAR;
  const uint32_t dslot = ((SBASE + OFF_SLOT) >> 4) + 0x10000u + HH * 4;
  const uint32_t dq = dslot + 3 * 1024;
  float sa[32], sb[32], o[2][16], l[2][2];
  auto dch = [&](int n) { return dslot + 1024u * (n % 3 == 0 ? 1 : (n % 3 == 1 ? 0 : 2)); };
  wgmma_fence();
  wgmma_n64_ssz_ta0_tb0(sa, desc_lo(dq + 512), desc_lo(dch(0)));
  wgmma_n64_ss_ta0_tb0(sa, desc_lo(dq + 512 + 2), desc_lo(dch(0) + 2), 1);
  wgmma_commit();
#pragma unroll
  for (int h = 0; h < 2; h++) {
#pragma unroll
    for (int i = 0; i < 16; i++) o[h][i] = 0.f;
    l[h][0] = l[h][1] = 0.f;
  }
  const int dg = (lane >> 2) - 2 * (lane & 3);
  const uint32_t tri = (dg >= 0 ? 0xffffu : 0u) | (dg >= 1 ? 0xffff0000u : 0u);
  const int nmax = 2 * gb + 1;
  wgmma_wait<0>();
  reg_fence<32>(sa);
#define STON false
  auto publish = [&]() {
    if (HH && wwarp == 1 && lane == 0) {
      bulk_wait0();
      fence_proxy_async_all();
      red_relaxed_add(g_flags + F_KV + (gb * 16 + hp) * KSTR + 1, 1u);
    }
    __syncwarp();
  };
#define ATT_STEP(i, MODE)                                                                                            \
  attn_unit<MODE, true>(sa, sb, o[1], l[1], i <= nmax, dch(i) + 512, dq, dch(i + 1), tri, wwarp,                     \
                        i >= 1 ? bars + 8u * (B_HALO + i - 1) : 0u, i == 1 ? par0 : parA, 0u, zero, STON); if (i == 0 && PUBPOS == 0) publish();                \
  attn_unit<MODE, (i < 4)>(sb, sa, o[0], l[0], i + 1 <= nmax, dch(i + 1) + 512, dq + 512, dch(i + 1), tri, wwarp, 0u, \
                           0u, i < 3 && lane == 0 ? bars + 8u * (B_REL + i) : 0u, zero);
  ATT_STEP(0, 1)
  if (PUBPOS == 1) publish();
  ATT_STEP(1, 0)
  ATT_STEP(2, 0)
  ATT_STEP(3, 0)
  ATT_STEP(4, 2)
#undef ATT_STEP
  const uint32_t ra = OA_TILE + (((lane & 8) ? 7 - wwarp : wwarp) * 8 + (lane & 7)) * 128;
  bool bad = false;
#pragma unroll
  for (int h = 1; h >= 0; h--) {
    float inv[2];
#pragma unroll
    for (int r = 0; r < 2; r++) {
      float v = l[h][r];
      v += __shfl_xor_sync(0xffffffffu, v, 1);
      v += __shfl_xor_sync(0xffffffffu, v, 2);
      bad |= !(v <= 1.152921504606846976e18f && v >= 8.673617379884035e-19f);
      inv[r] = rcp_fast(v);
    }
    if (h == 0) wgmma_wait<0>();
    reg_fence<16>(o[h]);
    store_o(o[h], inv, ra + h * 8192, HH, lane);
  }
  if (HH == 0) GTL(45);
  if (__any_sync(0xffffffffu, bad)) attn_a_slow(g_kvA[L >> 1][0][0][0], L, gb, hp, HH, wwarp, lane);
}

constexpr uint32_t KB_ROW0 = SBASE + OFF_SLOT + 2048, VB_ROW0 = SBASE + OFF_SLOT + 24576 + 2048;

__device__ __forceinline__ void attnB_soft(const float (&s)[40], int wwarp, int D, bool edge, bool odd,
                                           uint32_t (&p)[5][4], float (&sum)[2]) {
  float z[2][3];
#define GATHER_(W)                                                                                  \
  _Pragma("unroll") for (int r = 0; r < 2; r++) _Pragma("unroll") for (int t = 0; t < 3; t++)       \
      z[r][t] = odd ? s[4 * (2 * W + r + t) + 2 * r + 1] : s[4 * (2 * W + r + t) + 2 * r];
  if (wwarp < 2) {
    if (wwarp == 0) { GATHER_(0) } else { GATHER_(1) }
  } else {
    if (wwarp == 2) { GATHER_(2) } else { GATHER_(3) }
  }
#undef GATHER_
  float y[2];
  y[0] = D >= 2 ? z[0][0] : z[0][2];
  y[1] = D >= 2 ? z[1][0] : z[1][2];
  if (edge) {
    z[0][1] = -INFINITY;
    if (D >= 2) y[0] = y[1] = -INFINITY;
  }
  float m0 = fmaxf(z[0][1], y[0]), m1 = fmaxf(z[1][1], y[1]);
  m0 = fmaxf(m0, __shfl_xor_sync(0xffffffffu, m0, 1));
  m1 = fmaxf(m1, __shfl_xor_sync(0xffffffffu, m1, 1));
  m0 = fmaxf(m0, __shfl_xor_sync(0xffffffffu, m0, 2));
  m1 = fmaxf(m1, __shfl_xor_sync(0xffffffffu, m1, 2));
  const float e00 = ex2_approx(z[0][1] - m0), e01 = ex2_approx(y[0] - m0);
  const float e10 = ex2_approx(z[1][1] - m1), e11 = ex2_approx(y[1] - m1);
  sum[0] = e00 + e01;
  sum[1] = e10 + e11;
  const int sh = odd ? 16 : 0;
  const uint32_t a0 = pack_bf16x2(e00, 0.f) << sh, a1 = pack_bf16x2(e10, 0.f) << sh;
  const uint32_t b0 = pack_bf16x2(e01, 0.f) << sh, b1 = pack_bf16x2(e11, 0.f) << sh;
  const int kb = wwarp + (D >= 2 ? 0 : 1);
#pragma unroll
  for (int k = 0; k < 5; k++) {
    p[k][0] = k == kb ? b0 : 0u;
    p[k][1] = k == wwarp + 1 ? a1 : 0u;
    p[k][2] = k == wwarp ? a0 : 0u;
    p[k][3] = k == kb ? b1 : 0u;
#pragma unroll
    for (int q = 0; q < 4; q++) asm volatile("" : "+r"(p[k][q]));
  }
}

__device__ __forceinline__ void attnB_s(float (&s)[40], int HH, int h) {
  constexpr uint32_t sq = SBASE + OFF_SLOT + 3 * 16384;
#pragma unroll
  for (int ks = 0; ks < 2; ks++)
    wgmma_n80_ss_ta0_tb0(s, make_desc(sq + h * 8192 + HH * 64 + ks * 32, 16),
                         make_desc(KB_ROW0 + h * 8192 - 2048 + HH * 64 + ks * 32, 16), ks);
}
__device__ __forceinline__ void attnB_pv(float (&o)[16], const uint32_t (&p)[5][4], int HH, int h) {
#pragma unroll
  for (int k = 0; k < 5; k++)
    wgmma_n32_rs_tb1(o, p[k], make_desc(VB_ROW0 + h * 8192 - 2048 + k * 2048 + HH * 64, 16), k);
}

__device__ __forceinline__ void attention_b(int HH, int gb, uint32_t par0, int wwarp, int lane) {
  constexpr uint32_t bars = SBASE + OFF_BAR, sq = SBASE + OFF_SLOT + 3 * 16384;
  float s[40];
  reg_define<40>(s);
  wgmma_fence();
  attnB_s(s, HH, 1);
  wgmma_commit();
  const int g = lane >> 2;
  const bool odd = g & 1;
  const int D = 2 * (lane & 3) + (g & 1) - g;
  const uint32_t ra = sq + (wwarp * 16 + ((lane >> 3) & 1) * 8 + (lane & 7)) * 128;
  wgmma_wait<0>();
  reg_fence<40>(s);
#pragma unroll 1
  for (int h = 1; h >= 0; h--) {
    float o[16], inv[2];
    uint32_t p[5][4];
    reg_define<16>(o);
    attnB_soft(s, wwarp, D, h == 0 && gb == 0 && wwarp == 0, odd, p, inv);
    if (h == 1) {
      mbar_wait(bars + 8u * B_HALO, par0);
      wgmma_fence();
      attnB_s(s, HH, 0);
    }
    wgmma_fence();
    attnB_pv(o, p, HH, h);
    wgmma_commit();
#pragma unroll
    for (int r = 0; r < 2; r++) {
      inv[r] += __shfl_xor_sync(0xffffffffu, inv[r], 1);
      inv[r] += __shfl_xor_sync(0xffffffffu, inv[r], 2);
      inv[r] = rcp_fast(inv[r]);
    }
    wgmma_wait<0>();
    reg_fence<40>(s);
    reg_fence<16>(o);
    store_o(o, inv, ra + h * 8192, HH, lane);
  }
}

#define KTQM 0
#define TRICKLE 300
#define CSI 0
#define PCA 1
#define PCB 3
#define PXB 4
#define EPT -1
#define EPW1 4
#define EPW0 12
#define QTURN 2
struct Params {
  CUtensorMap xq[2], xr[3], o, wqkv[2], wo[2];
  const __nv_bfloat16* in_x;
  const __nv_bfloat16* wqkv_p[2];
  const __nv_bfloat16* wo_p[2];
  __nv_bfloat16* out;
  uint32_t zero;
};

__device__ __forceinline__ void colsum_part(const CUtensorMap* wmap, int ty, int qr, int hp) {
  constexpr uint32_t bars = SBASE + OFF_BAR, slots = SBASE + OFF_SLOT;
  PHASE_IDS
  const unsigned ep1 = (*(volatile unsigned*)(g_flags + F_DONE)) / NCTA + 1u;
  if (wwarp == 0 && elect_one()) {
    mbar_expect_tx(bars + 8u * B_CS, 6 * UNIT);
#pragma unroll 1
    for (int j = 0; j < 2; j++) {
      if (ty == 0) mbar_pace(bars + 8u * (B_EMPTY + PCA + PCB * j), 0);
      else __nanosleep(1000);
      tma_load_3d(slots + j * 3 * UNIT, wmap, bars + 8u * B_CS, hp * 64, qr * 128 + j * 64, 0);
    }
  }
  mbar_wait(bars + 8u * B_CS, ty);
  const uint32_t src = slots + (tid >> 3) * 128 + (((tid & 7) ^ ((tid >> 3) & 7)) << 4);
#pragma unroll 1
  for (int p = 0; p < 3; p++) {
    float s[8];
#pragma unroll
    for (int e = 0; e < 8; e++) s[e] = 0.f;
#pragma unroll
    for (int j = 0; j < 8; j++) {
      const uint4 v = lds128(src + p * UNIT + (j >> 2) * 3 * UNIT + (j & 3) * 2048);
      const uint32_t x[4] = {v.x, v.y, v.z, v.w};
#pragma unroll
      for (int e = 0; e < 4; e++) {
        s[2 * e] += bf_lo(x[e]);
        s[2 * e + 1] += bf_hi(x[e]);
      }
    }
#pragma unroll
    for (int st = 0; st < 2; st++) {
      const bool up = (lane >> (st + 3)) & 1;
#pragma unroll
      for (int e = 0; e < (4 >> st); e++) {
        const float keep = up ? s[e + (4 >> st)] : s[e], give = up ? s[e] : s[e + (4 >> st)];
        s[e] = keep + __shfl_xor_sync(0xffffffffu, give, 8 << st);
      }
    }
    const uint32_t dst = slots + 6 * UNIT + ((wwarp * 3 + p) * 64 + (lane & 7) * 8 + ((lane >> 3) & 1) * 4 + (lane >> 4) * 2) * 4;
    sts32(dst, __float_as_uint(s[0]));
    sts32(dst + 4, __float_as_uint(s[1]));
  }
  named_bar_sync(6, 128);
  if (tid < 64) {
    float r[3] = {0.f, 0.f, 0.f};
#pragma unroll
    for (int e = 0; e < 12; e++) r[e % 3] += __uint_as_float(lds32(slots + 6 * UNIT + (e * 64 + tid) * 4));
    st_rec(&g_cs[ty][hp][qr][tid], r[0], r[1], r[2], ep1);
  }
  named_bar_sync(6, 128);
}

__device__ __forceinline__ void cs_put(int blk, int ty, int col, float v) {
  const uint32_t hi = pack_bf16x2(v, 0.f), lo = pack_bf16x2(v - bf_lo(hi), 0.f);
  const uint32_t a = SBASE + OFF_CS + blk * 512 + ty * 256 + col * 2;
  asm volatile("st.shared.b16 [%0], %1;" ::"r"(a ^ (((a >> 7) & 7) << 4)), "h"((unsigned short)hi) : "memory");
  asm volatile("st.shared.b16 [%0], %1;" ::"r"((a + 128) ^ ((((a >> 7) + 1) & 7) << 4)), "h"((unsigned short)lo) : "memory");
}

__device__ __forceinline__ uint32_t ln_params(float s1, float s2) {
  const float mean = s1 * (1.0f / DM);
  const float var = fmaxf(fmaf(-mean, mean, s2 * (1.0f / DM)), 0.f);
  float sd;
  asm("sqrt.approx.f32 %0, %1;" : "=f"(sd) : "f"(bf16_round(bf16_round(var) + 1e-5f)));
  return pack_bf16x2(mean, sd);
}

__host__ __device__ constexpr int w_ua(int kt) { return (kt == 6 ? 20 : 3 * kt) % 20; }
__host__ __device__ constexpr int w_ub(int kt) { return (kt == 6 ? 18 : 3 * kt + 1) % 20; }

#define SPLITS 0x043333334ull
__device__ __forceinline__ int q_split(int inst) { return (int)((SPLITS >> (4 * inst)) & 15ull); }
__device__ __forceinline__ int q_first(int inst) { return inst == 0 ? 0 : 32 * inst - 16; }
__device__ __forceinline__ int w_first(int inst) { return 32 * inst + 16 + 4 * q_split(inst + 1); }
#define PREMASK 0x3Eu
__device__ __forceinline__ bool w_pre(int inst) { return (PREMASK >> inst) & 1u; }
__host__ __device__ constexpr bool p_buf(int kt) { return (kt & 1) == 0 || kt == 15; }
__host__ __device__ constexpr int p_ua(int kt) { return (2 * kt - (kt & 1)) % 20; }
__host__ __device__ constexpr int p_ub(int kt) { return p_buf(kt) ? NUNITS + 2 * (((kt + 1) >> 1) & 3) : (2 * kt) % 20; }
__host__ __device__ constexpr int p_wait(int kt, bool act) {
  const int sp = kt >= 10 ? -8 : (act ? p_ua(kt) : p_ub(kt) + 1) / 5 - 4;
  return !act && kt == 15 ? 8 : ((!act && p_buf(kt)) || kt - 8 > sp ? kt - 8 : sp);
}
__device__ __forceinline__ uint32_t unit_off(int u, uint32_t dl) { return u * UNIT + (u < 10 ? dl : (u < 20 ? 0u - dl : 0u)); }

__global__ void __launch_bounds__(512, 1) fused_kernel(const __grid_constant__ Params P) {
  extern __shared__ __align__(1024) uint8_t smem_raw[];
  constexpr uint32_t base = SBASE, bars = base + OFF_BAR, slots = base + OFF_SLOT;
  if (smem_u32(smem_raw) != base) __trap();
  const int warp = __shfl_sync(0xffffffffu, threadIdx.x >> 5, 0), lane = threadIdx.x & 31;
  const int b = blockIdx.x;
#define QS 0
#define WS 1
  const int qr = ((b & ((8 << QS) - 1)) >> QS) ^ (((b >> (3 + QS)) & 1) * 7);
  const int hp = ((b >> (3 + QS)) << QS) + (b & ((1 << QS) - 1));
  const int rt = ((b & ((16 << WS) - 1)) >> WS) ^ (((b >> (4 + WS)) & 1) * 15);
  const int ct = ((b >> (4 + WS)) << WS) + (b & ((1 << WS) - 1));

  if (warp == 12) {
    if (elect_one()) {
#pragma unroll
      for (int s = 0; s < 8; s++) {
        mbar_init(bars + 8u * (B_FULL + s), 2);
        mbar_init(bars + 8u * (B_EMPTY + s), 4);
      }
      mbar_init(bars + 8u * B_GO, 1);
      fence_barrier_init();
    }
    __syncwarp();
    named_bar_arrive(0, 512);
  }
  if (threadIdx.x == 0) {
    mbar_init(bars + 8u * B_PREP, 1);
    mbar_init(bars + 8u * (B_PREP + 1), 1);
    for (int s = 0; s < 4; s++) mbar_init(bars + 8u * (B_HALO + s), 1);
    for (int s = 0; s < 3; s++) mbar_init(bars + 8u * (B_REL + s), 8);
    mbar_init(bars + 8u * B_AFREE, 2);
    mbar_init(bars + 8u * B_TURN, 4);
    mbar_init(bars + 8u * (B_TURN + 1), 4);
    mbar_init(bars + 8u * B_CS, 1);
    for (int s = 0; s < 4; s++) mbar_init(bars + 8u * (B_PRE + s), 1);
    mbar_init(bars + 8u * B_RESF, 1);
    mbar_init(bars + 8u * B_RESE, 4);
    mbar_init(bars + 8u * B_CSD, 4);
    mbar_init(bars + 8u * B_XRDY, 1);
    mbar_init(bars + 8u * (B_XRDY + 1), 1);
    fence_barrier_init();
  }
  if (warp != 12) named_bar_sync(0, 512);

  if (warp >= 12) {
    setmaxnreg_dec<32>();
    if (warp <= 13) {
      const bool act = warp == 13;
      uint32_t q = 4, dl = 0;
      bool prevw = false;
      uint32_t back = 0x1234u;
      unsigned ep1 = 0;
      if (act) {
        mbar_wait(bars + 8u * B_GO, 0);
        ep1 = __shfl_sync(0xffffffffu, (*(volatile unsigned*)(g_flags + F_DONE)) / NCTA + 1u, 0);
      } else {
#pragma unroll 1
        for (int s = 0; s < 16; s++) {
          const uint32_t fb = bars + 8u * (B_FULL + (s & 7)), sa = base + (s & 3) * 5 * UNIT;
          if (s >= 4) mbar_wait(bars + 8u * (B_EMPTY + ((s - 4) & 7)), ((s - 4) >> 3) & 1);
          if (elect_one()) {
            mbar_expect_tx(fb, 5 * UNIT);
            mbar_arrive(fb);
            tma_load_3d(sa, &P.xq[0], fb, 0, qr * 128, s);
            tma_load_3d(sa + 2 * UNIT, &P.wqkv[0], fb, hp * 64, s * 64, 0);
          }
        }
        if (elect_one()) mbar_arrive(bars + 8u * B_GO);
      }
      auto rbar = [&](int b0, int c) { return bars + 8u * b0 + ((8u * (c & 7)) ^ ((q & 1u) << 5)); };
      auto rpar = [&](int c) { return ((q + (c >> 2)) >> 1) & 1u; };
#pragma unroll 1
      for (int sg = 4; sg < 34; sg++) {
        const int part = sg & 3, si = (sg >> 2) - (part & 1), L = si >> 1, ch = si & 1;
        const int k0 = part == 0 ? 0 : 4 * q_split(si), k1 = part == 0 ? 4 * q_split(si) : 16;
        if (part == 3 || (part != 1 && k0 == k1)) continue;
        uint32_t seen = act ? 0u : 0xFFFFu;
        if (part != 1) {
          const CUtensorMap* map = act ? &P.xq[L == 0 ? 0 : 1] : &P.wqkv[L & 1];
          if (act && (L == 0 || __any_sync(0xffffffffu, mbar_test(bars + 8u * (B_XRDY + ch), (L & 1) ^ 1)))) {
            seen = 0xFFFFu;
            fence_proxy_async_all();
          }
#pragma unroll 1
          for (int k4 = k0; k4 < k1; k4 += 4, q++) {
#pragma unroll
            for (int ks = 0; ks < 4; ks++) {
              const int kt = k4 + ks;
              if ((ks & 1) == 0)
                wait_mask<false>(g_flags + F_X + (ch * 8 + qr) * XSTR, 8, 6u * ep1 - 6u + 2u * L, 1u << (kt >> 1), seen, lane);
              const uint32_t nw = 4u * q - ((back >> (4 * ks)) & 15u);
              mbar_wait(bars + 8u * (B_EMPTY + (nw & 7u)), (nw >> 3) & 1u);
              if (ks == 3 && prevw && !act) mbar_wait(bars + 8u * B_RESE, dl == 0 ? 1u : 0u);
              if (elect_one()) {
                mbar_expect_tx(rbar(B_FULL, ks), act ? 2 * UNIT : 3 * UNIT);
                tma_load_3d(base + ks * 5 * UNIT + (act ? 0 : 2 * UNIT) + (ks < 2 ? dl : 0u - dl), map, rbar(B_FULL, ks),
                            act ? 0 : hp * 64, act ? ch * 1024 + qr * 128 : kt * 64, act ? kt : 0);
              }
            }
            prevw = false;
            back = 0x1234u;
          }
        } else {
          const CUtensorMap* map = act ? &P.o : &P.wo[L & 1];
          const bool pre = w_pre(si);
          const int m0 = ch * 1024 + rt * 64;
          const unsigned* of = g_flags + F_O + (ch * 16 + rt) * OSTR;
          auto wstep = [&](int kt, int ua, int ub) {
            if (elect_one()) {
              mbar_expect_tx(rbar(B_FULL, kt), act ? UNIT : 2 * UNIT);
              tma_load_3d(base + (act ? unit_off(ua, dl) : unit_off(ub, dl)), map, rbar(B_FULL, kt), 0, act ? m0 : kt * 64,
                          act ? kt : ct * 2);
            }
          };
          auto owait = [&](int kt) {
            if (kt == 0 || kt == 1 || kt == 4 || kt == 8)
              wait_mask<false>(of, 16, 4u * ep1 - 3u + L, kt == 0 ? 1u : (kt == 1 ? 0xEu : (kt == 4 ? 0xF0u : 0xFF00u)), seen, lane);
          };
          if (pre && act) {
            const uint32_t ppar = __popc(PREMASK & ((1u << si) - 1u)) & 1;
#pragma unroll
            for (int kt = 0; kt < 16; kt++) {
              owait(kt);
              if (kt == 0 || p_wait(kt, true) != p_wait(kt - 1, true)) mbar_wait(rbar(B_EMPTY, p_wait(kt, true)), rpar(p_wait(kt, true)));
              wstep(kt, p_ua(kt), p_ub(kt));
              if (kt < 8 && p_buf(kt)) {
                mbar_wait(bars + 8u * (B_PRE + (kt >> 1)), ppar);
                if (elect_one()) mbar_arrive(rbar(B_FULL, kt));
              }
            }
            mbar_wait(rbar(B_EMPTY, 10), rpar(10));
          } else if (pre) {
#pragma unroll
            for (int kt = 1; kt < 16; kt += kt < 7 ? 2 : 1) {
              mbar_wait(rbar(B_EMPTY, p_wait(kt, false)), rpar(p_wait(kt, false)));
              wstep(kt, p_ua(kt), p_ub(kt));
            }
          } else {
#pragma unroll
            for (int kt = 0; kt < 16; kt++) {
              owait(kt);
              if (kt < 4 && !prevw) mbar_wait(rbar(B_EMPTY, kt - 4 - (kt >> 1)), rpar(-4));
              else mbar_wait(rbar(B_EMPTY, kt - 6), rpar(kt - 6));
              if (kt == 6 && prevw && !act) mbar_wait(bars + 8u * B_RESE, dl == 0 ? 1u : 0u);
              wstep(kt, w_ua(kt), w_ub(kt));
            }
          }
          if (act && elect_one()) {
            mbar_expect_tx(bars + 8u * B_RESF, 2 * UNIT);
            tma_load_3d(pre ? slots + 2 * UNIT : base + 8 * UNIT + dl, &P.xr[L == 0 ? 0 : 1], bars + 8u * B_RESF, 0, m0, ct * 2);
          }
          q += 4;
          dl ^= 10u * UNIT;
          prevw = !pre;
          back = pre ? (act ? 0x3578u : 0x1478u) : 0x1235u;
        }
      }
    } else if (warp == 14) {
      const unsigned ep1 = (*(volatile unsigned*)(g_flags + F_DONE)) / NCTA + 1u;
#pragma unroll 1
      for (int inst = 0; inst < 8; inst++) {
        const int L = inst >> 1, ch = inst & 1, gb = ch * 8 + qr;
        const unsigned* fp = g_flags + F_KV + (max(gb - 1 - ((lane >> 1) & 1), 0) * 16 + hp) * KSTR + (lane & 1);
        const unsigned target = (lane & 1) ? 2u * ep1 - 1u + (L >> 1) : 4u * ep1 - 3u + L;
        uint32_t seen = gb == 0 ? 15u : (gb == 1 ? 12u : 0u);
        named_bar_sync(3, 192);
        STA(34);
        __nanosleep(HDELAY);
        if ((L & 1) == 0) {
#pragma unroll 1
          for (int i = 0; i < 4; i++) {
            wait_lanes(fp, target, 1u << i, seen);
            STA(36 + i);
            if (i > 0) mbar_wait_lazy<RELNS>(bars + 8u * (B_REL + i - 1), ch);
            if (elect_one()) {
              mbar_expect_tx(bars + 8u * (B_HALO + i), 16384);
              bulk_load(slots + (i == 3 ? 2 : 2 - i) * 16384, gb > (i >> 1) ? g_kvA[L >> 1][gb - 1 - (i >> 1)][hp][(i & 1) ^ 1] : g_zero,
                        16384, bars + 8u * (B_HALO + i));
            }
          }
        } else {
          wait_lanes(fp, target, 1u, seen);
        }
        if (elect_one()) {
          if (L & 1) {
            const uint8_t* s1 = gb >= 1 ? g_kvB[L >> 1][gb - 1][hp] : g_zero;
            mbar_expect_tx(bars + 8u * B_HALO, 4096);
            bulk_load(KB_ROW0 - 2048, s1, 2048, bars + 8u * B_HALO);
            bulk_load(VB_ROW0 - 2048, s1 + 2048, 2048, bars + 8u * B_HALO);
          }
          if (w_pre(inst)) {
            mbar_wait(bars + 8u * B_AFREE, (inst & 1) ^ 1);
            if (inst == CSI) mbar_wait(bars + 8u * B_CSD, 0);
#pragma unroll 1
            for (int j = 0; j < 4; j++) {
              mbar_expect_tx(bars + 8u * (B_PRE + j), 2 * UNIT);
              tma_load_3d(slots + j * 2 * UNIT, &P.wo[L & 1], bars + 8u * (B_PRE + j), 0, j * 128, ct * 2);
              if (L & 1) __nanosleep(200);
            }
          }
        }
        __syncwarp();
      }
    } else {
      const unsigned ep1 = (*(volatile unsigned*)(g_flags + F_DONE)) / NCTA + 1u;
      mbar_wait(bars + 8u * B_GO, 0);
#pragma unroll 1
      for (int i = 0; i < 20; i++) {
        const char* src = i < 4 ? reinterpret_cast<const char*>(P.wo_p[0]) + (size_t)b * 16384 + i * 4096
                                : (i < 16 ? reinterpret_cast<const char*>(P.wqkv_p[1]) + (size_t)b * 49152 + (i - 4) * 4096
                                          : reinterpret_cast<const char*>(P.wo_p[1]) + (size_t)b * 16384 + (i - 16) * 4096);
        asm volatile("prefetch.global.L2 [%0];" ::"l"(src + lane * 128));
        __nanosleep(TRICKLE);
      }
#pragma unroll 1
      for (int inst = 2; inst < 8; inst++) {
        const int L = inst >> 1, ch = inst & 1, gb = ch * 8 + qr;
        uint32_t seen = 0;
        wait_mask<true>(g_flags + F_X + gb * XSTR, 8, 6u * ep1 - 6u + 2u * L, 0xFFu, seen, lane);
        if (lane == 0) mbar_arrive(bars + 8u * (B_XRDY + ch));
#pragma unroll 1
        for (int h = 0; h < 4; h++) {
          const float4* sp = &g_stats[L][0][gb * 128 + h * 32 + lane];
          const float4 s0 = sum_recs<4>(sp, S_LEN, ep1), s1 = sum_recs<4>(sp + 4 * S_LEN, S_LEN, ep1);
          sts32(base + OFF_RS + (ch * 128 + h * 32 + lane) * 4, ln_params(s0.x + s1.x, s0.y + s1.y));
        }
        if (inst == 2) {
          mbar_wait(bars + 8u * B_CSD, 0);
#pragma unroll 1
          for (int hf = 0; hf < 2; hf++) {
            const float4* cp = &g_cs[1][hp][0][hf * 32 + lane];
            const float4 s0 = sum_recs<4>(cp, 64, ep1), s1 = sum_recs<4>(cp + 4 * 64, 64, ep1);
            cs_put(0, 1, hf * 32 + lane, s0.x + s1.x);
            cs_put(1, 1, hf * 32 + lane, s0.y + s1.y);
            cs_put(2, 1, hf * 32 + lane, s0.z + s1.z);
          }
          fence_proxy_async_smem();
        }
        __syncwarp();
        if (lane == 0) mbar_arrive(bars + 8u * (B_PREP + ch));
      }
    }
  } else {
    const bool asst = warp >= 8;
    const bool lane0 = lane == 0;
    uint32_t tpar = 0;
    GTL(0);
    if (asst) {
      colsum_part(&P.wqkv[0], 0, qr, hp);
      if ((threadIdx.x & 127) < 2) mbar_arrive(bars + 8u * B_AFREE);
    } else if (warp >= 4) {
      PHASE_IDS
      {
        const unsigned ep1 = (*(volatile unsigned*)(g_flags + F_DONE)) / NCTA + 1u;
        const int row = b * 16 + (tid >> 3);
        const uint4* src = reinterpret_cast<const uint4*>(P.in_x + (size_t)row * DM) + (tid & 7);
        float s1 = 0.f, s2 = 0.f;
#pragma unroll 1
        for (int k = 0; k < 4; k++) {
          mbar_pace(bars + 8u * (B_EMPTY + PXB * k / 2), 0);
          uint4 v[4];
#pragma unroll
          for (int j = 0; j < 4; j++) v[j] = __ldg(src + (k * 4 + j) * 8);
#pragma unroll
          for (int j = 0; j < 4; j++) {
            const uint32_t w[4] = {v[j].x, v[j].y, v[j].z, v[j].w};
#pragma unroll
            for (int e = 0; e < 4; e++) {
              const float x0 = bf_lo(w[e]), x1 = bf_hi(w[e]);
              s1 += x0 + x1;
              s2 = fmaf(x0, x0, fmaf(x1, x1, s2));
            }
          }
        }
#pragma unroll
        for (int o = 1; o < 8; o <<= 1) {
          s1 += __shfl_xor_sync(0xffffffffu, s1, o);
          s2 += __shfl_xor_sync(0xffffffffu, s2, o);
        }
        if ((tid & 7) == 0) st_rec(&g_stats[0][0][row], s1, s2, 0.f, ep1);
        if (tid == 0) sts32(base + OFF_EPOCH, ep1);
        float4 v[6];
#pragma unroll 1
        for (uint32_t it = 0; it < (1u << 17); ++it) {
          bool ok = true;
#pragma unroll
          for (int t = 0; t < 6; t++) {
            v[t] = ld_rec(t < 2 ? &g_stats[0][0][(t * 8 + qr) * 128 + tid] : &g_cs[0][hp][(tid & 1) * 4 + t - 2][tid >> 1]);
            ok &= __float_as_uint(v[t].w) == ep1;
          }
          STAMP(KSQ == 0 && it == 0, 18);
          if (ok) break;
          __nanosleep(100);
        }
        STAMP(KSQ == 0, 17);
        __syncwarp();
        STAMP(KSQ == 0, 19);
#pragma unroll
        for (int cc = 0; cc < 2; cc++) sts32(base + OFF_RS + (cc * 128 + tid) * 4, ln_params(v[cc].x, v[cc].y));
        const float cs[3] = {(v[2].x + v[3].x) + (v[4].x + v[5].x), (v[2].y + v[3].y) + (v[4].y + v[5].y),
                             (v[2].z + v[3].z) + (v[4].z + v[5].z)};
#pragma unroll
        for (int blk = 0; blk < 3; blk++) {
          const float t = cs[blk] + __shfl_xor_sync(0xffffffffu, cs[blk], 1);
          cs_put(blk, tid & 1, tid >> 1, (tid & 1) ? 0.f : t);
        }
        fence_proxy_async_smem();
        named_bar_sync(2, 128);
        if (tid < 2) mbar_arrive(bars + 8u * (B_PREP + tid));
      }
    }
#pragma unroll 1
    for (int inst = asst ? 0 : warp >> 2; inst < 8; inst += asst ? 1 : 2) {
      const int L = inst >> 1, ch = inst & 1, gb = ch * 8 + qr;
      if (asst) {
        setmaxnreg_dec<24>();
        if (warp == 8) {
          named_bar_sync(3, 192);
          STA(32);
          if (elect_one()) {
            if ((L & 1) == 0) {
              bulk_store(g_kvA[L >> 1][gb][hp][1], slots + 16384, 16384);
            } else {
              bulk_store(g_kvB[L >> 1][gb][hp], KB_ROW0 + 112 * 128, 2048);
              bulk_store(g_kvB[L >> 1][gb][hp] + 2048, VB_ROW0 + 112 * 128, 2048);
            }
            bulk_commit();
            bulk_wait0();
            fence_proxy_async_all();
            red_relaxed_add(g_flags + F_KV + (gb * 16 + hp) * KSTR, 1u);
            STA(33);
          }
          __syncwarp();
        } else if (warp == 9 && (L & 1) == 0) {
          named_bar_sync(7, 160);
          if (lane0) {
            bulk_store(g_kvA[L >> 1][gb][hp][0], slots, 16384);
            bulk_commit();
          }
          __syncwarp();
        }
        named_bar_sync(4, 256);
        setmaxnreg_inc<128>();
      } else {
      setmaxnreg_inc<224>();
      {
        float acc[2][96];
        const int ksp = q_split(inst);
        int n = q_first(inst);
        uint32_t dlt = (ch == 0 && L > 0) ? 10u * (UNIT >> 4) : 0u;
        if (inst == 1 || (inst > 1 && q_split(inst - 1) != 4)) {
          mbar_wait_lazy<100>(bars + 8u * (B_TURN + ch), tpar);
          tpar ^= 1u;
        }
        if (L == 3) GTL(37);
        mbar_wait(bars + 8u * (B_FULL + (n & 7)), (n >> 3) & 1);
        GTL(1 + L * 8);
        {
          const uint32_t da = (base >> 4) + 0x10000u + dlt;
          const uint64_t db = desc_lo(da - 0x10000u + ((UNIT >> 4) << 16) + 2 * (UNIT >> 4));
          wgmma_fence();
          wgmma_n192_ssz_ta0_tb1(acc[0], desc_lo(da), db);
          wgmma_commit();
          wgmma_n192_ssz_ta0_tb1(acc[1], desc_lo(da + (UNIT >> 4)), db);
          wgmma_commit();
        }
#pragma unroll 1
        for (int k4 = 0; k4 < 4; k4++) {
          const bool brk = k4 + 1 == ksp && k4 < 3;
#pragma unroll
          for (int ks = 0; ks < 4; ks++, n++) {
            if (ks == 2 && k4 == 3) break;
            STAMP(inst == KSQ, k4 * 4 + ks);
            const uint32_t da = ((base + ks * 5 * UNIT) >> 4) + 0x10000u + (ks < 2 ? dlt : 0u - dlt);
            const uint32_t dbb = da - 0x10000u + ((UNIT >> 4) << 16) + 2 * (UNIT >> 4);
#pragma unroll
            for (int k16 = 0; k16 < 4; k16++) {
              if (ks == 0 && k16 == 0 && k4 == 0) continue;
              const uint64_t db = desc_lo(dbb + k16 * 128);
              wgmma_fence();
              wgmma_n192_ss_ta0_tb1(acc[0], desc_lo(da + k16 * 2), db, 1);
              wgmma_commit();
              wgmma_wait<1>();
              if (k16 == 0 && lane0 && (ks != 0 || k4 != ksp)) mbar_arrive(bars + 8u * (B_EMPTY + ((n - 1) & 7)));
              wgmma_fence();
              wgmma_n192_ss_ta0_tb1(acc[1], desc_lo(da + (UNIT >> 4) + k16 * 2), db, 1);
              wgmma_commit();
              bool ok = true;
              if (k16 == 2) ok = mbar_test(bars + 8u * (B_FULL + ((n + 1) & 7)), ((n + 1) >> 3) & 1) || (ks == 3 && brk);
              if (k16 == QTURN && ks == 3 && brk && lane0) mbar_arrive(bars + 8u * (B_TURN + (ch ^ 1)));
              if ((ks & 1) == 0 || k16 < 3) wgmma_wait<1>();
              if (k16 == 2 && !ok) mbar_wait(bars + 8u * (B_FULL + ((n + 1) & 7)), ((n + 1) >> 3) & 1);
            }
          }
          if (brk) {
            wgmma_wait<0>();
            if (lane0) mbar_arrive(bars + 8u * (B_EMPTY + ((n - 1) & 7)));
            n += 16;
            dlt ^= 10u * (UNIT >> 4);
            mbar_wait_lazy<100>(bars + 8u * (B_TURN + ch), tpar);
            tpar ^= 1u;
            STAMP(inst == KSQ, 17);
            mbar_wait(bars + 8u * (B_FULL + (n & 7)), (n >> 3) & 1);
          }
        }
        auto tail_group = [&](int u) {
          const uint32_t da = ((base + (2 + (u & 1)) * 5 * UNIT) >> 4) + 0x10000u - dlt;
          const uint32_t dbb = da - 0x10000u + ((UNIT >> 4) << 16) + 2 * (UNIT >> 4);
          if (u < 3) wgmma_fence();
#pragma unroll
          for (int k16 = 0; k16 < 4; k16++)
            wgmma_n192_ss_ta0_tb1(acc[u < 2], desc_lo(da + (u < 2 ? UNIT >> 4 : 0) + k16 * 2), desc_lo(dbb + k16 * 128), 1);
          wgmma_commit();
        };
        STAMP(inst == KSQ, 14);
        tail_group(0);
        wgmma_wait<1>();
        STAMP(inst == KSQ, 42);
        if (lane0) mbar_arrive(bars + 8u * (B_EMPTY + ((n - 1) & 7)));
        PHASE_IDS
        mbar_wait(bars + 8u * (B_PREP + ch), L & 1);
        STAMP(inst == KSQ, 43);
        uint32_t rs[4];
#pragma unroll
        for (int i = 0; i < 4; i++)
          rs[i] = lds32(base + OFF_RS + (ch * 128 + (i >> 1) * 64 + wwarp * 16 + g + 8 * (i & 1)) * 4);
        auto fold = [&](int h) {
          uint32_t a[2];
#pragma unroll
          for (int r = 0; r < 2; r++) a[r] = c == (L & 1) ? __byte_perm(rs[2 * h + r], 0, 0x1010) ^ 0x80008000u : 0u;
          uint64_t d;
          asm("mov.b64 %0, {%1, %2};" : "=l"(d) : "r"(((base + OFF_CS) >> 4) + ((512 >> 4) << 16)), "r"(0x40000000u));
          wgmma_fence();
          wgmma_n192_rs_tb1(acc[h], a[0], a[1], d);
        };
        fold(1);
        wgmma_commit();
        mbar_wait(bars + 8u * (B_FULL + ((n + 1) & 7)), ((n + 1) >> 3) & 1);
        STAMP(inst == KSQ, 44);
        tail_group(1);
        tail_group(2);
        STAMP(inst == KSQ, 45);
        const bool ppre = inst > 0 && w_pre(inst - 1);
        const uint32_t fbar = bars + 8u * (ppre ? B_RESE : (inst == CSI + 1 ? B_CSD : B_AFREE));
        const uint32_t fpar = ppre ? ch ^ 1 : (inst == CSI + 1 ? 0 : ch);
        const bool afree = mbar_test(fbar, fpar);
        float rinv[2][2];
#pragma unroll
        for (int i = 0; i < 4; i++) rinv[i >> 1][i & 1] = rcp_fast(bf_hi(rs[i]));
        const int mat = lane >> 3;
        const uint32_t soff = (wwarp * 16 + (mat & 1) * 8 + (lane & 7)) * 128;
        const uint32_t kdst = ((L & 1) ? KB_ROW0 : slots) + soff, vdst = ((L & 1) ? VB_ROW0 : slots + 8192) + soff;
        const uint32_t hs = (L & 1) ? 8192 : 16384;
        const int rg = 2 * wwarp + (mat & 1);
        const uint32_t qdst = slots + 3 * 16384 + ((L & 1) ? soff : ((rg < 4 ? 2 * rg : 15 - 2 * rg) * 8 + (lane & 7)) * 128);
        wgmma_wait<2>();
        STAMP(inst == KSQ, 46);
        fold(0);
        tail_group(3);
        STAMP(inst == KSQ, 47);
        if (EPT < 0 && lane0) mbar_arrive(bars + 8u * (B_TURN + (ch ^ 1)));
        if (!afree) {
          if (EPT >= 0 && lane0) mbar_arrive(bars + 8u * (B_TURN + (ch ^ 1)));
          wgmma_wait<1>();
          if (lane0) mbar_arrive(bars + 8u * (B_EMPTY + (n & 7)));
          wgmma_wait<0>();
          if (lane0) mbar_arrive(bars + 8u * (B_EMPTY + ((n + 1) & 7)));
          mbar_wait(fbar, fpar);
        }
        wgmma_wait<2>();
        reg_fence<96>(acc[1]);
        STAMP(inst == KSQ, 15);
#pragma unroll
        for (int t = 0; t < 24; t++) {
          const int h = t < 12 ? 1 : 0, p = (t % 12 / 4 + 1) % 3, jp = t & 3;
          if (t == EPT && lane0 && afree) mbar_arrive(bars + 8u * (B_TURN + (ch ^ 1)));
          if (t == EPW1) {
            wgmma_wait<1>();
            if (lane0 && afree) mbar_arrive(bars + 8u * (B_EMPTY + (n & 7)));
          }
          if (t == EPW0) {
            wgmma_wait<0>();
            reg_fence<96>(acc[0]);
            if (lane0 && afree) mbar_arrive(bars + 8u * (B_EMPTY + ((n + 1) & 7)));
            STAMP(inst == KSQ, 16);
            GTL(2 + L * 8);
          }
          if (t % 12 == 8) {
            rinv[h][0] *= SM_C;
            rinv[h][1] *= SM_C;
          }
          const uint32_t sw = ((2 * jp + (mat >> 1)) ^ (lane & 7)) << 4;
          const float* a = &acc[h][32 * p + 8 * jp];
          const uint32_t dst = p == 0 ? qdst + h * 8192 : (p == 1 ? kdst : vdst) + h * hs;
          stmatrix_x4(dst + sw, pack_bf16x2(a[0] * rinv[h][0], a[1] * rinv[h][0]), pack_bf16x2(a[2] * rinv[h][1], a[3] * rinv[h][1]),
                      pack_bf16x2(a[4] * rinv[h][0], a[5] * rinv[h][0]), pack_bf16x2(a[6] * rinv[h][1], a[7] * rinv[h][1]));
          if (t % 12 == 7) {
            fence_proxy_async_smem();
            if (t == 7) named_bar_arrive(3, 192);
            else if ((L & 1) == 0) named_bar_arrive(7, 160);
            if (t > EPW0) sched_fence(P.zero);
          }
        }
      }
      fence_proxy_async_smem();
      setmaxnreg_dec<128>();
      named_bar_sync(4, 256);
      }
      GTL(3 + L * 8);
      {
        PHASE_IDS
        if ((L & 1) == 0) attention_a(asst, L, gb, hp, inst & 1, ch, (tid_ >> 5) & 3, lane, P.zero);
        else attention_b(asst, gb, inst & 1, wwarp, lane);
        GTL(4 + L * 8);
        fence_proxy_async_smem();
      }
      if (asst) {
        named_bar_arrive(5, 256);
        if (inst == CSI) {
          mbar_wait(bars + 8u * B_AFREE, CSI ^ 1);
          colsum_part(&P.wqkv[1], 1, qr, hp);
          if (lane0) mbar_arrive(bars + 8u * B_CSD);
        }
        continue;
      }
      {
        named_bar_sync(5, 256);
        const int wwarp = warp & 3;
        if (wwarp < 2 && elect_one()) {
          tma_store_3d(&P.o, ((L & 1) ? slots + 3 * 16384 : OA_TILE) + wwarp * 8192, 0, gb * 128 + wwarp * 64, hp);
          bulk_commit();
          bulk_wait0();
          mbar_arrive(bars + 8u * B_AFREE);
          fence_proxy_async_all();
          red_relaxed_add(g_flags + F_O + (gb * 2 + wwarp) * OSTR + hp, 1u);
        }
        __syncwarp();
      }
      GTL(5 + L * 8);

      {
        float acc[64];
        const int n0 = w_first(inst);
        const bool pre = w_pre(inst);
        const uint32_t dl = ch * 10u * UNIT;
        mbar_wait_lazy<100>(bars + 8u * (B_TURN + ch), tpar);
        tpar ^= 1u;
        mbar_wait(bars + 8u * (B_FULL + (n0 & 7)), (n0 >> 3) & 1);
        GTL(6 + L * 8);
#pragma unroll
        for (int kt = 0; kt < 16; kt++) {
          const int n = n0 + kt;
          STAMP(inst == KSW, 20 + kt);
          const uint32_t da = ((base + (pre ? unit_off(p_ua(kt), dl) : unit_off(w_ua(kt), dl))) >> 4) + 0x10000u;
          const uint32_t db = ((base + (pre ? unit_off(p_ub(kt), dl) : unit_off(w_ub(kt), dl))) >> 4) + ((UNIT >> 4) << 16);
          if (kt == 15 && lane0 && (inst >= 6 || q_split(inst + 1) != 4)) mbar_arrive(bars + 8u * (B_TURN + (ch ^ 1)));
          wgmma_fence();
          if (kt == 0) wgmma_n128_ssz_ta0_tb1(acc, desc_lo(da), desc_lo(db));
#pragma unroll
          for (int k16 = kt == 0 ? 1 : 0; k16 < 4; k16++) wgmma_n128_ss_ta0_tb1(acc, desc_lo(da + 2 * k16), desc_lo(db + 128 * k16), 1);
          wgmma_commit();
          const uint32_t nb = bars + 8u * (kt == 15 ? B_RESF : B_FULL + ((n + 1) & 7)), np = kt == 15 ? ch : ((n + 1) >> 3) & 1;
          const bool ok = mbar_test(nb, np);
          if (kt > 0) {
            wgmma_wait<1>();
            if (lane0) mbar_arrive(bars + 8u * (B_EMPTY + ((n - 1) & 7)));
          }
          if (!ok) mbar_wait(nb, np);
        }
        PHASE_IDS
        const uint32_t xb = pre ? slots + 2 * UNIT : base + 8 * UNIT + dl;
        const int mat = lane >> 3;
        const uint32_t xrow = xb + (wwarp * 16 + (mat & 1) * 8 + (lane & 7)) * 128;
        uint32_t xv[8][4];
#pragma unroll
        for (int jp = 0; jp < 8; jp++)
          ldmatrix_x4(xv[jp], xrow + (jp >> 2) * UNIT + (((2 * (jp & 3) + (mat >> 1)) ^ (lane & 7)) << 4));
        wgmma_wait<0>();
        reg_fence<64>(acc);
        if (lane0) mbar_arrive(bars + 8u * (B_EMPTY + ((n0 + 15) & 7)));
        STAMP(inst == KSW, 36);
        GTL(7 + L * 8);
#pragma unroll
        for (int jp = 0; jp < 8; jp++) {
#pragma unroll
          for (int q = 0; q < 4; q++) xv[jp][q] = add_bf16x2(xv[jp][q], pack_bf16x2(acc[8 * jp + 2 * q], acc[8 * jp + 2 * q + 1]));
          stmatrix_x4(xrow + (jp >> 2) * UNIT + (((2 * (jp & 3) + (mat >> 1)) ^ (lane & 7)) << 4), xv[jp][0], xv[jp][1],
                      xv[jp][2], xv[jp][3]);
        }
        fence_proxy_async_smem();
        named_bar_sync(1 + ch, 128);
        const int grow = ch * 1024 + rt * 64;
        if (wwarp == 0) {
          if (elect_one()) {
            tma_store_3d(&P.xr[L == 3 ? 2 : 1], xb, 0, grow, ct * 2);
            bulk_commit();
            bulk_wait_read0();
            mbar_arrive(bars + 8u * B_RESE);
            bulk_wait0();
            TGET(t35);
            fence_proxy_async_all();
            if (L < 3) red_relaxed_add(g_flags + F_X + (ch * 8 + (rt >> 1)) * XSTR + ct, 1u);
            if (L == 2) TPUT(ch, 35, t35);
          }
          __syncwarp();
        } else if (lane == 0) {
          mbar_arrive(bars + 8u * B_RESE);
        }
        if (L < 3) {
          const unsigned ep1 = lds32(base + OFF_EPOCH);
          float s1[2] = {0.f, 0.f}, s2[2] = {0.f, 0.f};
#pragma unroll
          for (int jp = 0; jp < 8; jp++)
#pragma unroll
            for (int q = 0; q < 4; q++) {
              const float x0 = bf_lo(xv[jp][q]), x1 = bf_hi(xv[jp][q]);
              s1[q & 1] += x0 + x1;
              s2[q & 1] = fmaf(x0, x0, fmaf(x1, x1, s2[q & 1]));
            }
#pragma unroll
          for (int r = 0; r < 2; r++) {
            s1[r] += __shfl_xor_sync(0xffffffffu, s1[r], 1);
            s2[r] += __shfl_xor_sync(0xffffffffu, s2[r], 1);
            s1[r] += __shfl_xor_sync(0xffffffffu, s1[r], 2);
            s2[r] += __shfl_xor_sync(0xffffffffu, s2[r], 2);
            if (c == 0) st_rec(&g_stats[L + 1][ct][grow + wwarp * 16 + g + 8 * r], s1[r], s2[r], 0.f, ep1);
          }
        }
        GTL(8 + L * 8);
      }
    }
    if (threadIdx.x == 128) atomicAdd(g_flags + F_DONE, 1u);
  }
}

typedef CUresult (*PFN_tmEncode)(CUtensorMap*, CUtensorMapDataType, cuuint32_t, void*, const cuuint64_t*,
                                 const cuuint64_t*, const cuuint32_t*, const cuuint32_t*, CUtensorMapInterleave,
                                 CUtensorMapSwizzle, CUtensorMapL2promotion, CUtensorMapFloatOOBfill);

PFN_tmEncode get_encode_fn() {
  static PFN_tmEncode fn = nullptr;
  if (!fn) {
    cudaDriverEntryPointQueryResult qr;
    void* p = nullptr;
    cudaGetDriverEntryPoint("cuTensorMapEncodeTiled", &p, cudaEnableDefault, &qr);
    fn = (PFN_tmEncode)p;
  }
  return fn;
}

CUtensorMap make_map(const void* ptr, int rows, int cols, int inner, int box_rows, int box_blk) {
  CUtensorMap m;
  cuuint64_t gdim[3] = {(cuuint64_t)inner, (cuuint64_t)rows, (cuuint64_t)(cols / inner)};
  cuuint64_t gstr[2] = {(cuuint64_t)cols * 2, (cuuint64_t)inner * 2};
  cuuint32_t box[3] = {64, (cuuint32_t)box_rows, (cuuint32_t)box_blk};
  cuuint32_t estr[3] = {1, 1, 1};
  get_encode_fn()(&m, CU_TENSOR_MAP_DATA_TYPE_BFLOAT16, 3, const_cast<void*>(ptr), gdim, gstr, box, estr,
                  CU_TENSOR_MAP_INTERLEAVE_NONE, CU_TENSOR_MAP_SWIZZLE_128B, CU_TENSOR_MAP_L2_PROMOTION_L2_128B,
                  CU_TENSOR_MAP_FLOAT_OOB_FILL_NONE);
  return m;
}

}

extern "C" void kernel_launch(void* const* d_in, const int* in_sizes, int n_in, void* d_out, int out_size) {
  (void)in_sizes; (void)n_in; (void)out_size;
  void *p_o, *p_x;
  cudaGetSymbolAddress(&p_o, g_o);
  cudaGetSymbolAddress(&p_x, g_x);
  static bool attr_done = false;
  if (!attr_done) {
    cudaFuncSetAttribute(fused_kernel, cudaFuncAttributeMaxDynamicSharedMemorySize, SMEM_BYTES);
    attr_done = true;
  }
  Params P;
  P.in_x = (const __nv_bfloat16*)d_in[0];
  P.wqkv_p[0] = (const __nv_bfloat16*)d_in[1];
  P.wo_p[0] = (const __nv_bfloat16*)d_in[2];
  P.wqkv_p[1] = (const __nv_bfloat16*)d_in[4];
  P.wo_p[1] = (const __nv_bfloat16*)d_in[5];
  P.out = (__nv_bfloat16*)d_out;
  P.zero = 0;
  P.xq[0] = make_map(P.in_x, S_LEN, DM, 64, 128, 1);
  P.xq[1] = make_map(p_x, S_LEN, DM, 64, 128, 1);
  P.xr[0] = make_map(P.in_x, S_LEN, DM, 64, 64, 2);
  P.xr[1] = make_map(p_x, S_LEN, DM, 64, 64, 2);
  P.xr[2] = make_map(d_out, S_LEN, DM, 64, 64, 2);
  P.o = make_map(p_o, S_LEN, DM, 64, 64, 1);
  for (int t = 0; t < 2; t++) {
    P.wqkv[t] = make_map(P.wqkv_p[t], DM, NQKV, 1024, 64, 3);
    P.wo[t] = make_map(P.wo_p[t], DM, DM, 64, 64, 2);
  }
  fused_kernel<<<NCTA, 512, SMEM_BYTES>>>(P);
}
```

```cpp
#include <cuda_runtime.h>
#include <cuda_bf16.h>
#include <cuda.h>
#include <stdint.h>

namespace {

constexpr int S_LEN = 2048;
constexpr int DM = 1024;
constexpr int NQKV = 3072;
constexpr int NCTA = 128;

__device__ __align__(1024) uint8_t g_kvA[2][16][16][2][16384];
__device__ __align__(1024) uint8_t g_kvB[2][16][16][4096];
__device__ __align__(1024) uint8_t g_zero[16384];
__device__ __align__(1024) __nv_bfloat16 g_o[S_LEN * DM];
__device__ __align__(1024) __nv_bfloat16 g_x[S_LEN * DM];
__device__ __align__(1024) float4 g_stats[4][8][S_LEN];
__device__ __align__(1024) float4 g_cs[2][16][8][64];
constexpr int F_X = 0;
constexpr int XSTR = 32, OSTR = 32, KSTR = 32;
constexpr int F_O = F_X + 16 * XSTR;
constexpr int F_KV = F_O + 32 * OSTR;
constexpr int F_DONE = F_KV + 256 * KSTR;
__device__ __align__(1024) unsigned g_flags[F_DONE + 32];

constexpr uint32_t SBASE = 1024;
constexpr int UNIT = 8192;
constexpr int NUNITS = 20;
constexpr int OFF_SLOT = NUNITS * UNIT;
constexpr int OFF_CS = OFF_SLOT + 4 * 16384;
constexpr int OFF_RS = OFF_CS + 1536;
constexpr int OFF_BAR = OFF_RS + 1024;
constexpr int OFF_EPOCH = OFF_BAR + 296;
constexpr int OFF_TS = OFF_BAR + 304;
constexpr int SMEM_BYTES = OFF_TS;
constexpr int B_FULL = 0, B_EMPTY = 8, B_PREP = 16, B_HALO = 18, B_REL = 22, B_AFREE = 25, B_TURN = 26, B_XRDY = 28,
              B_CS = 30, B_CSD = 31, B_GO = 32, B_PRE = 33, B_RESF = 34, B_RESE = 35;

__device__ __forceinline__ uint32_t smem_u32(const void* p) { return (uint32_t)__cvta_generic_to_shared(p); }

__device__ __forceinline__ void mbar_init(uint32_t bar, uint32_t cnt) {
  asm volatile("mbarrier.init.shared::cta.b64 [%0], %1;" ::"r"(bar), "r"(cnt));
}
__device__ __forceinline__ void mbar_expect_tx(uint32_t bar, uint32_t bytes) {
  asm volatile("mbarrier.arrive.expect_tx.shared::cta.b64 _, [%0], %1;" ::"r"(bar), "r"(bytes) : "memory");
}
__device__ __forceinline__ void mbar_arrive(uint32_t bar) {
  asm volatile("mbarrier.arrive.shared::cta.b64 _, [%0];" ::"r"(bar) : "memory");
}
__device__ __forceinline__ bool mbar_try_wait(uint32_t bar, uint32_t parity) {
  uint32_t ok;
  asm volatile(
      "{\n.reg .pred p;\nmbarrier.try_wait.parity.shared::cta.b64 p, [%1], %2;\nselp.b32 %0, 1, 0, p;\n}\n"
      : "=r"(ok)
      : "r"(bar), "r"(parity)
      : "memory");
  return ok != 0;
}
__device__ __forceinline__ bool mbar_test(uint32_t bar, uint32_t parity) {
  uint32_t ok;
  asm volatile(
      "{\n.reg .pred p;\nmbarrier.test_wait.parity.shared::cta.b64 p, [%1], %2;\nselp.b32 %0, 1, 0, p;\n}\n"
      : "=r"(ok)
      : "r"(bar), "r"(parity)
      : "memory");
  return ok != 0;
}
__device__ __forceinline__ void mbar_wait(uint32_t bar, uint32_t parity) {
#pragma unroll 1
  for (uint32_t it = 0; it < (1u << 18); ++it) {
    if (mbar_try_wait(bar, parity)) return;
  }
}
__device__ __forceinline__ void mbar_pace(uint32_t bar, uint32_t parity) {
#pragma unroll 1
  for (uint32_t it = 0; it < 24; ++it) {
    if (mbar_try_wait(bar, parity)) return;
  }
}
template <int NS>
__device__ __forceinline__ void mbar_wait_lazy(uint32_t bar, uint32_t parity) {
#pragma unroll 1
  for (uint32_t it = 0; it < (1u << 18); ++it) {
    if (mbar_try_wait(bar, parity)) return;
    __nanosleep(NS);
  }
}
__device__ __forceinline__ bool elect_one() {
  uint32_t ok;
  asm volatile("{\n.reg .pred p;\nelect.sync _|p, 0xffffffff;\nselp.b32 %0, 1, 0, p;\n}\n" : "=r"(ok));
  return ok != 0;
}
__device__ __forceinline__ void fence_barrier_init() { asm volatile("fence.mbarrier_init.release.cluster;" ::: "memory"); }
__device__ __forceinline__ void fence_proxy_async_smem() { asm volatile("fence.proxy.async.shared::cta;" ::: "memory"); }
__device__ __forceinline__ void fence_proxy_async_all() { asm volatile("fence.proxy.async.global;" ::: "memory"); }

__device__ __forceinline__ void tma_load_3d(uint32_t dst, const CUtensorMap* map, uint32_t bar, int c0, int c1, int c2) {
  asm volatile(
      "cp.async.bulk.tensor.3d.shared::cluster.global.mbarrier::complete_tx::bytes [%0], [%1, {%3, %4, %5}], [%2];" ::"r"(dst),
      "l"(map), "r"(bar), "r"(c0), "r"(c1), "r"(c2)
      : "memory");
}
__device__ __forceinline__ void bulk_load(uint32_t dst, const void* src, uint32_t bytes, uint32_t bar) {
  asm volatile("cp.async.bulk.shared::cluster.global.mbarrier::complete_tx::bytes [%0], [%1], %2, [%3];" ::"r"(dst),
               "l"(src), "r"(bytes), "r"(bar)
               : "memory");
}
__device__ __forceinline__ void bulk_store(void* dst, uint32_t src, uint32_t bytes) {
  asm volatile("cp.async.bulk.global.shared::cta.bulk_group [%0], [%1], %2;" ::"l"(dst), "r"(src), "r"(bytes) : "memory");
}
__device__ __forceinline__ void tma_store_3d(const CUtensorMap* map, uint32_t src, int c0, int c1, int c2) {
  asm volatile("cp.async.bulk.tensor.3d.global.shared::cta.bulk_group [%0, {%2, %3, %4}], [%1];" ::"l"(map), "r"(src),
               "r"(c0), "r"(c1), "r"(c2)
               : "memory");
}
__device__ __forceinline__ void bulk_commit() { asm volatile("cp.async.bulk.commit_group;" ::: "memory"); }
__device__ __forceinline__ void bulk_wait_read0() { asm volatile("cp.async.bulk.wait_group.read 0;" ::: "memory"); }
__device__ __forceinline__ void bulk_wait0() { asm volatile("cp.async.bulk.wait_group 0;" ::: "memory"); }
__device__ __forceinline__ void named_bar_sync(int id, int nthreads) {
  asm volatile("bar.sync %0, %1;" ::"r"(id), "r"(nthreads) : "memory");
}
__device__ __forceinline__ void named_bar_arrive(int id, int nthreads) {
  asm volatile("bar.arrive %0, %1;" ::"r"(id), "r"(nthreads) : "memory");
}

__device__ __forceinline__ void wgmma_fence() { asm volatile("wgmma.fence.sync.aligned;\n" ::: "memory"); }
__device__ __forceinline__ void wgmma_commit() { asm volatile("wgmma.commit_group.sync.aligned;\n" ::: "memory"); }
template <int N>
__device__ __forceinline__ void wgmma_wait() {
  asm volatile("wgmma.wait_group.sync.aligned %0;\n" ::"n"(N) : "memory");
}
template <int R>
__device__ __forceinline__ void setmaxnreg_inc() { asm volatile("setmaxnreg.inc.sync.aligned.u32 %0;\n" ::"n"(R)); }
template <int R>
__device__ __forceinline__ void setmaxnreg_dec() { asm volatile("setmaxnreg.dec.sync.aligned.u32 %0;\n" ::"n"(R)); }
template <int N>
__device__ __forceinline__ void reg_fence(float* r) {
#pragma unroll
  for (int i = 0; i < N; i++) asm volatile("" : "+f"(r[i])::"memory");
}

template <int N>
__device__ __forceinline__ void reg_define(float* r) {
#pragma unroll
  for (int i = 0; i < N; i++) r[i] = 0.f;
}

__device__ __forceinline__ uint64_t desc_lo(uint32_t lo) {
  uint64_t d;
  asm("mov.b64 %0, {%1, %2};" : "=l"(d) : "r"(lo), "r"(0x40000040u));
  return d;
}
__device__ __forceinline__ uint64_t make_desc(uint32_t addr, uint32_t lbo_bytes) {
  return desc_lo((addr >> 4) + ((lbo_bytes >> 4) << 16));
}

__device__ __forceinline__ void wgmma_n192_ss_ta0_tb1(float* d, uint64_t descA, uint64_t descB, int scaleD) {
  asm volatile("{\n.reg .pred p;\nsetp.ne.b32 p, %98, 0;\n"
    "wgmma.mma_async.sync.aligned.m64n192k16.f32.bf16.bf16 {%0, %1, %2, %3, %4, %5, %6, %7, %8, %9, %10, %11, %12, %13, %14, %15, %16, %17, %18, %19, %20, %21, %22, %23, %24, %25, %26, %27, %28, %29, %30, %31, %32, %33, %34, %35, %36, %37, %38, %39, %40, %41, %42, %43, %44, %45, %46, %47, %48, %49, %50, %51, %52, %53, %54, %55, %56, %57, %58, %59, %60, %61, %62, %63, %64, %65, %66, %67, %68, %69, %70, %71, %72, %73, %74, %75, %76, %77, %78, %79, %80, %81, %82, %83, %84, %85, %86, %87, %88, %89, %90, %91, %92, %93, %94, %95}, %96, %97, p, 1, 1, 0, 1;\n}\n"
    : "+f"(d[0]), "+f"(d[1]), "+f"(d[2]), "+f"(d[3]), "+f"(d[4]), "+f"(d[5]), "+f"(d[6]), "+f"(d[7]), "+f"(d[8]), "+f"(d[9]), "+f"(d[10]), "+f"(d[11]), "+f"(d[12]), "+f"(d[13]), "+f"(d[14]), "+f"(d[15]), "+f"(d[16]), "+f"(d[17]), "+f"(d[18]), "+f"(d[19]), "+f"(d[20]), "+f"(d[21]), "+f"(d[22]), "+f"(d[23]), "+f"(d[24]), "+f"(d[25]), "+f"(d[26]), "+f"(d[27]), "+f"(d[28]), "+f"(d[29]), "+f"(d[30]), "+f"(d[31]), "+f"(d[32]), "+f"(d[33]), "+f"(d[34]), "+f"(d[35]), "+f"(d[36]), "+f"(d[37]), "+f"(d[38]), "+f"(d[39]), "+f"(d[40]), "+f"(d[41]), "+f"(d[42]), "+f"(d[43]), "+f"(d[44]), "+f"(d[45]), "+f"(d[46]), "+f"(d[47]), "+f"(d[48]), "+f"(d[49]), "+f"(d[50]), "+f"(d[51]), "+f"(d[52]), "+f"(d[53]), "+f"(d[54]), "+f"(d[55]), "+f"(d[56]), "+f"(d[57]), "+f"(d[58]), "+f"(d[59]), "+f"(d[60]), "+f"(d[61]), "+f"(d[62]), "+f"(d[63]), "+f"(d[64]), "+f"(d[65]), "+f"(d[66]), "+f"(d[67]), "+f"(d[68]), "+f"(d[69]), "+f"(d[70]), "+f"(d[71]), "+f"(d[72]), "+f"(d[73]), "+f"(d[74]), "+f"(d[75]), "+f"(d[76]), "+f"(d[77]), "+f"(d[78]), "+f"(d[79]), "+f"(d[80]), "+f"(d[81]), "+f"(d[82]), "+f"(d[83]), "+f"(d[84]), "+f"(d[85]), "+f"(d[86]), "+f"(d[87]), "+f"(d[88]), "+f"(d[89]), "+f"(d[90]), "+f"(d[91]), "+f"(d[92]), "+f"(d[93]), "+f"(d[94]), "+f"(d[95])
    : "l"(descA), "l"(descB), "r"(scaleD));
}

__device__ __forceinline__ void wgmma_n128_ss_ta0_tb1(float* d, uint64_t descA, uint64_t descB, int scaleD) {
  asm volatile("{\n.reg .pred p;\nsetp.ne.b32 p, %66, 0;\n"
    "wgmma.mma_async.sync.aligned.m64n128k16.f32.bf16.bf16 {%0, %1, %2, %3, %4, %5, %6, %7, %8, %9, %10, %11, %12, %13, %14, %15, %16, %17, %18, %19, %20, %21, %22, %23, %24, %25, %26, %27, %28, %29, %30, %31, %32, %33, %34, %35, %36, %37, %38, %39, %40, %41, %42, %43, %44, %45, %46, %47, %48, %49, %50, %51, %52, %53, %54, %55, %56, %57, %58, %59, %60, %61, %62, %63}, %64, %65, p, 1, 1, 0, 1;\n}\n"
    : "+f"(d[0]), "+f"(d[1]), "+f"(d[2]), "+f"(d[3]), "+f"(d[4]), "+f"(d[5]), "+f"(d[6]), "+f"(d[7]), "+f"(d[8]), "+f"(d[9]), "+f"(d[10]), "+f"(d[11]), "+f"(d[12]), "+f"(d[13]), "+f"(d[14]), "+f"(d[15]), "+f"(d[16]), "+f"(d[17]), "+f"(d[18]), "+f"(d[19]), "+f"(d[20]), "+f"(d[21]), "+f"(d[22]), "+f"(d[23]), "+f"(d[24]), "+f"(d[25]), "+f"(d[26]), "+f"(d[27]), "+f"(d[28]), "+f"(d[29]), "+f"(d[30]), "+f"(d[31]), "+f"(d[32]), "+f"(d[33]), "+f"(d[34]), "+f"(d[35]), "+f"(d[36]), "+f"(d[37]), "+f"(d[38]), "+f"(d[39]), "+f"(d[40]), "+f"(d[41]), "+f"(d[42]), "+f"(d[43]), "+f"(d[44]), "+f"(d[45]), "+f"(d[46]), "+f"(d[47]), "+f"(d[48]), "+f"(d[49]), "+f"(d[50]), "+f"(d[51]), "+f"(d[52]), "+f"(d[53]), "+f"(d[54]), "+f"(d[55]), "+f"(d[56]), "+f"(d[57]), "+f"(d[58]), "+f"(d[59]), "+f"(d[60]), "+f"(d[61]), "+f"(d[62]), "+f"(d[63])
    : "l"(descA), "l"(descB), "r"(scaleD));
}

__device__ __forceinline__ void wgmma_n192_ssz_ta0_tb1(float* d, uint64_t descA, uint64_t descB) {
  asm volatile("{\n.reg .pred p;\nsetp.ne.b32 p, 0, 0;\n"
    "wgmma.mma_async.sync.aligned.m64n192k16.f32.bf16.bf16 {%0, %1, %2, %3, %4, %5, %6, %7, %8, %9, %10, %11, %12, %13, %14, %15, %16, %17, %18, %19, %20, %21, %22, %23, %24, %25, %26, %27, %28, %29, %30, %31, %32, %33, %34, %35, %36, %37, %38, %39, %40, %41, %42, %43, %44, %45, %46, %47, %48, %49, %50, %51, %52, %53, %54, %55, %56, %57, %58, %59, %60, %61, %62, %63, %64, %65, %66, %67, %68, %69, %70, %71, %72, %73, %74, %75, %76, %77, %78, %79, %80, %81, %82, %83, %84, %85, %86, %87, %88, %89, %90, %91, %92, %93, %94, %95}, %96, %97, p, 1, 1, 0, 1;\n}\n"
    : "=f"(d[0]), "=f"(d[1]), "=f"(d[2]), "=f"(d[3]), "=f"(d[4]), "=f"(d[5]), "=f"(d[6]), "=f"(d[7]), "=f"(d[8]), "=f"(d[9]), "=f"(d[10]), "=f"(d[11]), "=f"(d[12]), "=f"(d[13]), "=f"(d[14]), "=f"(d[15]), "=f"(d[16]), "=f"(d[17]), "=f"(d[18]), "=f"(d[19]), "=f"(d[20]), "=f"(d[21]), "=f"(d[22]), "=f"(d[23]), "=f"(d[24]), "=f"(d[25]), "=f"(d[26]), "=f"(d[27]), "=f"(d[28]), "=f"(d[29]), "=f"(d[30]), "=f"(d[31]), "=f"(d[32]), "=f"(d[33]), "=f"(d[34]), "=f"(d[35]), "=f"(d[36]), "=f"(d[37]), "=f"(d[38]), "=f"(d[39]), "=f"(d[40]), "=f"(d[41]), "=f"(d[42]), "=f"(d[43]), "=f"(d[44]), "=f"(d[45]), "=f"(d[46]), "=f"(d[47]), "=f"(d[48]), "=f"(d[49]), "=f"(d[50]), "=f"(d[51]), "=f"(d[52]), "=f"(d[53]), "=f"(d[54]), "=f"(d[55]), "=f"(d[56]), "=f"(d[57]), "=f"(d[58]), "=f"(d[59]), "=f"(d[60]), "=f"(d[61]), "=f"(d[62]), "=f"(d[63]), "=f"(d[64]), "=f"(d[65]), "=f"(d[66]), "=f"(d[67]), "=f"(d[68]), "=f"(d[69]), "=f"(d[70]), "=f"(d[71]), "=f"(d[72]), "=f"(d[73]), "=f"(d[74]), "=f"(d[75]), "=f"(d[76]), "=f"(d[77]), "=f"(d[78]), "=f"(d[79]), "=f"(d[80]), "=f"(d[81]), "=f"(d[82]), "=f"(d[83]), "=f"(d[84]), "=f"(d[85]), "=f"(d[86]), "=f"(d[87]), "=f"(d[88]), "=f"(d[89]), "=f"(d[90]), "=f"(d[91]), "=f"(d[92]), "=f"(d[93]), "=f"(d[94]), "=f"(d[95])
    : "l"(descA), "l"(descB));
}

__device__ __forceinline__ void wgmma_n192_rs_tb1(float* d, uint32_t a0, uint32_t a1, uint64_t descB) {
  asm volatile("{\n.reg .pred p;\nsetp.eq.b32 p, 0, 0;\n"
    "wgmma.mma_async.sync.aligned.m64n192k16.f32.bf16.bf16 {%0, %1, %2, %3, %4, %5, %6, %7, %8, %9, %10, %11, %12, %13, %14, %15, %16, %17, %18, %19, %20, %21, %22, %23, %24, %25, %26, %27, %28, %29, %30, %31, %32, %33, %34, %35, %36, %37, %38, %39, %40, %41, %42, %43, %44, %45, %46, %47, %48, %49, %50, %51, %52, %53, %54, %55, %56, %57, %58, %59, %60, %61, %62, %63, %64, %65, %66, %67, %68, %69, %70, %71, %72, %73, %74, %75, %76, %77, %78, %79, %80, %81, %82, %83, %84, %85, %86, %87, %88, %89, %90, %91, %92, %93, %94, %95}, {%96, %97, %98, %98}, %99, p, 1, 1, 1;\n}\n"
    : "+f"(d[0]), "+f"(d[1]), "+f"(d[2]), "+f"(d[3]), "+f"(d[4]), "+f"(d[5]), "+f"(d[6]), "+f"(d[7]), "+f"(d[8]), "+f"(d[9]), "+f"(d[10]), "+f"(d[11]), "+f"(d[12]), "+f"(d[13]), "+f"(d[14]), "+f"(d[15]), "+f"(d[16]), "+f"(d[17]), "+f"(d[18]), "+f"(d[19]), "+f"(d[20]), "+f"(d[21]), "+f"(d[22]), "+f"(d[23]), "+f"(d[24]), "+f"(d[25]), "+f"(d[26]), "+f"(d[27]), "+f"(d[28]), "+f"(d[29]), "+f"(d[30]), "+f"(d[31]), "+f"(d[32]), "+f"(d[33]), "+f"(d[34]), "+f"(d[35]), "+f"(d[36]), "+f"(d[37]), "+f"(d[38]), "+f"(d[39]), "+f"(d[40]), "+f"(d[41]), "+f"(d[42]), "+f"(d[43]), "+f"(d[44]), "+f"(d[45]), "+f"(d[46]), "+f"(d[47]), "+f"(d[48]), "+f"(d[49]), "+f"(d[50]), "+f"(d[51]), "+f"(d[52]), "+f"(d[53]), "+f"(d[54]), "+f"(d[55]), "+f"(d[56]), "+f"(d[57]), "+f"(d[58]), "+f"(d[59]), "+f"(d[60]), "+f"(d[61]), "+f"(d[62]), "+f"(d[63]), "+f"(d[64]), "+f"(d[65]), "+f"(d[66]), "+f"(d[67]), "+f"(d[68]), "+f"(d[69]), "+f"(d[70]), "+f"(d[71]), "+f"(d[72]), "+f"(d[73]), "+f"(d[74]), "+f"(d[75]), "+f"(d[76]), "+f"(d[77]), "+f"(d[78]), "+f"(d[79]), "+f"(d[80]), "+f"(d[81]), "+f"(d[82]), "+f"(d[83]), "+f"(d[84]), "+f"(d[85]), "+f"(d[86]), "+f"(d[87]), "+f"(d[88]), "+f"(d[89]), "+f"(d[90]), "+f"(d[91]), "+f"(d[92]), "+f"(d[93]), "+f"(d[94]), "+f"(d[95])
    : "r"(a0), "r"(a1), "r"(0u), "l"(descB));
}

__device__ __forceinline__ void wgmma_n128_ssz_ta0_tb1(float* d, uint64_t descA, uint64_t descB) {
  asm volatile("{\n.reg .pred p;\nsetp.ne.b32 p, 0, 0;\n"
    "wgmma.mma_async.sync.aligned.m64n128k16.f32.bf16.bf16 {%0, %1, %2, %3, %4, %5, %6, %7, %8, %9, %10, %11, %12, %13, %14, %15, %16, %17, %18, %19, %20, %21, %22, %23, %24, %25, %26, %27, %28, %29, %30, %31, %32, %33, %34, %35, %36, %37, %38, %39, %40, %41, %42, %43, %44, %45, %46, %47, %48, %49, %50, %51, %52, %53, %54, %55, %56, %57, %58, %59, %60, %61, %62, %63}, %64, %65, p, 1, 1, 0, 1;\n}\n"
    : "=f"(d[0]), "=f"(d[1]), "=f"(d[2]), "=f"(d[3]), "=f"(d[4]), "=f"(d[5]), "=f"(d[6]), "=f"(d[7]), "=f"(d[8]), "=f"(d[9]), "=f"(d[10]), "=f"(d[11]), "=f"(d[12]), "=f"(d[13]), "=f"(d[14]), "=f"(d[15]), "=f"(d[16]), "=f"(d[17]), "=f"(d[18]), "=f"(d[19]), "=f"(d[20]), "=f"(d[21]), "=f"(d[22]), "=f"(d[23]), "=f"(d[24]), "=f"(d[25]), "=f"(d[26]), "=f"(d[27]), "=f"(d[28]), "=f"(d[29]), "=f"(d[30]), "=f"(d[31]), "=f"(d[32]), "=f"(d[33]), "=f"(d[34]), "=f"(d[35]), "=f"(d[36]), "=f"(d[37]), "=f"(d[38]), "=f"(d[39]), "=f"(d[40]), "=f"(d[41]), "=f"(d[42]), "=f"(d[43]), "=f"(d[44]), "=f"(d[45]), "=f"(d[46]), "=f"(d[47]), "=f"(d[48]), "=f"(d[49]), "=f"(d[50]), "=f"(d[51]), "=f"(d[52]), "=f"(d[53]), "=f"(d[54]), "=f"(d[55]), "=f"(d[56]), "=f"(d[57]), "=f"(d[58]), "=f"(d[59]), "=f"(d[60]), "=f"(d[61]), "=f"(d[62]), "=f"(d[63])
    : "l"(descA), "l"(descB));
}

__device__ __forceinline__ void wgmma_n64_ss_ta0_tb0(float* d, uint64_t descA, uint64_t descB, int scaleD) {
  asm volatile("{\n.reg .pred p;\nsetp.ne.b32 p, %34, 0;\n"
    "wgmma.mma_async.sync.aligned.m64n64k16.f32.bf16.bf16 {%0, %1, %2, %3, %4, %5, %6, %7, %8, %9, %10, %11, %12, %13, %14, %15, %16, %17, %18, %19, %20, %21, %22, %23, %24, %25, %26, %27, %28, %29, %30, %31}, %32, %33, p, 1, 1, 0, 0;\n}\n"
    : "+f"(d[0]), "+f"(d[1]), "+f"(d[2]), "+f"(d[3]), "+f"(d[4]), "+f"(d[5]), "+f"(d[6]), "+f"(d[7]), "+f"(d[8]), "+f"(d[9]), "+f"(d[10]), "+f"(d[11]), "+f"(d[12]), "+f"(d[13]), "+f"(d[14]), "+f"(d[15]), "+f"(d[16]), "+f"(d[17]), "+f"(d[18]), "+f"(d[19]), "+f"(d[20]), "+f"(d[21]), "+f"(d[22]), "+f"(d[23]), "+f"(d[24]), "+f"(d[25]), "+f"(d[26]), "+f"(d[27]), "+f"(d[28]), "+f"(d[29]), "+f"(d[30]), "+f"(d[31])
    : "l"(descA), "l"(descB), "r"(scaleD));
}

__device__ __forceinline__ void wgmma_n64_ssz_ta0_tb0(float* d, uint64_t descA, uint64_t descB) {
  asm volatile("{\n.reg .pred p;\nsetp.ne.b32 p, 0, 0;\n"
    "wgmma.mma_async.sync.aligned.m64n64k16.f32.bf16.bf16 {%0, %1, %2, %3, %4, %5, %6, %7, %8, %9, %10, %11, %12, %13, %14, %15, %16, %17, %18, %19, %20, %21, %22, %23, %24, %25, %26, %27, %28, %29, %30, %31}, %32, %33, p, 1, 1, 0, 0;\n}\n"
    : "=f"(d[0]), "=f"(d[1]), "=f"(d[2]), "=f"(d[3]), "=f"(d[4]), "=f"(d[5]), "=f"(d[6]), "=f"(d[7]), "=f"(d[8]), "=f"(d[9]), "=f"(d[10]), "=f"(d[11]), "=f"(d[12]), "=f"(d[13]), "=f"(d[14]), "=f"(d[15]), "=f"(d[16]), "=f"(d[17]), "=f"(d[18]), "=f"(d[19]), "=f"(d[20]), "=f"(d[21]), "=f"(d[22]), "=f"(d[23]), "=f"(d[24]), "=f"(d[25]), "=f"(d[26]), "=f"(d[27]), "=f"(d[28]), "=f"(d[29]), "=f"(d[30]), "=f"(d[31])
    : "l"(descA), "l"(descB));
}

__device__ __forceinline__ void wgmma_n80_ss_ta0_tb0(float* d, uint64_t descA, uint64_t descB, int scaleD) {
  asm volatile("{\n.reg .pred p;\nsetp.ne.b32 p, %42, 0;\n"
    "wgmma.mma_async.sync.aligned.m64n80k16.f32.bf16.bf16 {%0, %1, %2, %3, %4, %5, %6, %7, %8, %9, %10, %11, %12, %13, %14, %15, %16, %17, %18, %19, %20, %21, %22, %23, %24, %25, %26, %27, %28, %29, %30, %31, %32, %33, %34, %35, %36, %37, %38, %39}, %40, %41, p, 1, 1, 0, 0;\n}\n"
    : "+f"(d[0]), "+f"(d[1]), "+f"(d[2]), "+f"(d[3]), "+f"(d[4]), "+f"(d[5]), "+f"(d[6]), "+f"(d[7]), "+f"(d[8]), "+f"(d[9]), "+f"(d[10]), "+f"(d[11]), "+f"(d[12]), "+f"(d[13]), "+f"(d[14]), "+f"(d[15]), "+f"(d[16]), "+f"(d[17]), "+f"(d[18]), "+f"(d[19]), "+f"(d[20]), "+f"(d[21]), "+f"(d[22]), "+f"(d[23]), "+f"(d[24]), "+f"(d[25]), "+f"(d[26]), "+f"(d[27]), "+f"(d[28]), "+f"(d[29]), "+f"(d[30]), "+f"(d[31]), "+f"(d[32]), "+f"(d[33]), "+f"(d[34]), "+f"(d[35]), "+f"(d[36]), "+f"(d[37]), "+f"(d[38]), "+f"(d[39])
    : "l"(descA), "l"(descB), "r"(scaleD));
}

__device__ __forceinline__ void wgmma_n32_rs_tb1(float* d, const uint32_t* a, uint64_t descB, int scaleD) {
  asm volatile("{\n.reg .pred p;\nsetp.ne.b32 p, %21, 0;\n"
    "wgmma.mma_async.sync.aligned.m64n32k16.f32.bf16.bf16 {%0, %1, %2, %3, %4, %5, %6, %7, %8, %9, %10, %11, %12, %13, %14, %15}, {%16, %17, %18, %19}, %20, p, 1, 1, 1;\n}\n"
    : "+f"(d[0]), "+f"(d[1]), "+f"(d[2]), "+f"(d[3]), "+f"(d[4]), "+f"(d[5]), "+f"(d[6]), "+f"(d[7]), "+f"(d[8]), "+f"(d[9]), "+f"(d[10]), "+f"(d[11]), "+f"(d[12]), "+f"(d[13]), "+f"(d[14]), "+f"(d[15])
    : "r"(a[0]), "r"(a[1]), "r"(a[2]), "r"(a[3]), "l"(descB), "r"(scaleD));
}

__device__ __forceinline__ uint32_t pack_bf16x2(float lo, float hi) {
  uint32_t r;
  asm("cvt.rn.bf16x2.f32 %0, %1, %2;" : "=r"(r) : "f"(hi), "f"(lo));
  return r;
}
__device__ __forceinline__ float bf_lo(uint32_t p) { return __uint_as_float(p << 16); }
__device__ __forceinline__ float bf_hi(uint32_t p) { return __uint_as_float(p & 0xffff0000u); }
__device__ __forceinline__ float bf16_round(float v) { return __bfloat162float(__float2bfloat16_rn(v)); }
__device__ __forceinline__ float ex2_approx(float x) {
  float r;
  asm("ex2.approx.ftz.f32 %0, %1;" : "=f"(r) : "f"(x));
  return r;
}
__device__ __forceinline__ float rcp_fast(float x) {
  float r;
  asm("rcp.approx.ftz.f32 %0, %1;" : "=f"(r) : "f"(x));
  return r;
}
__device__ __forceinline__ void ldmatrix_x4(uint32_t (&r)[4], uint32_t addr) {
  asm volatile("ldmatrix.sync.aligned.m8n8.x4.shared.b16 {%0,%1,%2,%3}, [%4];"
               : "=r"(r[0]), "=r"(r[1]), "=r"(r[2]), "=r"(r[3])
               : "r"(addr)
               : "memory");
}
__device__ __forceinline__ void stmatrix_x4(uint32_t addr, uint32_t r0, uint32_t r1, uint32_t r2, uint32_t r3) {
  asm volatile("stmatrix.sync.aligned.m8n8.x4.shared.b16 [%0], {%1,%2,%3,%4};" ::"r"(addr), "r"(r0), "r"(r1), "r"(r2),
               "r"(r3));
}
__device__ __forceinline__ uint32_t add_bf16x2(uint32_t a, uint32_t b) {
  uint32_t r;
  asm("add.rn.bf16x2 %0, %1, %2;" : "=r"(r) : "r"(a), "r"(b));
  return r;
}
__device__ __forceinline__ uint4 lds128(uint32_t addr) {
  uint4 v;
  asm volatile("ld.shared.v4.b32 {%0,%1,%2,%3}, [%4];" : "=r"(v.x), "=r"(v.y), "=r"(v.z), "=r"(v.w) : "r"(addr) : "memory");
  return v;
}
__device__ __forceinline__ uint32_t lds32(uint32_t addr) {
  uint32_t v;
  asm volatile("ld.shared.b32 %0, [%1];" : "=r"(v) : "r"(addr) : "memory");
  return v;
}
__device__ __forceinline__ void sts32(uint32_t addr, uint32_t v) {
  asm volatile("st.shared.b32 [%0], %1;" ::"r"(addr), "r"(v) : "memory");
}

__device__ __forceinline__ unsigned ld_acquire_u32(const unsigned* p) {
  unsigned v;
  asm volatile("ld.acquire.gpu.global.u32 %0, [%1];" : "=r"(v) : "l"(p) : "memory");
  return v;
}
__device__ __forceinline__ void red_relaxed_add(unsigned* p, unsigned v) {
  asm volatile("red.relaxed.gpu.global.add.u32 [%0], %1;" ::"l"(p), "r"(v) : "memory");
}
__device__ __forceinline__ void wait_ge(const unsigned* p, unsigned target) {
#pragma unroll 1
  for (uint32_t it = 0; it < (1u << 17); ++it) {
    if ((int)(ld_acquire_u32(p) - target) >= 0) return;
  }
}

__device__ __forceinline__ void wait_ge2(const unsigned* p, unsigned t0, unsigned t1) {
#pragma unroll 1
  for (uint32_t it = 0; it < (1u << 17); ++it) {
    unsigned long long v;
    asm volatile("ld.acquire.gpu.global.u64 %0, [%1];" : "=l"(v) : "l"(p) : "memory");
    if ((int)((unsigned)v - t0) >= 0 && (int)((unsigned)(v >> 32) - t1) >= 0) return;
  }
}

#define PDEPTH 1
#define RELNS 100
#define HDELAY 500
#define PUBPOS 0
#define PGAP 100
template <bool SLOW>
__device__ __forceinline__ void wait_mask(const unsigned* f, int cnt, unsigned target, uint32_t need, uint32_t& seen, int lane) {
  if ((seen & need) == need) return;
  const unsigned* fp = f + (lane & (cnt - 1));
#pragma unroll 1
  for (uint32_t it = 0; it < (1u << 17); ++it) {
    seen = __ballot_sync(0xffffffffu, (int)(ld_acquire_u32(fp) - target) >= 0);
    if ((seen & need) == need) break;
    if (SLOW) __nanosleep(400);
  }
  fence_proxy_async_all();
}
__device__ __forceinline__ void wait_lanes(const unsigned* fp, unsigned target, uint32_t need, uint32_t& seen) {
  if ((seen & need) == need) return;
  unsigned v[PDEPTH];
#pragma unroll
  for (int i = 0; i < PDEPTH; i++) {
    asm volatile("ld.relaxed.gpu.global.u32 %0, [%1];" : "=r"(v[i]) : "l"(fp) : "memory");
    if (i + 1 < PDEPTH) __nanosleep(PGAP);
  }
#pragma unroll 1
  for (uint32_t it = 0; it < (1u << 16); ++it) {
#pragma unroll
    for (int i = 0; i < PDEPTH; i++) {
      seen |= __ballot_sync(0xffffffffu, (int)(v[i] - target) >= 0);
      if ((seen & need) == need) goto done;
      asm volatile("ld.relaxed.gpu.global.u32 %0, [%1];" : "=r"(v[i]) : "l"(fp) : "memory");
    }
  }
done:
  fence_proxy_async_all();
}
__device__ __forceinline__ float4 ld_rec(const float4* p) {
  float4 v;
  asm volatile("ld.relaxed.gpu.global.v4.f32 {%0,%1,%2,%3}, [%4];" : "=f"(v.x), "=f"(v.y), "=f"(v.z), "=f"(v.w) : "l"(p) : "memory");
  return v;
}
__device__ __forceinline__ void st_rec(float4* p, float a, float b, float c, unsigned tag) {
  asm volatile("st.relaxed.gpu.global.v4.f32 [%0], {%1,%2,%3,%4};" ::"l"(p), "f"(a), "f"(b), "f"(c), "f"(__uint_as_float(tag)) : "memory");
}
template <int N>
__device__ __forceinline__ float4 sum_recs(const float4* p, int stride, unsigned tag) {
  float4 s;
#pragma unroll 1
  for (uint32_t it = 0; it < (1u << 17); ++it) {
    float4 v[N];
#pragma unroll
    for (int t = 0; t < N; t++) v[t] = ld_rec(p + t * stride);
    bool ok = true;
    s = make_float4(0.f, 0.f, 0.f, 0.f);
#pragma unroll
    for (int t = 0; t < N; t++) {
      ok &= __float_as_uint(v[t].w) == tag;
      s.x += v[t].x;
      s.y += v[t].y;
      s.z += v[t].z;
    }
    if (ok) break;
    __nanosleep(200);
  }
  return s;
}

__device__ __forceinline__ int fresh_tid() {
  int t;
  asm volatile("mov.u32 %0, %%tid.x;" : "=r"(t));
  return t;
}
#define PHASE_IDS                                  \
  const int tid_ = fresh_tid();                    \
  const int lane = tid_ & 31, wwarp = __shfl_sync(0xffffffffu, (tid_ >> 5) & 3, 0), tid = tid_ & 127; \
  const int g = lane >> 2, c = lane & 3;           \
  (void)tid; (void)g; (void)c; (void)wwarp;

#define STAMPW(cond, i) do { } while (0)
#define STAMP(cond, i) do { } while (0)
#define STA(i) do { } while (0)
#define GTL(i) do { } while (0)
#define GTLX(c, i) do { } while (0)
#define TGET(v) do { } while (0)
#define TPUT(c, i, v) do { } while (0)

constexpr float SM_C = 0.17677669529663687f * 1.4426950408889634f;

constexpr uint32_t OA_TILE = SBASE + OFF_SLOT + 16384;

__device__ __forceinline__ void sched_fence(uint32_t never) {
  asm volatile("{\n.reg .pred p;\nsetp.ne.u32 p, %0, 0;\n@p exit;\n}\n" ::"r"(never) : "memory");
}

template <int K0, int K1>
__device__ __forceinline__ void attn_exp(float (&s)[32]) {
#pragma unroll
  for (int k = K0; k < K1; k++) s[k] = ex2_approx(s[k]);
}
#define ASPL 16
#define ASPM 6
template <int MODE, bool NEXT>
__device__ __forceinline__ void attn_unit(float (&s)[32], float (&sn)[32], float (&o)[16], float (&l)[2], bool valid,
                                          uint32_t vdesc, uint32_t qdesc, uint32_t kdesc, uint32_t tri, int w,
                                          uint32_t hbar, uint32_t hpar, uint32_t rel, uint32_t zero, bool stampon = false) {
  float x[9][2];
  if (MODE == 0) {
    attn_exp<0, ASPL>(s);
  } else {
#pragma unroll
    for (int e = 0; e < 2; e++) {
#pragma unroll
      for (int j = 0; j < 4; j++) x[j][e] = MODE == 1 ? s[4 * j + 2 + e] : s[16 + 4 * j + e];
      x[4][e] = MODE == 1 ? s[e] : s[30 + e];
      x[5][e] = MODE == 1 ? s[18 + e] : s[12 + e];
#pragma unroll
      for (int u = 1; u < 4; u++)
        x[5 + u][e] = MODE == 1 ? (w >= u ? s[4 * u + e] : s[4 * (8 - u) + 2 + e]) : (w >= u ? s[4 * (7 - u) + 2 + e] : s[4 * (u - 1) + e]);
    }
#pragma unroll
    for (int k = 0; k < 2 * ASPM; k++) x[k >> 1][k & 1] = ex2_approx(x[k >> 1][k & 1]);
  }
  sched_fence(zero);
  if (hbar) mbar_wait(hbar, hpar);
  wgmma_wait<0>();
  if (rel) mbar_arrive(rel);
  if (NEXT) {
    wgmma_fence();
    wgmma_n64_ssz_ta0_tb0(sn, desc_lo(qdesc), desc_lo(kdesc));
    wgmma_n64_ss_ta0_tb0(sn, desc_lo(qdesc + 2), desc_lo(kdesc + 2), 1);
    wgmma_commit();
    sched_fence(zero);
  }
  uint32_t p[16];
  if (MODE == 0) {
    attn_exp<ASPL, 32>(s);
#pragma unroll
    for (int k = 0; k < 16; k++) p[k] = pack_bf16x2(s[2 * k], s[2 * k + 1]);
  } else {
#pragma unroll
    for (int k = 2 * ASPM; k < 18; k++) x[k >> 1][k & 1] = ex2_approx(x[k >> 1][k & 1]);
    const uint32_t tm = MODE == 1 ? tri : ~tri;
#pragma unroll
    for (int j = 0; j < 4; j++) {
      p[MODE == 1 ? 2 * j + 1 : 8 + 2 * j] = pack_bf16x2(x[j][0], x[j][1]);
      p[MODE == 1 ? 8 + 2 * j : 2 * j + 1] = 0u;
    }
    p[MODE == 1 ? 0 : 15] = pack_bf16x2(x[4][0], x[4][1]) & (w == 0 ? tm : 0xffffffffu);
    p[MODE == 1 ? 9 : 6] = pack_bf16x2(x[5][0], x[5][1]) & (w == 3 ? tm : 0xffffffffu);
#pragma unroll
    for (int u = 1; u < 4; u++) {
      const uint32_t q = pack_bf16x2(x[5 + u][0], x[5 + u][1]);
      p[MODE == 1 ? 2 * u : 2 * (7 - u) + 1] = q & (w > u ? 0xffffffffu : (w == u ? tm : 0u));
      p[MODE == 1 ? 2 * (8 - u) + 1 : 2 * (u - 1)] = q & (w < u - 1 ? 0xffffffffu : (w == u - 1 ? tm : 0u));
    }
  }
  wgmma_fence();
#pragma unroll
  for (int k = 0; k < 4; k++) wgmma_n32_rs_tb1(o, p + 4 * k, desc_lo(vdesc + k * 128), 1);
  wgmma_commit();
#pragma unroll
  for (int r = 0; r < 2; r++) {
    float t = 0.f;
#pragma unroll
    for (int hf = 0; hf < 2; hf++) {
      if (MODE != 0 && r == MODE - 1 && hf == 2 - MODE) continue;
      const uint32_t* q = p + 8 * hf + r;
      const uint32_t v = add_bf16x2(add_bf16x2(q[0], q[2]), add_bf16x2(q[4], q[6]));
      t = (MODE != 0 && r == MODE - 1) || hf == 0 ? bf_lo(v) + bf_hi(v) : t + (bf_lo(v) + bf_hi(v));
    }
    if (valid) l[r] += t;
  }
  if (NEXT) {
    wgmma_wait<1>();
    reg_fence<32>(sn);
  }
}

__device__ __forceinline__ void attn_a_slow(const uint8_t* __restrict__ kvimg, int L, int gb, int hp,
                                         int hh, int wwarp, int lane) {
  constexpr uint32_t sq = SBASE + OFF_SLOT + 3 * 16384;
  const unsigned ep = (*(volatile unsigned*)(g_flags + F_DONE)) / NCTA;
  wait_ge2(g_flags + F_KV + (gb * 16 + hp) * KSTR, 4u * ep + L + 1u, 2u * ep + (L >> 1) + 1u);
#pragma unroll 1
  for (int t = 0; t < 32; t++) {
    const int row = (t >> 4) * 64 + ((t & 8) ? 7 - wwarp : wwarp) * 8 + (t & 7);
    const int qpos = gb * 128 + row;
    const uint32_t qaddr = sq + ((t >> 4) * 64 + wwarp * 16 + (t & 15)) * 128;
    float mx = -INFINITY, sum = 0.f, acc = 0.f;
#pragma unroll 1
    for (int pass = 0; pass < 2; pass++) {
#pragma unroll 1
      for (int j = 0; j < 8; j++) {
        const int kp = qpos - (lane + 32 * j);
        const uint8_t* kr = kvimg + ((size_t)((kp >> 7) * 16 + hp) * 2 + ((kp >> 6) & 1)) * 16384 + (kp & 63) * 128;
        float d = -INFINITY;
        if (kp >= 0) {
          d = 0.f;
#pragma unroll 1
          for (int q = 0; q < 4; q++) {
            const uint4 kv = __ldcg(reinterpret_cast<const uint4*>(kr + (((hh * 4 + q) ^ (kp & 7)) << 4)));
            const uint4 qv = lds128(qaddr + (((hh * 4 + q) ^ (row & 7)) << 4));
            const uint32_t kw[4] = {kv.x, kv.y, kv.z, kv.w}, qw[4] = {qv.x, qv.y, qv.z, qv.w};
#pragma unroll
            for (int e = 0; e < 4; e++) d = fmaf(bf_lo(kw[e]), bf_lo(qw[e]), fmaf(bf_hi(kw[e]), bf_hi(qw[e]), d));
          }
        }
        if (pass == 0) {
          mx = fmaxf(mx, d);
        } else {
          const float ev = ex2_approx(d - mx);
          sum += ev;
          const float pv = bf16_round(ev);
#pragma unroll 1
          for (int kk = 0; kk < 32; kk++) {
            const float pk = __shfl_sync(0xffffffffu, pv, kk);
            const int k2 = qpos - (kk + 32 * j);
            if (k2 >= 0) {
              const uint8_t* vr = kvimg + ((size_t)((k2 >> 7) * 16 + hp) * 2 + ((k2 >> 6) & 1)) * 16384 + 8192 + (k2 & 63) * 128;
              const unsigned short vv =
                  __ldcg(reinterpret_cast<const unsigned short*>(vr + (((hh * 4 + (lane >> 3)) ^ (k2 & 7)) << 4) + (lane & 7) * 2));
              acc = fmaf(pk, __uint_as_float((uint32_t)vv << 16), acc);
            }
          }
        }
      }
      if (pass == 0) {
#pragma unroll
        for (int o = 16; o > 0; o >>= 1) mx = fmaxf(mx, __shfl_xor_sync(0xffffffffu, mx, o));
      }
    }
#pragma unroll
    for (int o = 16; o > 0; o >>= 1) sum += __shfl_xor_sync(0xffffffffu, sum, o);
    acc *= rcp_fast(sum);
    const float hi = __shfl_down_sync(0xffffffffu, acc, 1);
    __syncwarp();
    if ((lane & 1) == 0)
      sts32(OA_TILE + row * 128 + (((hh * 4 + (lane >> 3)) ^ (row & 7)) << 4) + (lane & 7) * 2, pack_bf16x2(acc, hi));
    __syncwarp();
  }
}

__device__ __forceinline__ void store_o(const float (&o)[16], const float (&inv)[2], uint32_t rowaddr, int hh, int lane) {
  const int mat = lane >> 3, r7 = lane & 7;
#pragma unroll
  for (int jp = 0; jp < 2; jp++)
    stmatrix_x4(rowaddr + (((hh * 4 + 2 * jp + (mat >> 1)) ^ r7) << 4),
                pack_bf16x2(o[8 * jp] * inv[0], o[8 * jp + 1] * inv[0]),
                pack_bf16x2(o[8 * jp + 2] * inv[1], o[8 * jp + 3] * inv[1]),
                pack_bf16x2(o[8 * jp + 4] * inv[0], o[8 * jp + 5] * inv[0]),
                pack_bf16x2(o[8 * jp + 6] * inv[1], o[8 * jp + 7] * inv[1]));
}

__device__ __forceinline__ void attention_a(int HH, int L, int gb, int hp, uint32_t par0, uint32_t parA, int wwarp, int lane,
                                            uint32_t zero) {
  constexpr uint32_t bars = SBASE + OFF_BAR;
  const uint32_t dslot = ((SBASE + OFF_SLOT) >> 4) + 0x10000u + HH * 4;
  const uint32_t dq = dslot + 3 * 1024;
  float sa[32], sb[32], o[2][16], l[2][2];
  auto dch = [&](int n) { return dslot + 1024u * (n % 3 == 0 ? 1 : (n % 3 == 1 ? 0 : 2)); };
  wgmma_fence();
  wgmma_n64_ssz_ta0_tb0(sa, desc_lo(dq + 512), desc_lo(dch(0)));
  wgmma_n64_ss_ta0_tb0(sa, desc_lo(dq + 512 + 2), desc_lo(dch(0) + 2), 1);
  wgmma_commit();
#pragma unroll
  for (int h = 0; h < 2; h++) {
#pragma unroll
    for (int i = 0; i < 16; i++) o[h][i] = 0.f;
    l[h][0] = l[h][1] = 0.f;
  }
  const int dg = (lane >> 2) - 2 * (lane & 3);
  const uint32_t tri = (dg >= 0 ? 0xffffu : 0u) | (dg >= 1 ? 0xffff0000u : 0u);
  const int nmax = 2 * gb + 1;
  wgmma_wait<0>();
  reg_fence<32>(sa);
#define STON false
  auto publish = [&]() {
    if (HH && wwarp == 1 && lane == 0) {
      bulk_wait0();
      fence_proxy_async_all();
      red_relaxed_add(g_flags + F_KV + (gb * 16 + hp) * KSTR + 1, 1u);
    }
    __syncwarp();
  };
#define ATT_STEP(i, MODE)                                                                                            \
  attn_unit<MODE, true>(sa, sb, o[1], l[1], i <= nmax, dch(i) + 512, dq, dch(i + 1), tri, wwarp,                     \
                        i >= 1 ? bars + 8u * (B_HALO + i - 1) : 0u, i == 1 ? par0 : parA, 0u, zero, STON); if (i == 0 && PUBPOS == 0) publish();                \
  attn_unit<MODE, (i < 4)>(sb, sa, o[0], l[0], i + 1 <= nmax, dch(i + 1) + 512, dq + 512, dch(i + 1), tri, wwarp, 0u, \
                           0u, i < 3 && lane == 0 ? bars + 8u * (B_REL + i) : 0u, zero);
  ATT_STEP(0, 1)
  if (PUBPOS == 1) publish();
  ATT_STEP(1, 0)
  ATT_STEP(2, 0)
  ATT_STEP(3, 0)
  ATT_STEP(4, 2)
#undef ATT_STEP
  const uint32_t ra = OA_TILE + (((lane & 8) ? 7 - wwarp : wwarp) * 8 + (lane & 7)) * 128;
  bool bad = false;
#pragma unroll
  for (int h = 1; h >= 0; h--) {
    float inv[2];
#pragma unroll
    for (int r = 0; r < 2; r++) {
      float v = l[h][r];
      v += __shfl_xor_sync(0xffffffffu, v, 1);
      v += __shfl_xor_sync(0xffffffffu, v, 2);
      bad |= !(v <= 1.152921504606846976e18f && v >= 8.673617379884035e-19f);
      inv[r] = rcp_fast(v);
    }
    if (h == 0) wgmma_wait<0>();
    reg_fence<16>(o[h]);
    store_o(o[h], inv, ra + h * 8192, HH, lane);
  }
  if (HH == 0) GTL(45);
  if (__any_sync(0xffffffffu, bad)) attn_a_slow(g_kvA[L >> 1][0][0][0], L, gb, hp, HH, wwarp, lane);
}

constexpr uint32_t KB_ROW0 = SBASE + OFF_SLOT + 2048, VB_ROW0 = SBASE + OFF_SLOT + 24576 + 2048;

__device__ __forceinline__ void attnB_soft(const float (&s)[40], int wwarp, int D, bool edge, bool odd,
                                           uint32_t (&p)[5][4], float (&sum)[2]) {
  float z[2][3];
#define GATHER_(W)                                                                                  \
  _Pragma("unroll") for (int r = 0; r < 2; r++) _Pragma("unroll") for (int t = 0; t < 3; t++)       \
      z[r][t] = odd ? s[4 * (2 * W + r + t) + 2 * r + 1] : s[4 * (2 * W + r + t) + 2 * r];
  if (wwarp < 2) {
    if (wwarp == 0) { GATHER_(0) } else { GATHER_(1) }
  } else {
    if (wwarp == 2) { GATHER_(2) } else { GATHER_(3) }
  }
#undef GATHER_
  float y[2];
  y[0] = D >= 2 ? z[0][0] : z[0][2];
  y[1] = D >= 2 ? z[1][0] : z[1][2];
  if (edge) {
    z[0][1] = -INFINITY;
    if (D >= 2) y[0] = y[1] = -INFINITY;
  }
  float m0 = fmaxf(z[0][1], y[0]), m1 = fmaxf(z[1][1], y[1]);
  m0 = fmaxf(m0, __shfl_xor_sync(0xffffffffu, m0, 1));
  m1 = fmaxf(m1, __shfl_xor_sync(0xffffffffu, m1, 1));
  m0 = fmaxf(m0, __shfl_xor_sync(0xffffffffu, m0, 2));
  m1 = fmaxf(m1, __shfl_xor_sync(0xffffffffu, m1, 2));
  const float e00 = ex2_approx(z[0][1] - m0), e01 = ex2_approx(y[0] - m0);
  const float e10 = ex2_approx(z[1][1] - m1), e11 = ex2_approx(y[1] - m1);
  sum[0] = e00 + e01;
  sum[1] = e10 + e11;
  const int sh = odd ? 16 : 0;
  const uint32_t a0 = pack_bf16x2(e00, 0.f) << sh, a1 = pack_bf16x2(e10, 0.f) << sh;
  const uint32_t b0 = pack_bf16x2(e01, 0.f) << sh, b1 = pack_bf16x2(e11, 0.f) << sh;
  const int kb = wwarp + (D >= 2 ? 0 : 1);
#pragma unroll
  for (int k = 0; k < 5; k++) {
    p[k][0] = k == kb ? b0 : 0u;
    p[k][1] = k == wwarp + 1 ? a1 : 0u;
    p[k][2] = k == wwarp ? a0 : 0u;
    p[k][3] = k == kb ? b1 : 0u;
#pragma unroll
    for (int q = 0; q < 4; q++) asm volatile("" : "+r"(p[k][q]));
  }
}

__device__ __forceinline__ void attnB_s(float (&s)[40], int HH, int h) {
  constexpr uint32_t sq = SBASE + OFF_SLOT + 3 * 16384;
#pragma unroll
  for (int ks = 0; ks < 2; ks++)
    wgmma_n80_ss_ta0_tb0(s, make_desc(sq + h * 8192 + HH * 64 + ks * 32, 16),
                         make_desc(KB_ROW0 + h * 8192 - 2048 + HH * 64 + ks * 32, 16), ks);
}
__device__ __forceinline__ void attnB_pv(float (&o)[16], const uint32_t (&p)[5][4], int HH, int h) {
#pragma unroll
  for (int k = 0; k < 5; k++)
    wgmma_n32_rs_tb1(o, p[k], make_desc(VB_ROW0 + h * 8192 - 2048 + k * 2048 + HH * 64, 16), k);
}

__device__ __forceinline__ void attention_b(int HH, int gb, uint32_t par0, int wwarp, int lane) {
  constexpr uint32_t bars = SBASE + OFF_BAR, sq = SBASE + OFF_SLOT + 3 * 16384;
  float s[40];
  reg_define<40>(s);
  wgmma_fence();
  attnB_s(s, HH, 1);
  wgmma_commit();
  const int g = lane >> 2;
  const bool odd = g & 1;
  const int D = 2 * (lane & 3) + (g & 1) - g;
  const uint32_t ra = sq + (wwarp * 16 + ((lane >> 3) & 1) * 8 + (lane & 7)) * 128;
  wgmma_wait<0>();
  reg_fence<40>(s);
#pragma unroll 1
  for (int h = 1; h >= 0; h--) {
    float o[16], inv[2];
    uint32_t p[5][4];
    reg_define<16>(o);
    attnB_soft(s, wwarp, D, h == 0 && gb == 0 && wwarp == 0, odd, p, inv);
    if (h == 1) {
      mbar_wait(bars + 8u * B_HALO, par0);
      wgmma_fence();
      attnB_s(s, HH, 0);
    }
    wgmma_fence();
    attnB_pv(o, p, HH, h);
    wgmma_commit();
#pragma unroll
    for (int r = 0; r < 2; r++) {
      inv[r] += __shfl_xor_sync(0xffffffffu, inv[r], 1);
      inv[r] += __shfl_xor_sync(0xffffffffu, inv[r], 2);
      inv[r] = rcp_fast(inv[r]);
    }
    wgmma_wait<0>();
    reg_fence<40>(s);
    reg_fence<16>(o);
    store_o(o, inv, ra + h * 8192, HH, lane);
  }
}

#define KTQM 0
#define TRICKLE 300
#define CSI 1
#define PCA 1
#define PCB 3
#define PXB 4
#define EPT -1
#define EPW1 4
#define EPW0 12
#define QTURN 2
struct Params {
  CUtensorMap xq[2], xr[3], o, wqkv[2], wo[2];
  const __nv_bfloat16* in_x;
  const __nv_bfloat16* wqkv_p[2];
  const __nv_bfloat16* wo_p[2];
  __nv_bfloat16* out;
  uint32_t zero;
};

__device__ __forceinline__ void colsum_part(const CUtensorMap* wmap, int ty, int qr, int hp) {
  constexpr uint32_t bars = SBASE + OFF_BAR, slots = SBASE + OFF_SLOT;
  PHASE_IDS
  const unsigned ep1 = (*(volatile unsigned*)(g_flags + F_DONE)) / NCTA + 1u;
  if (wwarp == 0 && elect_one()) {
    mbar_expect_tx(bars + 8u * B_CS, 6 * UNIT);
#pragma unroll 1
    for (int j = 0; j < 2; j++) {
      if (ty == 0) mbar_pace(bars + 8u * (B_EMPTY + PCA + PCB * j), 0);
      else __nanosleep(1000);
      tma_load_3d(slots + j * 3 * UNIT, wmap, bars + 8u * B_CS, hp * 64, qr * 128 + j * 64, 0);
    }
  }
  mbar_wait(bars + 8u * B_CS, ty);
  STAMP(KSQ == 0 && ty == 0, 49);
  const uint32_t src = slots + (tid >> 3) * 128 + (((tid & 7) ^ ((tid >> 3) & 7)) << 4);
#pragma unroll 1
  for (int p = 0; p < 3; p++) {
    float s[8];
#pragma unroll
    for (int e = 0; e < 8; e++) s[e] = 0.f;
#pragma unroll
    for (int j = 0; j < 8; j++) {
      const uint4 v = lds128(src + p * UNIT + (j >> 2) * 3 * UNIT + (j & 3) * 2048);
      const uint32_t x[4] = {v.x, v.y, v.z, v.w};
#pragma unroll
      for (int e = 0; e < 4; e++) {
        s[2 * e] += bf_lo(x[e]);
        s[2 * e + 1] += bf_hi(x[e]);
      }
    }
#pragma unroll
    for (int st = 0; st < 2; st++) {
      const bool up = (lane >> (st + 3)) & 1;
#pragma unroll
      for (int e = 0; e < (4 >> st); e++) {
        const float keep = up ? s[e + (4 >> st)] : s[e], give = up ? s[e] : s[e + (4 >> st)];
        s[e] = keep + __shfl_xor_sync(0xffffffffu, give, 8 << st);
      }
    }
    const uint32_t dst = slots + 6 * UNIT + ((wwarp * 3 + p) * 64 + (lane & 7) * 8 + ((lane >> 3) & 1) * 4 + (lane >> 4) * 2) * 4;
    sts32(dst, __float_as_uint(s[0]));
    sts32(dst + 4, __float_as_uint(s[1]));
  }
  named_bar_sync(6, 128);
  if (tid < 64) {
    float r[3] = {0.f, 0.f, 0.f};
#pragma unroll
    for (int e = 0; e < 12; e++) r[e % 3] += __uint_as_float(lds32(slots + 6 * UNIT + (e * 64 + tid) * 4));
    st_rec(&g_cs[ty][hp][qr][tid], r[0], r[1], r[2], ep1);
    STAMP(KSQ == 0 && ty == 0, 50);
  }
  named_bar_sync(6, 128);
}

__device__ __forceinline__ void cs_put(int blk, int ty, int col, float v) {
  const uint32_t hi = pack_bf16x2(v, 0.f), lo = pack_bf16x2(v - bf_lo(hi), 0.f);
  const uint32_t a = SBASE + OFF_CS + blk * 512 + ty * 256 + col * 2;
  asm volatile("st.shared.b16 [%0], %1;" ::"r"(a ^ (((a >> 7) & 7) << 4)), "h"((unsigned short)hi) : "memory");
  asm volatile("st.shared.b16 [%0], %1;" ::"r"((a + 128) ^ ((((a >> 7) + 1) & 7) << 4)), "h"((unsigned short)lo) : "memory");
}

__device__ __forceinline__ uint32_t ln_params(float s1, float s2) {
  const float mean = s1 * (1.0f / DM);
  const float var = fmaxf(fmaf(-mean, mean, s2 * (1.0f / DM)), 0.f);
  float sd;
  asm("sqrt.approx.f32 %0, %1;" : "=f"(sd) : "f"(bf16_round(bf16_round(var) + 1e-5f)));
  return pack_bf16x2(mean, sd);
}

__host__ __device__ constexpr int w_ua(int kt) { return (kt == 6 ? 20 : 3 * kt) % 20; }
__host__ __device__ constexpr int w_ub(int kt) { return (kt == 6 ? 18 : 3 * kt + 1) % 20; }

#define SPLITS 0x043333344ull
__device__ __forceinline__ int q_split(int inst) { return (int)((SPLITS >> (4 * inst)) & 15ull); }
__device__ __forceinline__ int q_first(int inst) { return inst == 0 ? 0 : 32 * inst - 16; }
__device__ __forceinline__ int w_first(int inst) { return 32 * inst + 16 + 4 * q_split(inst + 1); }
#define PREMASK 0x3Cu
#define PRE0 3
#define PRESH 2
__host__ __device__ constexpr int pre_idx(int kt) {
  const int d = kt - PRE0;
  return (d >= 0 && (d & ((1 << PRESH) - 1)) == 0 && (d >> PRESH) < 4) ? d >> PRESH : -1;
}
__device__ __forceinline__ bool w_pre(int inst) { return (PREMASK >> inst) & 1u; }

__global__ void __launch_bounds__(512, 1) fused_kernel(const __grid_constant__ Params P) {
  extern __shared__ __align__(1024) uint8_t smem_raw[];
  constexpr uint32_t base = SBASE, bars = base + OFF_BAR, slots = base + OFF_SLOT;
  if (smem_u32(smem_raw) != base) __trap();
  const int warp = __shfl_sync(0xffffffffu, threadIdx.x >> 5, 0), lane = threadIdx.x & 31;
  const int b = blockIdx.x;
#define QS 0
#define WS 1
  const int qr = ((b & ((8 << QS) - 1)) >> QS) ^ (((b >> (3 + QS)) & 1) * 7);
  const int hp = ((b >> (3 + QS)) << QS) + (b & ((1 << QS) - 1));
  const int rt = ((b & ((16 << WS) - 1)) >> WS) ^ (((b >> (4 + WS)) & 1) * 15);
  const int ct = ((b >> (4 + WS)) << WS) + (b & ((1 << WS) - 1));

  if (warp == 12) {
    if (elect_one()) {
#pragma unroll
      for (int s = 0; s < 8; s++) {
        mbar_init(bars + 8u * (B_FULL + s), 2);
        mbar_init(bars + 8u * (B_EMPTY + s), 4);
      }
      mbar_init(bars + 8u * B_GO, 1);
      fence_barrier_init();
    }
    __syncwarp();
    named_bar_arrive(0, 512);
  }
  if (threadIdx.x == 0) {
    mbar_init(bars + 8u * B_PREP, 1);
    mbar_init(bars + 8u * (B_PREP + 1), 1);
    for (int s = 0; s < 4; s++) mbar_init(bars + 8u * (B_HALO + s), 1);
    for (int s = 0; s < 3; s++) mbar_init(bars + 8u * (B_REL + s), 8);
    mbar_init(bars + 8u * B_AFREE, 2);
    mbar_init(bars + 8u * B_TURN, 4);
    mbar_init(bars + 8u * (B_TURN + 1), 4);
    mbar_init(bars + 8u * B_CS, 1);
    mbar_init(bars + 8u * B_PRE, 1);
    mbar_init(bars + 8u * B_RESF, 1);
    mbar_init(bars + 8u * B_RESE, 4);
    mbar_init(bars + 8u * B_CSD, 4);
    mbar_init(bars + 8u * B_XRDY, 1);
    mbar_init(bars + 8u * (B_XRDY + 1), 1);
    fence_barrier_init();
  }
  if (warp != 12) named_bar_sync(0, 512);

  if (warp >= 12) {
    setmaxnreg_dec<32>();
    if (warp <= 13) {
      const bool act = warp == 13;
      uint32_t q = 4, dl = 0;
      bool prevw = false;
      unsigned ep1 = 0;
      if (act) {
        mbar_wait(bars + 8u * B_GO, 0);
        ep1 = __shfl_sync(0xffffffffu, (*(volatile unsigned*)(g_flags + F_DONE)) / NCTA + 1u, 0);
      } else {
#pragma unroll 1
        for (int s = 0; s < 16; s++) {
          const uint32_t fb = bars + 8u * (B_FULL + (s & 7)), sa = base + (s & 3) * 5 * UNIT;
          if (s >= 4) mbar_wait(bars + 8u * (B_EMPTY + ((s - 4) & 7)), ((s - 4) >> 3) & 1);
          if (elect_one()) {
            mbar_expect_tx(fb, 5 * UNIT);
            mbar_arrive(fb);
            tma_load_3d(sa, &P.xq[0], fb, 0, qr * 128, s);
            tma_load_3d(sa + 2 * UNIT, &P.wqkv[0], fb, hp * 64, s * 64, 0);
          }
        }
        if (elect_one()) mbar_arrive(bars + 8u * B_GO);
      }
      auto rbar = [&](int b0, int c) { return bars + 8u * b0 + ((8u * (c & 7)) ^ ((q & 1u) << 5)); };
      auto rpar = [&](int c) { return ((q + (c >> 2)) >> 1) & 1u; };
#pragma unroll 1
      for (int sg = 4; sg < 34; sg++) {
        const int part = sg & 3, si = (sg >> 2) - (part & 1), L = si >> 1, ch = si & 1;
        const int k0 = part == 0 ? 0 : 4 * q_split(si), k1 = part == 0 ? 4 * q_split(si) : 16;
        if (part == 3 || (part != 1 && k0 == k1)) continue;
        uint32_t seen = act ? 0u : 0xFFFFu;
        if (part != 1) {
          const CUtensorMap* map = act ? &P.xq[L == 0 ? 0 : 1] : &P.wqkv[L & 1];
          if (act && (L == 0 || __any_sync(0xffffffffu, mbar_test(bars + 8u * (B_XRDY + ch), (L & 1) ^ 1)))) {
            seen = 0xFFFFu;
            fence_proxy_async_all();
          }
#pragma unroll 1
          for (int k4 = k0; k4 < k1; k4 += 4, q++) {
#pragma unroll
            for (int ks = 0; ks < 4; ks++) {
              const int kt = k4 + ks;
              if ((ks & 1) == 0)
                wait_mask<false>(g_flags + F_X + (ch * 8 + qr) * XSTR, 8, 6u * ep1 - 6u + 2u * L, 1u << (kt >> 1), seen, lane);
              if (ks == 0 && prevw) mbar_wait(rbar(B_EMPTY, -5), rpar(-5));
              else mbar_wait(rbar(B_EMPTY, ks - 4), rpar(-4));
              if (ks == 3 && prevw && !act) mbar_wait(bars + 8u * B_RESE, dl == 0 ? 1u : 0u);
              if (elect_one()) {
                mbar_expect_tx(rbar(B_FULL, ks), act ? 2 * UNIT : 3 * UNIT);
                tma_load_3d(base + ks * 5 * UNIT + (act ? 0 : 2 * UNIT) + (ks < 2 ? dl : 0u - dl), map, rbar(B_FULL, ks),
                            act ? 0 : hp * 64, act ? ch * 1024 + qr * 128 : kt * 64, act ? kt : 0);
              }
            }
            prevw = false;
          }
        } else {
          const CUtensorMap* map = act ? &P.o : &P.wo[L & 1];
          const bool pre = !act && w_pre(2 * L + ch);
          const int m0 = ch * 1024 + rt * 64;
#pragma unroll
          for (int kt = 0; kt < 16; kt++) {
            if (kt == 0 || kt == 1 || kt == 4 || kt == 8)
              wait_mask<false>(g_flags + F_O + (ch * 16 + rt) * OSTR, 16, 4u * ep1 - 3u + L,
                               kt == 0 ? 1u : (kt == 1 ? 0xEu : (kt == 4 ? 0xF0u : 0xFF00u)), seen, lane);
            if (kt < 4 && !prevw) mbar_wait(rbar(B_EMPTY, kt - 4 - (kt >> 1)), rpar(-4));
            else mbar_wait(rbar(B_EMPTY, kt - 6), rpar(kt - 6));
            if (kt == 6 && prevw && !act) mbar_wait(bars + 8u * B_RESE, dl == 0 ? 1u : 0u);
            if (elect_one()) {
              if (pre_idx(kt) >= 0 && pre) {
                mbar_arrive(rbar(B_FULL, kt));
              } else {
                mbar_expect_tx(rbar(B_FULL, kt), act ? UNIT : 2 * UNIT);
                const uint32_t da = base + w_ua(kt) * UNIT + (w_ua(kt) < 10 ? dl : 0u - dl);
                const uint32_t db = base + w_ub(kt) * UNIT + (w_ub(kt) < 10 ? dl : 0u - dl);
                tma_load_3d(act ? da : db, map, rbar(B_FULL, kt), 0, act ? m0 : kt * 64, act ? kt : ct * 2);
              }
            }
          }
          if (act && elect_one()) {
            mbar_expect_tx(bars + 8u * B_RESF, 2 * UNIT);
            tma_load_3d(base + 8 * UNIT + dl, &P.xr[L == 0 ? 0 : 1], bars + 8u * B_RESF, 0, m0, ct * 2);
          }
          q += 4;
          dl ^= 10u * UNIT;
          prevw = true;
        }
      }
    } else if (warp == 14) {
      const unsigned ep1 = (*(volatile unsigned*)(g_flags + F_DONE)) / NCTA + 1u;
#pragma unroll 1
      for (int inst = 0; inst < 8; inst++) {
        const int L = inst >> 1, ch = inst & 1, gb = ch * 8 + qr;
        const unsigned* fp = g_flags + F_KV + (max(gb - 1 - ((lane >> 1) & 1), 0) * 16 + hp) * KSTR + (lane & 1);
        const unsigned target = (lane & 1) ? 2u * ep1 - 1u + (L >> 1) : 4u * ep1 - 3u + L;
        uint32_t seen = gb == 0 ? 15u : (gb == 1 ? 12u : 0u);
        named_bar_sync(3, 192);
        STA(34);
        __nanosleep(HDELAY);
        if ((L & 1) == 0) {
#pragma unroll 1
          for (int i = 0; i < 4; i++) {
            wait_lanes(fp, target, 1u << i, seen);
            STA(36 + i);
            if (i > 0) mbar_wait_lazy<RELNS>(bars + 8u * (B_REL + i - 1), ch);
            if (elect_one()) {
              mbar_expect_tx(bars + 8u * (B_HALO + i), 16384);
              bulk_load(slots + (i == 3 ? 2 : 2 - i) * 16384, gb > (i >> 1) ? g_kvA[L >> 1][gb - 1 - (i >> 1)][hp][(i & 1) ^ 1] : g_zero,
                        16384, bars + 8u * (B_HALO + i));
            }
          }
        } else {
          wait_lanes(fp, target, 1u, seen);
        }
        if (elect_one()) {
          if (L & 1) {
            const uint8_t* s1 = gb >= 1 ? g_kvB[L >> 1][gb - 1][hp] : g_zero;
            mbar_expect_tx(bars + 8u * B_HALO, 4096);
            bulk_load(KB_ROW0 - 2048, s1, 2048, bars + 8u * B_HALO);
            bulk_load(VB_ROW0 - 2048, s1 + 2048, 2048, bars + 8u * B_HALO);
          }
          if (w_pre(inst)) {
            mbar_wait(bars + 8u * B_AFREE, (inst & 1) ^ 1);
            if (inst == CSI) mbar_wait(bars + 8u * B_CSD, 0);
            mbar_expect_tx(bars + 8u * B_PRE, 8 * UNIT);
#pragma unroll 1
            for (int j = 0; j < 4; j++) {
              tma_load_3d(slots + j * 2 * UNIT, &P.wo[L & 1], bars + 8u * B_PRE, 0, (PRE0 + (j << PRESH)) * 64, ct * 2);
              __nanosleep(200);
            }
          }
        }
        __syncwarp();
      }
    } else {
      const unsigned ep1 = (*(volatile unsigned*)(g_flags + F_DONE)) / NCTA + 1u;
      mbar_wait(bars + 8u * B_GO, 0);
#pragma unroll 1
      for (int i = 0; i < 20; i++) {
        const char* src = i < 4 ? reinterpret_cast<const char*>(P.wo_p[0]) + (size_t)b * 16384 + i * 4096
                                : (i < 16 ? reinterpret_cast<const char*>(P.wqkv_p[1]) + (size_t)b * 49152 + (i - 4) * 4096
                                          : reinterpret_cast<const char*>(P.wo_p[1]) + (size_t)b * 16384 + (i - 16) * 4096);
        asm volatile("prefetch.global.L2 [%0];" ::"l"(src + lane * 128));
        __nanosleep(TRICKLE);
      }
#pragma unroll 1
      for (int inst = 2; inst < 8; inst++) {
        const int L = inst >> 1, ch = inst & 1, gb = ch * 8 + qr;
        uint32_t seen = 0;
        wait_mask<true>(g_flags + F_X + gb * XSTR, 8, 6u * ep1 - 6u + 2u * L, 0xFFu, seen, lane);
        if (lane == 0) mbar_arrive(bars + 8u * (B_XRDY + ch));
#pragma unroll 1
        for (int h = 0; h < 4; h++) {
          const float4* sp = &g_stats[L][0][gb * 128 + h * 32 + lane];
          const float4 s0 = sum_recs<4>(sp, S_LEN, ep1), s1 = sum_recs<4>(sp + 4 * S_LEN, S_LEN, ep1);
          sts32(base + OFF_RS + (ch * 128 + h * 32 + lane) * 4, ln_params(s0.x + s1.x, s0.y + s1.y));
        }
        if (inst == 2) {
          mbar_wait(bars + 8u * B_CSD, 0);
#pragma unroll 1
          for (int hf = 0; hf < 2; hf++) {
            const float4* cp = &g_cs[1][hp][0][hf * 32 + lane];
            const float4 s0 = sum_recs<4>(cp, 64, ep1), s1 = sum_recs<4>(cp + 4 * 64, 64, ep1);
            cs_put(0, 1, hf * 32 + lane, s0.x + s1.x);
            cs_put(1, 1, hf * 32 + lane, s0.y + s1.y);
            cs_put(2, 1, hf * 32 + lane, s0.z + s1.z);
          }
          fence_proxy_async_smem();
        }
        __syncwarp();
        if (lane == 0) mbar_arrive(bars + 8u * (B_PREP + ch));
      }
    }
  } else {
    const bool asst = warp >= 8;
    const bool lane0 = lane == 0;
    uint32_t tpar = 0;
    GTL(0);
    if (asst) {
      colsum_part(&P.wqkv[0], 0, qr, hp);
      if ((threadIdx.x & 127) < 2) mbar_arrive(bars + 8u * B_AFREE);
    } else if (warp >= 4) {
      PHASE_IDS
      {
        const unsigned ep1 = (*(volatile unsigned*)(g_flags + F_DONE)) / NCTA + 1u;
        const int row = b * 16 + (tid >> 3);
        const uint4* src = reinterpret_cast<const uint4*>(P.in_x + (size_t)row * DM) + (tid & 7);
        float s1 = 0.f, s2 = 0.f;
#pragma unroll 1
        for (int k = 0; k < 4; k++) {
          mbar_pace(bars + 8u * (B_EMPTY + PXB * k / 2), 0);
          uint4 v[4];
#pragma unroll
          for (int j = 0; j < 4; j++) v[j] = __ldg(src + (k * 4 + j) * 8);
#pragma unroll
          for (int j = 0; j < 4; j++) {
            const uint32_t w[4] = {v[j].x, v[j].y, v[j].z, v[j].w};
#pragma unroll
            for (int e = 0; e < 4; e++) {
              const float x0 = bf_lo(w[e]), x1 = bf_hi(w[e]);
              s1 += x0 + x1;
              s2 = fmaf(x0, x0, fmaf(x1, x1, s2));
            }
          }
        }
#pragma unroll
        for (int o = 1; o < 8; o <<= 1) {
          s1 += __shfl_xor_sync(0xffffffffu, s1, o);
          s2 += __shfl_xor_sync(0xffffffffu, s2, o);
        }
        if ((tid & 7) == 0) st_rec(&g_stats[0][0][row], s1, s2, 0.f, ep1);
        if (tid == 0) sts32(base + OFF_EPOCH, ep1);
        STAMP(KSQ == 0, 51);
        float4 v[6];
#pragma unroll 1
        for (uint32_t it = 0; it < (1u << 17); ++it) {
          bool ok = true;
#pragma unroll
          for (int t = 0; t < 6; t++) {
            v[t] = ld_rec(t < 2 ? &g_stats[0][0][(t * 8 + qr) * 128 + tid] : &g_cs[0][hp][(tid & 1) * 4 + t - 2][tid >> 1]);
            ok &= __float_as_uint(v[t].w) == ep1;
          }
          STAMP(KSQ == 0 && it == 0, 18);
          if (ok) break;
          __nanosleep(100);
        }
        STAMP(KSQ == 0, 17);
        __syncwarp();
        STAMP(KSQ == 0, 19);
#pragma unroll
        for (int cc = 0; cc < 2; cc++) sts32(base + OFF_RS + (cc * 128 + tid) * 4, ln_params(v[cc].x, v[cc].y));
        const float cs[3] = {(v[2].x + v[3].x) + (v[4].x + v[5].x), (v[2].y + v[3].y) + (v[4].y + v[5].y),
                             (v[2].z + v[3].z) + (v[4].z + v[5].z)};
#pragma unroll
        for (int blk = 0; blk < 3; blk++) {
          const float t = cs[blk] + __shfl_xor_sync(0xffffffffu, cs[blk], 1);
          cs_put(blk, tid & 1, tid >> 1, (tid & 1) ? 0.f : t);
        }
        fence_proxy_async_smem();
        named_bar_sync(2, 128);
        if (tid < 2) mbar_arrive(bars + 8u * (B_PREP + tid));
        STAMP(KSQ == 0, 48);
      }
    }
#pragma unroll 1
    for (int inst = asst ? 0 : warp >> 2; inst < 8; inst += asst ? 1 : 2) {
      const int L = inst >> 1, ch = inst & 1, gb = ch * 8 + qr;
      if (asst) {
        setmaxnreg_dec<24>();
        if (warp == 8) {
          named_bar_sync(3, 192);
          STA(32);
          if (elect_one()) {
            if ((L & 1) == 0) {
              bulk_store(g_kvA[L >> 1][gb][hp][1], slots + 16384, 16384);
            } else {
              bulk_store(g_kvB[L >> 1][gb][hp], KB_ROW0 + 112 * 128, 2048);
              bulk_store(g_kvB[L >> 1][gb][hp] + 2048, VB_ROW0 + 112 * 128, 2048);
            }
            bulk_commit();
            bulk_wait0();
            fence_proxy_async_all();
            red_relaxed_add(g_flags + F_KV + (gb * 16 + hp) * KSTR, 1u);
            STA(33);
          }
          __syncwarp();
        } else if (warp == 9 && (L & 1) == 0) {
          named_bar_sync(7, 160);
          if (lane0) {
            bulk_store(g_kvA[L >> 1][gb][hp][0], slots, 16384);
            bulk_commit();
          }
          __syncwarp();
        }
        named_bar_sync(4, 256);
        setmaxnreg_inc<128>();
      } else {
      setmaxnreg_inc<224>();
      {
        float acc[2][96];
        const int ksp = q_split(inst);
        int n = q_first(inst);
        uint32_t dlt = (ch == 0 && L > 0) ? 10u * (UNIT >> 4) : 0u;
        if (inst == 1 || (inst > 1 && q_split(inst - 1) != 4)) {
          mbar_wait_lazy<100>(bars + 8u * (B_TURN + ch), tpar);
          tpar ^= 1u;
        }
        if (L == 3) GTL(37);
        mbar_wait(bars + 8u * (B_FULL + (n & 7)), (n >> 3) & 1);
        GTL(1 + L * 8);
        {
          const uint32_t da = (base >> 4) + 0x10000u + dlt;
          const uint64_t db = desc_lo(da - 0x10000u + ((UNIT >> 4) << 16) + 2 * (UNIT >> 4));
          wgmma_fence();
          wgmma_n192_ssz_ta0_tb1(acc[0], desc_lo(da), db);
          wgmma_commit();
          wgmma_n192_ssz_ta0_tb1(acc[1], desc_lo(da + (UNIT >> 4)), db);
          wgmma_commit();
        }
#pragma unroll 1
        for (int k4 = 0; k4 < 4; k4++) {
          const bool brk = k4 + 1 == ksp && k4 < 3;
#pragma unroll
          for (int ks = 0; ks < 4; ks++, n++) {
            if (ks == 2 && k4 == 3) break;
            STAMP(inst == KSQ, k4 * 4 + ks);
            const uint32_t da = ((base + ks * 5 * UNIT) >> 4) + 0x10000u + (ks < 2 ? dlt : 0u - dlt);
            const uint32_t dbb = da - 0x10000u + ((UNIT >> 4) << 16) + 2 * (UNIT >> 4);
#pragma unroll
            for (int k16 = 0; k16 < 4; k16++) {
              if (ks == 0 && k16 == 0 && k4 == 0) continue;
              const uint64_t db = desc_lo(dbb + k16 * 128);
              wgmma_fence();
              wgmma_n192_ss_ta0_tb1(acc[0], desc_lo(da + k16 * 2), db, 1);
              wgmma_commit();
              wgmma_wait<1>();
              if (k16 == 0 && lane0 && (ks != 0 || k4 != ksp)) mbar_arrive(bars + 8u * (B_EMPTY + ((n - 1) & 7)));
              wgmma_fence();
              wgmma_n192_ss_ta0_tb1(acc[1], desc_lo(da + (UNIT >> 4) + k16 * 2), db, 1);
              wgmma_commit();
              bool ok = true;
              if (k16 == 2) ok = mbar_test(bars + 8u * (B_FULL + ((n + 1) & 7)), ((n + 1) >> 3) & 1) || (ks == 3 && brk);
              if (k16 == QTURN && ks == 3 && brk && lane0) mbar_arrive(bars + 8u * (B_TURN + (ch ^ 1)));
              if ((ks & 1) == 0 || k16 < 3) wgmma_wait<1>();
              if (k16 == 2 && !ok) mbar_wait(bars + 8u * (B_FULL + ((n + 1) & 7)), ((n + 1) >> 3) & 1);
            }
          }
          if (brk) {
            wgmma_wait<0>();
            if (lane0) mbar_arrive(bars + 8u * (B_EMPTY + ((n - 1) & 7)));
            n += 16;
            dlt ^= 10u * (UNIT >> 4);
            mbar_wait_lazy<100>(bars + 8u * (B_TURN + ch), tpar);
            tpar ^= 1u;
            STAMP(inst == KSQ, 17);
            mbar_wait(bars + 8u * (B_FULL + (n & 7)), (n >> 3) & 1);
          }
        }
        auto tail_group = [&](int u) {
          const uint32_t da = ((base + (2 + (u & 1)) * 5 * UNIT) >> 4) + 0x10000u - dlt;
          const uint32_t dbb = da - 0x10000u + ((UNIT >> 4) << 16) + 2 * (UNIT >> 4);
          if (u < 3) wgmma_fence();
#pragma unroll
          for (int k16 = 0; k16 < 4; k16++)
            wgmma_n192_ss_ta0_tb1(acc[u < 2], desc_lo(da + (u < 2 ? UNIT >> 4 : 0) + k16 * 2), desc_lo(dbb + k16 * 128), 1);
          wgmma_commit();
        };
        STAMP(inst == KSQ, 14);
        tail_group(0);
        wgmma_wait<1>();
        STAMP(inst == KSQ, 42);
        if (lane0) mbar_arrive(bars + 8u * (B_EMPTY + ((n - 1) & 7)));
        PHASE_IDS
        mbar_wait(bars + 8u * (B_PREP + ch), L & 1);
        STAMP(inst == KSQ, 43);
        uint32_t rs[4];
#pragma unroll
        for (int i = 0; i < 4; i++)
          rs[i] = lds32(base + OFF_RS + (ch * 128 + (i >> 1) * 64 + wwarp * 16 + g + 8 * (i & 1)) * 4);
        auto fold = [&](int h) {
          uint32_t a[2];
#pragma unroll
          for (int r = 0; r < 2; r++) a[r] = c == (L & 1) ? __byte_perm(rs[2 * h + r], 0, 0x1010) ^ 0x80008000u : 0u;
          uint64_t d;
          asm("mov.b64 %0, {%1, %2};" : "=l"(d) : "r"(((base + OFF_CS) >> 4) + ((512 >> 4) << 16)), "r"(0x40000000u));
          wgmma_fence();
          wgmma_n192_rs_tb1(acc[h], a[0], a[1], d);
        };
        fold(1);
        wgmma_commit();
        mbar_wait(bars + 8u * (B_FULL + ((n + 1) & 7)), ((n + 1) >> 3) & 1);
        STAMP(inst == KSQ, 44);
        tail_group(1);
        tail_group(2);
        STAMP(inst == KSQ, 45);
        const bool afree = mbar_test(bars + 8u * (inst == CSI + 1 ? B_CSD : B_AFREE), inst == CSI + 1 ? 0 : inst & 1);
        float rinv[2][2];
#pragma unroll
        for (int i = 0; i < 4; i++) rinv[i >> 1][i & 1] = rcp_fast(bf_hi(rs[i]));
        const int mat = lane >> 3;
        const uint32_t soff = (wwarp * 16 + (mat & 1) * 8 + (lane & 7)) * 128;
        const uint32_t kdst = ((L & 1) ? KB_ROW0 : slots) + soff, vdst = ((L & 1) ? VB_ROW0 : slots + 8192) + soff;
        const uint32_t hs = (L & 1) ? 8192 : 16384;
        const int rg = 2 * wwarp + (mat & 1);
        const uint32_t qdst = slots + 3 * 16384 + ((L & 1) ? soff : ((rg < 4 ? 2 * rg : 15 - 2 * rg) * 8 + (lane & 7)) * 128);
        wgmma_wait<2>();
        STAMP(inst == KSQ, 46);
        fold(0);
        tail_group(3);
        STAMP(inst == KSQ, 47);
        if (EPT < 0 && lane0) mbar_arrive(bars + 8u * (B_TURN + (ch ^ 1)));
        if (!afree) {
          if (EPT >= 0 && lane0) mbar_arrive(bars + 8u * (B_TURN + (ch ^ 1)));
          wgmma_wait<1>();
          if (lane0) mbar_arrive(bars + 8u * (B_EMPTY + (n & 7)));
          wgmma_wait<0>();
          if (lane0) mbar_arrive(bars + 8u * (B_EMPTY + ((n + 1) & 7)));
          mbar_wait(bars + 8u * (inst == CSI + 1 ? B_CSD : B_AFREE), inst == CSI + 1 ? 0 : inst & 1);
        }
        wgmma_wait<2>();
        reg_fence<96>(acc[1]);
        STAMP(inst == KSQ, 15);
#pragma unroll
        for (int t = 0; t < 24; t++) {
          const int h = t < 12 ? 1 : 0, p = (t % 12 / 4 + 1) % 3, jp = t & 3;
          if (t == EPT && lane0 && afree) mbar_arrive(bars + 8u * (B_TURN + (ch ^ 1)));
          if (t == EPW1) {
            wgmma_wait<1>();
            if (lane0 && afree) mbar_arrive(bars + 8u * (B_EMPTY + (n & 7)));
          }
          if (t == EPW0) {
            wgmma_wait<0>();
            reg_fence<96>(acc[0]);
            if (lane0 && afree) mbar_arrive(bars + 8u * (B_EMPTY + ((n + 1) & 7)));
            STAMP(inst == KSQ, 16);
            GTL(2 + L * 8);
          }
          if (t % 12 == 8) {
            rinv[h][0] *= SM_C;
            rinv[h][1] *= SM_C;
          }
          const uint32_t sw = ((2 * jp + (mat >> 1)) ^ (lane & 7)) << 4;
          const float* a = &acc[h][32 * p + 8 * jp];
          const uint32_t dst = p == 0 ? qdst + h * 8192 : (p == 1 ? kdst : vdst) + h * hs;
          stmatrix_x4(dst + sw, pack_bf16x2(a[0] * rinv[h][0], a[1] * rinv[h][0]), pack_bf16x2(a[2] * rinv[h][1], a[3] * rinv[h][1]),
                      pack_bf16x2(a[4] * rinv[h][0], a[5] * rinv[h][0]), pack_bf16x2(a[6] * rinv[h][1], a[7] * rinv[h][1]));
          if (t % 12 == 7) {
            fence_proxy_async_smem();
            if (t == 7) named_bar_arrive(3, 192);
            else if ((L & 1) == 0) named_bar_arrive(7, 160);
            if (t > EPW0) sched_fence(P.zero);
          }
        }
      }
      fence_proxy_async_smem();
      setmaxnreg_dec<128>();
      named_bar_sync(4, 256);
      }
      GTL(3 + L * 8);
      {
        PHASE_IDS
        if ((L & 1) == 0) attention_a(asst, L, gb, hp, inst & 1, ch, (tid_ >> 5) & 3, lane, P.zero);
        else attention_b(asst, gb, inst & 1, wwarp, lane);
        GTL(4 + L * 8);
        fence_proxy_async_smem();
      }
      if (asst) {
        named_bar_arrive(5, 256);
        if (inst == CSI) {
          mbar_wait(bars + 8u * B_AFREE, CSI ^ 1);
          colsum_part(&P.wqkv[1], 1, qr, hp);
          if (lane0) mbar_arrive(bars + 8u * B_CSD);
        }
        continue;
      }
      {
        named_bar_sync(5, 256);
        const int wwarp = warp & 3;
        if (wwarp < 2 && elect_one()) {
          tma_store_3d(&P.o, ((L & 1) ? slots + 3 * 16384 : OA_TILE) + wwarp * 8192, 0, gb * 128 + wwarp * 64, hp);
          bulk_commit();
          bulk_wait0();
          mbar_arrive(bars + 8u * B_AFREE);
          fence_proxy_async_all();
          red_relaxed_add(g_flags + F_O + (gb * 2 + wwarp) * OSTR + hp, 1u);
        }
        __syncwarp();
      }
      GTL(5 + L * 8);

      {
        float acc[64];
        const int n0 = w_first(inst);
        const bool pre = w_pre(inst);
        const uint32_t dl = ch * 10u * (UNIT >> 4);
        mbar_wait_lazy<100>(bars + 8u * (B_TURN + ch), tpar);
        tpar ^= 1u;
        mbar_wait(bars + 8u * (B_FULL + (n0 & 7)), (n0 >> 3) & 1);
        GTL(6 + L * 8);
#pragma unroll
        for (int kt = 0; kt < 16; kt++) {
          const int n = n0 + kt;
          STAMP(inst == KSW, 20 + kt);
          const uint32_t da = ((base + w_ua(kt) * UNIT) >> 4) + 0x10000u + (w_ua(kt) < 10 ? dl : 0u - dl);
          uint32_t db = ((base + w_ub(kt) * UNIT) >> 4) + ((UNIT >> 4) << 16) + (w_ub(kt) < 10 ? dl : 0u - dl);
          if (pre_idx(kt) >= 0 && pre) db = ((slots + pre_idx(kt) * 2 * UNIT) >> 4) + ((UNIT >> 4) << 16);
          if (kt == PRE0 && pre) mbar_wait(bars + 8u * B_PRE, __popc(PREMASK & ((1u << inst) - 1u)) & 1);
          if (kt == 15 && lane0 && (inst >= 6 || q_split(inst + 1) != 4)) mbar_arrive(bars + 8u * (B_TURN + (ch ^ 1)));
          wgmma_fence();
          if (kt == 0) wgmma_n128_ssz_ta0_tb1(acc, desc_lo(da), desc_lo(db));
#pragma unroll
          for (int k16 = kt == 0 ? 1 : 0; k16 < 4; k16++) wgmma_n128_ss_ta0_tb1(acc, desc_lo(da + 2 * k16), desc_lo(db + 128 * k16), 1);
          wgmma_commit();
          const uint32_t nb = bars + 8u * (kt == 15 ? B_RESF : B_FULL + ((n + 1) & 7)), np = kt == 15 ? ch : ((n + 1) >> 3) & 1;
          const bool ok = mbar_test(nb, np);
          if (kt > 0) {
            wgmma_wait<1>();
            if (lane0) mbar_arrive(bars + 8u * (B_EMPTY + ((n - 1) & 7)));
          }
          if (!ok) mbar_wait(nb, np);
        }
        PHASE_IDS
        const uint32_t xb = base + (8 + ch * 10) * UNIT;
        const int mat = lane >> 3;
        const uint32_t xrow = xb + (wwarp * 16 + (mat & 1) * 8 + (lane & 7)) * 128;
        uint32_t xv[8][4];
#pragma unroll
        for (int jp = 0; jp < 8; jp++)
          ldmatrix_x4(xv[jp], xrow + (jp >> 2) * UNIT + (((2 * (jp & 3) + (mat >> 1)) ^ (lane & 7)) << 4));
        wgmma_wait<0>();
        reg_fence<64>(acc);
        if (lane0) mbar_arrive(bars + 8u * (B_EMPTY + ((n0 + 15) & 7)));
        STAMP(inst == KSW, 36);
        GTL(7 + L * 8);
#pragma unroll
        for (int jp = 0; jp < 8; jp++) {
#pragma unroll
          for (int q = 0; q < 4; q++) xv[jp][q] = add_bf16x2(xv[jp][q], pack_bf16x2(acc[8 * jp + 2 * q], acc[8 * jp + 2 * q + 1]));
          stmatrix_x4(xrow + (jp >> 2) * UNIT + (((2 * (jp & 3) + (mat >> 1)) ^ (lane & 7)) << 4), xv[jp][0], xv[jp][1],
                      xv[jp][2], xv[jp][3]);
        }
        fence_proxy_async_smem();
        named_bar_sync(1 + ch, 128);
        const int grow = ch * 1024 + rt * 64;
        if (wwarp == 0) {
          if (elect_one()) {
            tma_store_3d(&P.xr[L == 3 ? 2 : 1], xb, 0, grow, ct * 2);
            bulk_commit();
            bulk_wait_read0();
            mbar_arrive(bars + 8u * B_RESE);
            bulk_wait0();
            TGET(t35);
            fence_proxy_async_all();
            if (L < 3) red_relaxed_add(g_flags + F_X + (ch * 8 + (rt >> 1)) * XSTR + ct, 1u);
            if (L == 2) TPUT(ch, 35, t35);
          }
          __syncwarp();
        } else if (lane == 0) {
          mbar_arrive(bars + 8u * B_RESE);
        }
        if (L < 3) {
          const unsigned ep1 = lds32(base + OFF_EPOCH);
          float s1[2] = {0.f, 0.f}, s2[2] = {0.f, 0.f};
#pragma unroll
          for (int jp = 0; jp < 8; jp++)
#pragma unroll
            for (int q = 0; q < 4; q++) {
              const float x0 = bf_lo(xv[jp][q]), x1 = bf_hi(xv[jp][q]);
              s1[q & 1] += x0 + x1;
              s2[q & 1] = fmaf(x0, x0, fmaf(x1, x1, s2[q & 1]));
            }
#pragma unroll
          for (int r = 0; r < 2; r++) {
            s1[r] += __shfl_xor_sync(0xffffffffu, s1[r], 1);
            s2[r] += __shfl_xor_sync(0xffffffffu, s2[r], 1);
            s1[r] += __shfl_xor_sync(0xffffffffu, s1[r], 2);
            s2[r] += __shfl_xor_sync(0xffffffffu, s2[r], 2);
            if (c == 0) st_rec(&g_stats[L + 1][ct][grow + wwarp * 16 + g + 8 * r], s1[r], s2[r], 0.f, ep1);
          }
        }
        GTL(8 + L * 8);
      }
    }
    if (threadIdx.x == 128) atomicAdd(g_flags + F_DONE, 1u);
  }
}

typedef CUresult (*PFN_tmEncode)(CUtensorMap*, CUtensorMapDataType, cuuint32_t, void*, const cuuint64_t*,
                                 const cuuint64_t*, const cuuint32_t*, const cuuint32_t*, CUtensorMapInterleave,
                                 CUtensorMapSwizzle, CUtensorMapL2promotion, CUtensorMapFloatOOBfill);

PFN_tmEncode get_encode_fn() {
  static PFN_tmEncode fn = nullptr;
  if (!fn) {
    cudaDriverEntryPointQueryResult qr;
    void* p = nullptr;
    cudaGetDriverEntryPoint("cuTensorMapEncodeTiled", &p, cudaEnableDefault, &qr);
    fn = (PFN_tmEncode)p;
  }
  return fn;
}

CUtensorMap make_map(const void* ptr, int rows, int cols, int inner, int box_rows, int box_blk) {
  CUtensorMap m;
  cuuint64_t gdim[3] = {(cuuint64_t)inner, (cuuint64_t)rows, (cuuint64_t)(cols / inner)};
  cuuint64_t gstr[2] = {(cuuint64_t)cols * 2, (cuuint64_t)inner * 2};
  cuuint32_t box[3] = {64, (cuuint32_t)box_rows, (cuuint32_t)box_blk};
  cuuint32_t estr[3] = {1, 1, 1};
  get_encode_fn()(&m, CU_TENSOR_MAP_DATA_TYPE_BFLOAT16, 3, const_cast<void*>(ptr), gdim, gstr, box, estr,
                  CU_TENSOR_MAP_INTERLEAVE_NONE, CU_TENSOR_MAP_SWIZZLE_128B, CU_TENSOR_MAP_L2_PROMOTION_L2_128B,
                  CU_TENSOR_MAP_FLOAT_OOB_FILL_NONE);
  return m;
}

}

extern "C" void kernel_launch(void* const* d_in, const int* in_sizes, int n_in, void* d_out, int out_size) {
  (void)in_sizes; (void)n_in; (void)out_size;
  void *p_o, *p_x;
  cudaGetSymbolAddress(&p_o, g_o);
  cudaGetSymbolAddress(&p_x, g_x);
  static bool attr_done = false;
  if (!attr_done) {
    cudaFuncSetAttribute(fused_kernel, cudaFuncAttributeMaxDynamicSharedMemorySize, SMEM_BYTES);
    attr_done = true;
  }
  Params P;
  P.in_x = (const __nv_bfloat16*)d_in[0];
  P.wqkv_p[0] = (const __nv_bfloat16*)d_in[1];
  P.wo_p[0] = (const __nv_bfloat16*)d_in[2];
  P.wqkv_p[1] = (const __nv_bfloat16*)d_in[4];
  P.wo_p[1] = (const __nv_bfloat16*)d_in[5];
  P.out = (__nv_bfloat16*)d_out;
  P.zero = 0;
  P.xq[0] = make_map(P.in_x, S_LEN, DM, 64, 128, 1);
  P.xq[1] = make_map(p_x, S_LEN, DM, 64, 128, 1);
  P.xr[0] = make_map(P.in_x, S_LEN, DM, 64, 64, 2);
  P.xr[1] = make_map(p_x, S_LEN, DM, 64, 64, 2);
  P.xr[2] = make_map(d_out, S_LEN, DM, 64, 64, 2);
  P.o = make_map(p_o, S_LEN, DM, 64, 64, 1);
  for (int t = 0; t < 2; t++) {
    P.wqkv[t] = make_map(P.wqkv_p[t], DM, NQKV, 1024, 64, 3);
    P.wo[t] = make_map(P.wo_p[t], DM, DM, 64, 64, 2);
  }
  fused_kernel<<<NCTA, 512, SMEM_BYTES>>>(P);
}
```

```cpp
#include <cuda_runtime.h>
#include <cuda_bf16.h>
#include <cuda.h>
#include <stdint.h>
#include <type_traits>

namespace {

constexpr int S_LEN = 2048;
constexpr int DM = 1024;
constexpr int NQKV = 3072;
constexpr int NCTA = 128;

__device__ __align__(1024) uint8_t g_kvA[2][16][16][2][16384];
__device__ __align__(1024) uint8_t g_kvB[2][16][16][4096];
__device__ __align__(1024) uint8_t g_zero[16384];
__device__ __align__(1024) __nv_bfloat16 g_o[S_LEN * DM];
__device__ __align__(1024) __nv_bfloat16 g_x[S_LEN * DM];
__device__ __align__(1024) float4 g_stats[4][8][S_LEN];
__device__ __align__(1024) float4 g_cs[2][16][8][64];
constexpr int F_X = 0;
constexpr int XSTR = 32, OSTR = 32, KSTR = 32;
constexpr int F_O = F_X + 16 * XSTR;
constexpr int F_KV = F_O + 32 * OSTR;
constexpr int F_DONE = F_KV + 256 * KSTR;
__device__ __align__(1024) unsigned g_flags[F_DONE + 32];

constexpr uint32_t SBASE = 1024;
constexpr int UNIT = 8192;
constexpr int NUNITS = 20;
constexpr int OFF_SLOT = NUNITS * UNIT;
constexpr int OFF_CS = OFF_SLOT + 4 * 16384;
constexpr int OFF_RS = OFF_CS + 1536;
constexpr int OFF_BAR = OFF_RS + 1024;
constexpr int OFF_EPOCH = OFF_BAR + 392;
constexpr int OFF_TS = OFF_BAR + 400;
constexpr int SMEM_BYTES = OFF_TS;
constexpr int B_FULL = 0, B_EMPTY = 8, B_PREP = 16, B_HALO = 18, B_REL = 22, B_AFREE = 25, B_TURN = 26, B_XRDY = 28,
              B_CS = 30, B_CSD = 31, B_GO = 32, B_RESF = 33, B_RESE = 34, B_PRE = 35, B_LOC = 40;

__device__ __forceinline__ uint32_t smem_u32(const void* p) { return (uint32_t)__cvta_generic_to_shared(p); }
extern __shared__ __align__(1024) uint8_t smem_raw[];
__device__ __forceinline__ uint32_t sw(uint32_t a) {
  uint32_t r;
  asm volatile("add.u32 %0, %1, %2;" : "=r"(r) : "r"(a), "r"(smem_u32(smem_raw) - SBASE));
  return r;
}

__device__ __forceinline__ void mbar_init(uint32_t bar, uint32_t cnt) {
  asm volatile("mbarrier.init.shared::cta.b64 [%0], %1;" ::"r"(sw(bar)), "r"(cnt));
}
__device__ __forceinline__ void mbar_expect_tx(uint32_t bar, uint32_t bytes) {
  asm volatile("mbarrier.arrive.expect_tx.shared::cta.b64 _, [%0], %1;" ::"r"(sw(bar)), "r"(bytes) : "memory");
}
__device__ __forceinline__ void mbar_arrive(uint32_t bar) {
  asm volatile("mbarrier.arrive.shared::cta.b64 _, [%0];" ::"r"(sw(bar)) : "memory");
}
__device__ __forceinline__ void warp_arrive(uint32_t bar, bool cond = true) {
  asm volatile("{\n.reg .pred p;\nelect.sync _|p, 0xffffffff;\nsetp.ne.and.b32 p, %1, 0, p;\n"
               "@p mbarrier.arrive.shared::cta.b64 _, [%0];\n}\n" ::"r"(sw(bar)), "r"((uint32_t)cond) : "memory");
}
__device__ __forceinline__ void warp_arrive_cl(uint32_t bar, bool cond = true) {
  asm volatile("{\n.reg .pred p;\nelect.sync _|p, 0xffffffff;\nsetp.ne.and.b32 p, %1, 0, p;\n"
               "@p mbarrier.arrive.shared::cluster.b64 _, [%0];\n}\n" ::"r"(bar), "r"((uint32_t)cond) : "memory");
}
__device__ __forceinline__ bool mbar_try_wait(uint32_t bar, uint32_t parity) {
  uint32_t ok;
  asm volatile(
      "{\n.reg .pred p;\nmbarrier.try_wait.parity.shared::cta.b64 p, [%1], %2;\nselp.b32 %0, 1, 0, p;\n}\n"
      : "=r"(ok)
      : "r"(sw(bar)), "r"(parity)
      : "memory");
  return ok != 0;
}
__device__ __forceinline__ bool mbar_test(uint32_t bar, uint32_t parity) {
  uint32_t ok;
  asm volatile(
      "{\n.reg .pred p;\nmbarrier.test_wait.parity.shared::cta.b64 p, [%1], %2;\nselp.b32 %0, 1, 0, p;\n}\n"
      : "=r"(ok)
      : "r"(sw(bar)), "r"(parity)
      : "memory");
  return ok != 0;
}
__device__ __forceinline__ void mbar_wait(uint32_t bar, uint32_t parity) {
#pragma unroll 1
  for (uint32_t it = 0; it < (1u << 18); ++it) {
    if (mbar_try_wait(bar, parity)) return;
  }
}
__device__ __forceinline__ void mbar_pace(uint32_t bar, uint32_t parity) {
#pragma unroll 1
  for (uint32_t it = 0; it < 24; ++it) {
    if (mbar_try_wait(bar, parity)) return;
  }
}
template <int NS>
__device__ __forceinline__ void mbar_wait_lazy(uint32_t bar, uint32_t parity) {
#pragma unroll 1
  for (uint32_t it = 0; it < (1u << 18); ++it) {
    if (mbar_try_wait(bar, parity)) return;
    __nanosleep(NS);
  }
}
__device__ __forceinline__ bool elect_one() {
  uint32_t ok;
  asm volatile("{\n.reg .pred p;\nelect.sync _|p, 0xffffffff;\nselp.b32 %0, 1, 0, p;\n}\n" : "=r"(ok));
  return ok != 0;
}
__device__ __forceinline__ void fence_barrier_init() { asm volatile("fence.mbarrier_init.release.cluster;" ::: "memory"); }
__device__ __forceinline__ void fence_proxy_async_smem() { asm volatile("fence.proxy.async.shared::cta;" ::: "memory"); }
__device__ __forceinline__ void fence_proxy_async_all() { asm volatile("fence.proxy.async.global;" ::: "memory"); }

__device__ __forceinline__ void tma_load_3d(uint32_t dst, const CUtensorMap* map, uint32_t bar, int c0, int c1, int c2) {
  asm volatile(
      "cp.async.bulk.tensor.3d.shared::cluster.global.mbarrier::complete_tx::bytes [%0], [%1, {%3, %4, %5}], [%2];" ::"r"(sw(dst)),
      "l"(map), "r"(sw(bar)), "r"(c0), "r"(c1), "r"(c2)
      : "memory");
}
__device__ __forceinline__ void tma_load_3d_mc(uint32_t dst, const CUtensorMap* map, uint32_t bar, int c0, int c1, int c2) {
  asm volatile(
      "cp.async.bulk.tensor.3d.shared::cluster.global.mbarrier::complete_tx::bytes.multicast::cluster [%0], [%1, {%3, %4, %5}], [%2], %6;" ::"r"(sw(dst)),
      "l"(map), "r"(sw(bar)), "r"(c0), "r"(c1), "r"(c2), "h"((unsigned short)3)
      : "memory");
}
__device__ __forceinline__ void bulk_load(uint32_t dst, const void* src, uint32_t bytes, uint32_t bar) {
  asm volatile("cp.async.bulk.shared::cluster.global.mbarrier::complete_tx::bytes [%0], [%1], %2, [%3];" ::"r"(sw(dst)),
               "l"(src), "r"(bytes), "r"(sw(bar))
               : "memory");
}
__device__ __forceinline__ void bulk_store(void* dst, uint32_t src, uint32_t bytes) {
  asm volatile("cp.async.bulk.global.shared::cta.bulk_group [%0], [%1], %2;" ::"l"(dst), "r"(sw(src)), "r"(bytes) : "memory");
}
__device__ __forceinline__ void tma_store_3d(const CUtensorMap* map, uint32_t src, int c0, int c1, int c2) {
  asm volatile("cp.async.bulk.tensor.3d.global.shared::cta.bulk_group [%0, {%2, %3, %4}], [%1];" ::"l"(map), "r"(sw(src)),
               "r"(c0), "r"(c1), "r"(c2)
               : "memory");
}
__device__ __forceinline__ void bulk_commit() { asm volatile("cp.async.bulk.commit_group;" ::: "memory"); }
__device__ __forceinline__ void bulk_wait_read0() { asm volatile("cp.async.bulk.wait_group.read 0;" ::: "memory"); }
__device__ __forceinline__ void bulk_wait0() { asm volatile("cp.async.bulk.wait_group 0;" ::: "memory"); }
__device__ __forceinline__ void named_bar_sync(int id, int nthreads) {
  asm volatile("bar.sync %0, %1;" ::"r"(id), "r"(nthreads) : "memory");
}
__device__ __forceinline__ void named_bar_arrive(int id, int nthreads) {
  asm volatile("bar.arrive %0, %1;" ::"r"(id), "r"(nthreads) : "memory");
}

__device__ __forceinline__ void wgmma_fence() { asm volatile("wgmma.fence.sync.aligned;\n" ::: "memory"); }
__device__ __forceinline__ void wgmma_commit() { asm volatile("wgmma.commit_group.sync.aligned;\n" ::: "memory"); }
template <int N>
__device__ __forceinline__ void wgmma_wait() {
  asm volatile("wgmma.wait_group.sync.aligned %0;\n" ::"n"(N) : "memory");
}
template <int R>
__device__ __forceinline__ void setmaxnreg_inc() { asm volatile("setmaxnreg.inc.sync.aligned.u32 %0;\n" ::"n"(R)); }
template <int R>
__device__ __forceinline__ void setmaxnreg_dec() { asm volatile("setmaxnreg.dec.sync.aligned.u32 %0;\n" ::"n"(R)); }
template <int N>
__device__ __forceinline__ void reg_fence(float* r) {
#pragma unroll
  for (int i = 0; i < N; i++) asm volatile("" : "+f"(r[i])::"memory");
}

template <int N>
__device__ __forceinline__ void reg_define(float* r) {
#pragma unroll
  for (int i = 0; i < N; i++) r[i] = 0.f;
}

__device__ __forceinline__ uint64_t desc_lo(uint32_t lo) {
  uint64_t d;
  asm("mov.b64 %0, {%1, %2};" : "=l"(d) : "r"(lo), "r"(0x40000040u));
  return d;
}
__device__ __forceinline__ uint64_t make_desc(uint32_t addr, uint32_t lbo_bytes) {
  return desc_lo((addr >> 4) + ((lbo_bytes >> 4) << 16));
}

__device__ __forceinline__ void wgmma_n192_ss_ta0_tb1(float* d, uint64_t descA, uint64_t descB, int scaleD) {
  asm volatile("{\n.reg .pred p;\nsetp.ne.b32 p, %98, 0;\n"
    "wgmma.mma_async.sync.aligned.m64n192k16.f32.bf16.bf16 {%0, %1, %2, %3, %4, %5, %6, %7, %8, %9, %10, %11, %12, %13, %14, %15, %16, %17, %18, %19, %20, %21, %22, %23, %24, %25, %26, %27, %28, %29, %30, %31, %32, %33, %34, %35, %36, %37, %38, %39, %40, %41, %42, %43, %44, %45, %46, %47, %48, %49, %50, %51, %52, %53, %54, %55, %56, %57, %58, %59, %60, %61, %62, %63, %64, %65, %66, %67, %68, %69, %70, %71, %72, %73, %74, %75, %76, %77, %78, %79, %80, %81, %82, %83, %84, %85, %86, %87, %88, %89, %90, %91, %92, %93, %94, %95}, %96, %97, p, 1, 1, 0, 1;\n}\n"
    : "+f"(d[0]), "+f"(d[1]), "+f"(d[2]), "+f"(d[3]), "+f"(d[4]), "+f"(d[5]), "+f"(d[6]), "+f"(d[7]), "+f"(d[8]), "+f"(d[9]), "+f"(d[10]), "+f"(d[11]), "+f"(d[12]), "+f"(d[13]), "+f"(d[14]), "+f"(d[15]), "+f"(d[16]), "+f"(d[17]), "+f"(d[18]), "+f"(d[19]), "+f"(d[20]), "+f"(d[21]), "+f"(d[22]), "+f"(d[23]), "+f"(d[24]), "+f"(d[25]), "+f"(d[26]), "+f"(d[27]), "+f"(d[28]), "+f"(d[29]), "+f"(d[30]), "+f"(d[31]), "+f"(d[32]), "+f"(d[33]), "+f"(d[34]), "+f"(d[35]), "+f"(d[36]), "+f"(d[37]), "+f"(d[38]), "+f"(d[39]), "+f"(d[40]), "+f"(d[41]), "+f"(d[42]), "+f"(d[43]), "+f"(d[44]), "+f"(d[45]), "+f"(d[46]), "+f"(d[47]), "+f"(d[48]), "+f"(d[49]), "+f"(d[50]), "+f"(d[51]), "+f"(d[52]), "+f"(d[53]), "+f"(d[54]), "+f"(d[55]), "+f"(d[56]), "+f"(d[57]), "+f"(d[58]), "+f"(d[59]), "+f"(d[60]), "+f"(d[61]), "+f"(d[62]), "+f"(d[63]), "+f"(d[64]), "+f"(d[65]), "+f"(d[66]), "+f"(d[67]), "+f"(d[68]), "+f"(d[69]), "+f"(d[70]), "+f"(d[71]), "+f"(d[72]), "+f"(d[73]), "+f"(d[74]), "+f"(d[75]), "+f"(d[76]), "+f"(d[77]), "+f"(d[78]), "+f"(d[79]), "+f"(d[80]), "+f"(d[81]), "+f"(d[82]), "+f"(d[83]), "+f"(d[84]), "+f"(d[85]), "+f"(d[86]), "+f"(d[87]), "+f"(d[88]), "+f"(d[89]), "+f"(d[90]), "+f"(d[91]), "+f"(d[92]), "+f"(d[93]), "+f"(d[94]), "+f"(d[95])
    : "l"(descA), "l"(descB), "r"(scaleD));
}

__device__ __forceinline__ void wgmma_n128_ss_ta0_tb1(float* d, uint64_t descA, uint64_t descB, int scaleD) {
  asm volatile("{\n.reg .pred p;\nsetp.ne.b32 p, %66, 0;\n"
    "wgmma.mma_async.sync.aligned.m64n128k16.f32.bf16.bf16 {%0, %1, %2, %3, %4, %5, %6, %7, %8, %9, %10, %11, %12, %13, %14, %15, %16, %17, %18, %19, %20, %21, %22, %23, %24, %25, %26, %27, %28, %29, %30, %31, %32, %33, %34, %35, %36, %37, %38, %39, %40, %41, %42, %43, %44, %45, %46, %47, %48, %49, %50, %51, %52, %53, %54, %55, %56, %57, %58, %59, %60, %61, %62, %63}, %64, %65, p, 1, 1, 0, 1;\n}\n"
    : "+f"(d[0]), "+f"(d[1]), "+f"(d[2]), "+f"(d[3]), "+f"(d[4]), "+f"(d[5]), "+f"(d[6]), "+f"(d[7]), "+f"(d[8]), "+f"(d[9]), "+f"(d[10]), "+f"(d[11]), "+f"(d[12]), "+f"(d[13]), "+f"(d[14]), "+f"(d[15]), "+f"(d[16]), "+f"(d[17]), "+f"(d[18]), "+f"(d[19]), "+f"(d[20]), "+f"(d[21]), "+f"(d[22]), "+f"(d[23]), "+f"(d[24]), "+f"(d[25]), "+f"(d[26]), "+f"(d[27]), "+f"(d[28]), "+f"(d[29]), "+f"(d[30]), "+f"(d[31]), "+f"(d[32]), "+f"(d[33]), "+f"(d[34]), "+f"(d[35]), "+f"(d[36]), "+f"(d[37]), "+f"(d[38]), "+f"(d[39]), "+f"(d[40]), "+f"(d[41]), "+f"(d[42]), "+f"(d[43]), "+f"(d[44]), "+f"(d[45]), "+f"(d[46]), "+f"(d[47]), "+f"(d[48]), "+f"(d[49]), "+f"(d[50]), "+f"(d[51]), "+f"(d[52]), "+f"(d[53]), "+f"(d[54]), "+f"(d[55]), "+f"(d[56]), "+f"(d[57]), "+f"(d[58]), "+f"(d[59]), "+f"(d[60]), "+f"(d[61]), "+f"(d[62]), "+f"(d[63])
    : "l"(descA), "l"(descB), "r"(scaleD));
}

__device__ __forceinline__ void wgmma_n192_ssz_ta0_tb1(float* d, uint64_t descA, uint64_t descB) {
  asm volatile("{\n.reg .pred p;\nsetp.ne.b32 p, 0, 0;\n"
    "wgmma.mma_async.sync.aligned.m64n192k16.f32.bf16.bf16 {%0, %1, %2, %3, %4, %5, %6, %7, %8, %9, %10, %11, %12, %13, %14, %15, %16, %17, %18, %19, %20, %21, %22, %23, %24, %25, %26, %27, %28, %29, %30, %31, %32, %33, %34, %35, %36, %37, %38, %39, %40, %41, %42, %43, %44, %45, %46, %47, %48, %49, %50, %51, %52, %53, %54, %55, %56, %57, %58, %59, %60, %61, %62, %63, %64, %65, %66, %67, %68, %69, %70, %71, %72, %73, %74, %75, %76, %77, %78, %79, %80, %81, %82, %83, %84, %85, %86, %87, %88, %89, %90, %91, %92, %93, %94, %95}, %96, %97, p, 1, 1, 0, 1;\n}\n"
    : "=f"(d[0]), "=f"(d[1]), "=f"(d[2]), "=f"(d[3]), "=f"(d[4]), "=f"(d[5]), "=f"(d[6]), "=f"(d[7]), "=f"(d[8]), "=f"(d[9]), "=f"(d[10]), "=f"(d[11]), "=f"(d[12]), "=f"(d[13]), "=f"(d[14]), "=f"(d[15]), "=f"(d[16]), "=f"(d[17]), "=f"(d[18]), "=f"(d[19]), "=f"(d[20]), "=f"(d[21]), "=f"(d[22]), "=f"(d[23]), "=f"(d[24]), "=f"(d[25]), "=f"(d[26]), "=f"(d[27]), "=f"(d[28]), "=f"(d[29]), "=f"(d[30]), "=f"(d[31]), "=f"(d[32]), "=f"(d[33]), "=f"(d[34]), "=f"(d[35]), "=f"(d[36]), "=f"(d[37]), "=f"(d[38]), "=f"(d[39]), "=f"(d[40]), "=f"(d[41]), "=f"(d[42]), "=f"(d[43]), "=f"(d[44]), "=f"(d[45]), "=f"(d[46]), "=f"(d[47]), "=f"(d[48]), "=f"(d[49]), "=f"(d[50]), "=f"(d[51]), "=f"(d[52]), "=f"(d[53]), "=f"(d[54]), "=f"(d[55]), "=f"(d[56]), "=f"(d[57]), "=f"(d[58]), "=f"(d[59]), "=f"(d[60]), "=f"(d[61]), "=f"(d[62]), "=f"(d[63]), "=f"(d[64]), "=f"(d[65]), "=f"(d[66]), "=f"(d[67]), "=f"(d[68]), "=f"(d[69]), "=f"(d[70]), "=f"(d[71]), "=f"(d[72]), "=f"(d[73]), "=f"(d[74]), "=f"(d[75]), "=f"(d[76]), "=f"(d[77]), "=f"(d[78]), "=f"(d[79]), "=f"(d[80]), "=f"(d[81]), "=f"(d[82]), "=f"(d[83]), "=f"(d[84]), "=f"(d[85]), "=f"(d[86]), "=f"(d[87]), "=f"(d[88]), "=f"(d[89]), "=f"(d[90]), "=f"(d[91]), "=f"(d[92]), "=f"(d[93]), "=f"(d[94]), "=f"(d[95])
    : "l"(descA), "l"(descB));
}

__device__ __forceinline__ void wgmma_n192_rs_tb1(float* d, uint32_t a0, uint32_t a1, uint64_t descB) {
  asm volatile("{\n.reg .pred p;\nsetp.eq.b32 p, 0, 0;\n"
    "wgmma.mma_async.sync.aligned.m64n192k16.f32.bf16.bf16 {%0, %1, %2, %3, %4, %5, %6, %7, %8, %9, %10, %11, %12, %13, %14, %15, %16, %17, %18, %19, %20, %21, %22, %23, %24, %25, %26, %27, %28, %29, %30, %31, %32, %33, %34, %35, %36, %37, %38, %39, %40, %41, %42, %43, %44, %45, %46, %47, %48, %49, %50, %51, %52, %53, %54, %55, %56, %57, %58, %59, %60, %61, %62, %63, %64, %65, %66, %67, %68, %69, %70, %71, %72, %73, %74, %75, %76, %77, %78, %79, %80, %81, %82, %83, %84, %85, %86, %87, %88, %89, %90, %91, %92, %93, %94, %95}, {%96, %97, %98, %98}, %99, p, 1, 1, 1;\n}\n"
    : "+f"(d[0]), "+f"(d[1]), "+f"(d[2]), "+f"(d[3]), "+f"(d[4]), "+f"(d[5]), "+f"(d[6]), "+f"(d[7]), "+f"(d[8]), "+f"(d[9]), "+f"(d[10]), "+f"(d[11]), "+f"(d[12]), "+f"(d[13]), "+f"(d[14]), "+f"(d[15]), "+f"(d[16]), "+f"(d[17]), "+f"(d[18]), "+f"(d[19]), "+f"(d[20]), "+f"(d[21]), "+f"(d[22]), "+f"(d[23]), "+f"(d[24]), "+f"(d[25]), "+f"(d[26]), "+f"(d[27]), "+f"(d[28]), "+f"(d[29]), "+f"(d[30]), "+f"(d[31]), "+f"(d[32]), "+f"(d[33]), "+f"(d[34]), "+f"(d[35]), "+f"(d[36]), "+f"(d[37]), "+f"(d[38]), "+f"(d[39]), "+f"(d[40]), "+f"(d[41]), "+f"(d[42]), "+f"(d[43]), "+f"(d[44]), "+f"(d[45]), "+f"(d[46]), "+f"(d[47]), "+f"(d[48]), "+f"(d[49]), "+f"(d[50]), "+f"(d[51]), "+f"(d[52]), "+f"(d[53]), "+f"(d[54]), "+f"(d[55]), "+f"(d[56]), "+f"(d[57]), "+f"(d[58]), "+f"(d[59]), "+f"(d[60]), "+f"(d[61]), "+f"(d[62]), "+f"(d[63]), "+f"(d[64]), "+f"(d[65]), "+f"(d[66]), "+f"(d[67]), "+f"(d[68]), "+f"(d[69]), "+f"(d[70]), "+f"(d[71]), "+f"(d[72]), "+f"(d[73]), "+f"(d[74]), "+f"(d[75]), "+f"(d[76]), "+f"(d[77]), "+f"(d[78]), "+f"(d[79]), "+f"(d[80]), "+f"(d[81]), "+f"(d[82]), "+f"(d[83]), "+f"(d[84]), "+f"(d[85]), "+f"(d[86]), "+f"(d[87]), "+f"(d[88]), "+f"(d[89]), "+f"(d[90]), "+f"(d[91]), "+f"(d[92]), "+f"(d[93]), "+f"(d[94]), "+f"(d[95])
    : "r"(a0), "r"(a1), "r"(0u), "l"(descB));
}

__device__ __forceinline__ void wgmma_n128_ssz_ta0_tb1(float* d, uint64_t descA, uint64_t descB) {
  asm volatile("{\n.reg .pred p;\nsetp.ne.b32 p, 0, 0;\n"
    "wgmma.mma_async.sync.aligned.m64n128k16.f32.bf16.bf16 {%0, %1, %2, %3, %4, %5, %6, %7, %8, %9, %10, %11, %12, %13, %14, %15, %16, %17, %18, %19, %20, %21, %22, %23, %24, %25, %26, %27, %28, %29, %30, %31, %32, %33, %34, %35, %36, %37, %38, %39, %40, %41, %42, %43, %44, %45, %46, %47, %48, %49, %50, %51, %52, %53, %54, %55, %56, %57, %58, %59, %60, %61, %62, %63}, %64, %65, p, 1, 1, 0, 1;\n}\n"
    : "=f"(d[0]), "=f"(d[1]), "=f"(d[2]), "=f"(d[3]), "=f"(d[4]), "=f"(d[5]), "=f"(d[6]), "=f"(d[7]), "=f"(d[8]), "=f"(d[9]), "=f"(d[10]), "=f"(d[11]), "=f"(d[12]), "=f"(d[13]), "=f"(d[14]), "=f"(d[15]), "=f"(d[16]), "=f"(d[17]), "=f"(d[18]), "=f"(d[19]), "=f"(d[20]), "=f"(d[21]), "=f"(d[22]), "=f"(d[23]), "=f"(d[24]), "=f"(d[25]), "=f"(d[26]), "=f"(d[27]), "=f"(d[28]), "=f"(d[29]), "=f"(d[30]), "=f"(d[31]), "=f"(d[32]), "=f"(d[33]), "=f"(d[34]), "=f"(d[35]), "=f"(d[36]), "=f"(d[37]), "=f"(d[38]), "=f"(d[39]), "=f"(d[40]), "=f"(d[41]), "=f"(d[42]), "=f"(d[43]), "=f"(d[44]), "=f"(d[45]), "=f"(d[46]), "=f"(d[47]), "=f"(d[48]), "=f"(d[49]), "=f"(d[50]), "=f"(d[51]), "=f"(d[52]), "=f"(d[53]), "=f"(d[54]), "=f"(d[55]), "=f"(d[56]), "=f"(d[57]), "=f"(d[58]), "=f"(d[59]), "=f"(d[60]), "=f"(d[61]), "=f"(d[62]), "=f"(d[63])
    : "l"(descA), "l"(descB));
}

__device__ __forceinline__ void wgmma_n64_ss_ta0_tb0(float* d, uint64_t descA, uint64_t descB, int scaleD) {
  asm volatile("{\n.reg .pred p;\nsetp.ne.b32 p, %34, 0;\n"
    "wgmma.mma_async.sync.aligned.m64n64k16.f32.bf16.bf16 {%0, %1, %2, %3, %4, %5, %6, %7, %8, %9, %10, %11, %12, %13, %14, %15, %16, %17, %18, %19, %20, %21, %22, %23, %24, %25, %26, %27, %28, %29, %30, %31}, %32, %33, p, 1, 1, 0, 0;\n}\n"
    : "+f"(d[0]), "+f"(d[1]), "+f"(d[2]), "+f"(d[3]), "+f"(d[4]), "+f"(d[5]), "+f"(d[6]), "+f"(d[7]), "+f"(d[8]), "+f"(d[9]), "+f"(d[10]), "+f"(d[11]), "+f"(d[12]), "+f"(d[13]), "+f"(d[14]), "+f"(d[15]), "+f"(d[16]), "+f"(d[17]), "+f"(d[18]), "+f"(d[19]), "+f"(d[20]), "+f"(d[21]), "+f"(d[22]), "+f"(d[23]), "+f"(d[24]), "+f"(d[25]), "+f"(d[26]), "+f"(d[27]), "+f"(d[28]), "+f"(d[29]), "+f"(d[30]), "+f"(d[31])
    : "l"(descA), "l"(descB), "r"(scaleD));
}

__device__ __forceinline__ void wgmma_n64_ssz_ta0_tb0(float* d, uint64_t descA, uint64_t descB) {
  asm volatile("{\n.reg .pred p;\nsetp.ne.b32 p, 0, 0;\n"
    "wgmma.mma_async.sync.aligned.m64n64k16.f32.bf16.bf16 {%0, %1, %2, %3, %4, %5, %6, %7, %8, %9, %10, %11, %12, %13, %14, %15, %16, %17, %18, %19, %20, %21, %22, %23, %24, %25, %26, %27, %28, %29, %30, %31}, %32, %33, p, 1, 1, 0, 0;\n}\n"
    : "=f"(d[0]), "=f"(d[1]), "=f"(d[2]), "=f"(d[3]), "=f"(d[4]), "=f"(d[5]), "=f"(d[6]), "=f"(d[7]), "=f"(d[8]), "=f"(d[9]), "=f"(d[10]), "=f"(d[11]), "=f"(d[12]), "=f"(d[13]), "=f"(d[14]), "=f"(d[15]), "=f"(d[16]), "=f"(d[17]), "=f"(d[18]), "=f"(d[19]), "=f"(d[20]), "=f"(d[21]), "=f"(d[22]), "=f"(d[23]), "=f"(d[24]), "=f"(d[25]), "=f"(d[26]), "=f"(d[27]), "=f"(d[28]), "=f"(d[29]), "=f"(d[30]), "=f"(d[31])
    : "l"(descA), "l"(descB));
}

__device__ __forceinline__ void wgmma_n80_ss_ta0_tb0(float* d, uint64_t descA, uint64_t descB, int scaleD) {
  asm volatile("{\n.reg .pred p;\nsetp.ne.b32 p, %42, 0;\n"
    "wgmma.mma_async.sync.aligned.m64n80k16.f32.bf16.bf16 {%0, %1, %2, %3, %4, %5, %6, %7, %8, %9, %10, %11, %12, %13, %14, %15, %16, %17, %18, %19, %20, %21, %22, %23, %24, %25, %26, %27, %28, %29, %30, %31, %32, %33, %34, %35, %36, %37, %38, %39}, %40, %41, p, 1, 1, 0, 0;\n}\n"
    : "+f"(d[0]), "+f"(d[1]), "+f"(d[2]), "+f"(d[3]), "+f"(d[4]), "+f"(d[5]), "+f"(d[6]), "+f"(d[7]), "+f"(d[8]), "+f"(d[9]), "+f"(d[10]), "+f"(d[11]), "+f"(d[12]), "+f"(d[13]), "+f"(d[14]), "+f"(d[15]), "+f"(d[16]), "+f"(d[17]), "+f"(d[18]), "+f"(d[19]), "+f"(d[20]), "+f"(d[21]), "+f"(d[22]), "+f"(d[23]), "+f"(d[24]), "+f"(d[25]), "+f"(d[26]), "+f"(d[27]), "+f"(d[28]), "+f"(d[29]), "+f"(d[30]), "+f"(d[31]), "+f"(d[32]), "+f"(d[33]), "+f"(d[34]), "+f"(d[35]), "+f"(d[36]), "+f"(d[37]), "+f"(d[38]), "+f"(d[39])
    : "l"(descA), "l"(descB), "r"(scaleD));
}

__device__ __forceinline__ void wgmma_n32_rs_tb1(float* d, const uint32_t* a, uint64_t descB, int scaleD) {
  asm volatile("{\n.reg .pred p;\nsetp.ne.b32 p, %21, 0;\n"
    "wgmma.mma_async.sync.aligned.m64n32k16.f32.bf16.bf16 {%0, %1, %2, %3, %4, %5, %6, %7, %8, %9, %10, %11, %12, %13, %14, %15}, {%16, %17, %18, %19}, %20, p, 1, 1, 1;\n}\n"
    : "+f"(d[0]), "+f"(d[1]), "+f"(d[2]), "+f"(d[3]), "+f"(d[4]), "+f"(d[5]), "+f"(d[6]), "+f"(d[7]), "+f"(d[8]), "+f"(d[9]), "+f"(d[10]), "+f"(d[11]), "+f"(d[12]), "+f"(d[13]), "+f"(d[14]), "+f"(d[15])
    : "r"(a[0]), "r"(a[1]), "r"(a[2]), "r"(a[3]), "l"(descB), "r"(scaleD));
}

__device__ __forceinline__ uint32_t pack_bf16x2(float lo, float hi) {
  uint32_t r;
  asm("cvt.rn.bf16x2.f32 %0, %1, %2;" : "=r"(r) : "f"(hi), "f"(lo));
  return r;
}
__device__ __forceinline__ float bf_lo(uint32_t p) { return __uint_as_float(p << 16); }
__device__ __forceinline__ float bf_hi(uint32_t p) { return __uint_as_float(p & 0xffff0000u); }
__device__ __forceinline__ float bf16_round(float v) { return __bfloat162float(__float2bfloat16_rn(v)); }
__device__ __forceinline__ float ex2_approx(float x) {
  float r;
  asm("ex2.approx.ftz.f32 %0, %1;" : "=f"(r) : "f"(x));
  return r;
}
__device__ __forceinline__ float rcp_fast(float x) {
  float r;
  asm("rcp.approx.ftz.f32 %0, %1;" : "=f"(r) : "f"(x));
  return r;
}
__device__ __forceinline__ void ldmatrix_x4(uint32_t (&r)[4], uint32_t addr) {
  asm volatile("ldmatrix.sync.aligned.m8n8.x4.shared.b16 {%0,%1,%2,%3}, [%4];"
               : "=r"(r[0]), "=r"(r[1]), "=r"(r[2]), "=r"(r[3])
               : "r"(sw(addr))
               : "memory");
}
__device__ __forceinline__ void stmatrix_x4(uint32_t addr, uint32_t r0, uint32_t r1, uint32_t r2, uint32_t r3) {
  asm volatile("stmatrix.sync.aligned.m8n8.x4.shared.b16 [%0], {%1,%2,%3,%4};" ::"r"(sw(addr)), "r"(r0), "r"(r1), "r"(r2),
               "r"(r3));
}
__device__ __forceinline__ uint32_t add_bf16x2(uint32_t a, uint32_t b) {
  uint32_t r;
  asm("add.rn.bf16x2 %0, %1, %2;" : "=r"(r) : "r"(a), "r"(b));
  return r;
}
__device__ __forceinline__ uint4 lds128(uint32_t addr) {
  uint4 v;
  asm volatile("ld.shared.v4.b32 {%0,%1,%2,%3}, [%4];" : "=r"(v.x), "=r"(v.y), "=r"(v.z), "=r"(v.w) : "r"(sw(addr)) : "memory");
  return v;
}
__device__ __forceinline__ uint32_t lds32(uint32_t addr) {
  uint32_t v;
  asm volatile("ld.shared.b32 %0, [%1];" : "=r"(v) : "r"(sw(addr)) : "memory");
  return v;
}
__device__ __forceinline__ void sts32(uint32_t addr, uint32_t v) {
  asm volatile("st.shared.b32 [%0], %1;" ::"r"(sw(addr)), "r"(v) : "memory");
}

__device__ __forceinline__ unsigned ld_acquire_u32(const unsigned* p) {
  unsigned v;
  asm volatile("ld.acquire.gpu.global.u32 %0, [%1];" : "=r"(v) : "l"(p) : "memory");
  return v;
}
__device__ __forceinline__ void red_relaxed_add(unsigned* p, unsigned v) {
  asm volatile("red.relaxed.gpu.global.add.u32 [%0], %1;" ::"l"(p), "r"(v) : "memory");
}
__device__ __forceinline__ void wait_ge(const unsigned* p, unsigned target) {
#pragma unroll 1
  for (uint32_t it = 0; it < (1u << 17); ++it) {
    if ((int)(ld_acquire_u32(p) - target) >= 0) return;
  }
}

__device__ __forceinline__ void wait_ge2(const unsigned* p, unsigned t0, unsigned t1) {
#pragma unroll 1
  for (uint32_t it = 0; it < (1u << 17); ++it) {
    unsigned long long v;
    asm volatile("ld.acquire.gpu.global.u64 %0, [%1];" : "=l"(v) : "l"(p) : "memory");
    if ((int)((unsigned)v - t0) >= 0 && (int)((unsigned)(v >> 32) - t1) >= 0) return;
  }
}

#define PDEPTH 1
#define RELNS 100
#define HDELAY 500
#define PUBPOS 0
#define PGAP 100
template <bool SLOW>
__device__ __forceinline__ void wait_mask(const unsigned* f, int cnt, unsigned target, uint32_t need, uint32_t& seen, int lane) {
  if ((seen & need) == need) return;
  const unsigned* fp = f + (lane & (cnt - 1));
#pragma unroll 1
  for (uint32_t it = 0; it < (1u << 17); ++it) {
    seen = __ballot_sync(0xffffffffu, (int)(ld_acquire_u32(fp) - target) >= 0);
    if ((seen & need) == need) break;
    if (SLOW) __nanosleep(400);
  }
  fence_proxy_async_all();
}
__device__ __forceinline__ void wait_lanes(const unsigned* fp, unsigned target, uint32_t need, uint32_t& seen) {
  if ((seen & need) == need) return;
  unsigned v[PDEPTH];
#pragma unroll
  for (int i = 0; i < PDEPTH; i++) {
    asm volatile("ld.relaxed.gpu.global.u32 %0, [%1];" : "=r"(v[i]) : "l"(fp) : "memory");
    if (i + 1 < PDEPTH) __nanosleep(PGAP);
  }
#pragma unroll 1
  for (uint32_t it = 0; it < (1u << 16); ++it) {
#pragma unroll
    for (int i = 0; i < PDEPTH; i++) {
      seen |= __ballot_sync(0xffffffffu, (int)(v[i] - target) >= 0);
      if ((seen & need) == need) goto done;
      asm volatile("ld.relaxed.gpu.global.u32 %0, [%1];" : "=r"(v[i]) : "l"(fp) : "memory");
    }
  }
done:
  fence_proxy_async_all();
}
__device__ __forceinline__ float4 ld_rec(const float4* p) {
  float4 v;
  asm volatile("ld.relaxed.gpu.global.v4.f32 {%0,%1,%2,%3}, [%4];" : "=f"(v.x), "=f"(v.y), "=f"(v.z), "=f"(v.w) : "l"(p) : "memory");
  return v;
}
__device__ __forceinline__ void st_rec(float4* p, float a, float b, float c, unsigned tag) {
  asm volatile("st.relaxed.gpu.global.v4.f32 [%0], {%1,%2,%3,%4};" ::"l"(p), "f"(a), "f"(b), "f"(c), "f"(__uint_as_float(tag)) : "memory");
}
template <int N>
__device__ __forceinline__ float4 sum_recs(const float4* p, int stride, unsigned tag) {
  float4 s;
#pragma unroll 1
  for (uint32_t it = 0; it < (1u << 17); ++it) {
    float4 v[N];
#pragma unroll
    for (int t = 0; t < N; t++) v[t] = ld_rec(p + t * stride);
    bool ok = true;
    s = make_float4(0.f, 0.f, 0.f, 0.f);
#pragma unroll
    for (int t = 0; t < N; t++) {
      ok &= __float_as_uint(v[t].w) == tag;
      s.x += v[t].x;
      s.y += v[t].y;
      s.z += v[t].z;
    }
    if (ok) break;
    __nanosleep(200);
  }
  return s;
}

__device__ __forceinline__ int fresh_tid() {
  int t;
  asm volatile("mov.u32 %0, %%tid.x;" : "=r"(t));
  return t;
}
#define PHASE_IDS                                  \
  const int tid_ = fresh_tid();                    \
  const int lane = tid_ & 31, wwarp = __shfl_sync(0xffffffffu, (tid_ >> 5) & 3, 0), tid = tid_ & 127; \
  const int g = lane >> 2, c = lane & 3;           \
  (void)tid; (void)g; (void)c; (void)wwarp;

#define STAMPW(cond, i) do { } while (0)
#define STAMP(cond, i) do { } while (0)
#define KSPN true
#define STA(i) do { } while (0)
#define GTL(i) do { } while (0)
#define GTLX(c, i) do { } while (0)
#define TGET(v) do { } while (0)
#define TPUT(c, i, v) do { } while (0)

constexpr float SM_C = 0.17677669529663687f * 1.4426950408889634f;

constexpr uint32_t OA_TILE = SBASE + OFF_SLOT + 16384;

__device__ __forceinline__ void sched_fence(uint32_t never) {
  asm volatile("{\n.reg .pred p;\nsetp.ne.u32 p, %0, 0;\n@p exit;\n}\n" ::"r"(never) : "memory");
}

template <int K0, int K1>
__device__ __forceinline__ void attn_exp(float (&s)[32]) {
#pragma unroll
  for (int k = K0; k < K1; k++) s[k] = ex2_approx(s[k]);
}
#define ASPL 16
#define ASPM 6
template <int MODE, bool NEXT>
__device__ __forceinline__ void attn_unit(float (&s)[32], float (&sn)[32], float (&o)[16], float (&l)[2], bool valid,
                                          uint32_t vdesc, uint32_t qdesc, uint32_t kdesc, uint32_t tri, int w,
                                          uint32_t hbar, uint32_t hpar, uint32_t rel, uint32_t zero, bool stampon = false) {
  float x[9][2];
  if (MODE == 0) {
    attn_exp<0, ASPL>(s);
  } else {
#pragma unroll
    for (int e = 0; e < 2; e++) {
#pragma unroll
      for (int j = 0; j < 4; j++) x[j][e] = MODE == 1 ? s[4 * j + 2 + e] : s[16 + 4 * j + e];
      x[4][e] = MODE == 1 ? s[e] : s[30 + e];
      x[5][e] = MODE == 1 ? s[18 + e] : s[12 + e];
#pragma unroll
      for (int u = 1; u < 4; u++)
        x[5 + u][e] = MODE == 1 ? (w >= u ? s[4 * u + e] : s[4 * (8 - u) + 2 + e]) : (w >= u ? s[4 * (7 - u) + 2 + e] : s[4 * (u - 1) + e]);
    }
#pragma unroll
    for (int k = 0; k < 2 * ASPM; k++) x[k >> 1][k & 1] = ex2_approx(x[k >> 1][k & 1]);
  }
  sched_fence(zero);
  if (hbar) mbar_wait(hbar, hpar);
  wgmma_wait<0>();
  if (rel) mbar_arrive(rel);
  if (NEXT) {
    wgmma_fence();
    wgmma_n64_ssz_ta0_tb0(sn, desc_lo(qdesc), desc_lo(kdesc));
    wgmma_n64_ss_ta0_tb0(sn, desc_lo(qdesc + 2), desc_lo(kdesc + 2), 1);
    wgmma_commit();
    sched_fence(zero);
  }
  uint32_t p[16];
  if (MODE == 0) {
    attn_exp<ASPL, 32>(s);
#pragma unroll
    for (int k = 0; k < 16; k++) p[k] = pack_bf16x2(s[2 * k], s[2 * k + 1]);
  } else {
#pragma unroll
    for (int k = 2 * ASPM; k < 18; k++) x[k >> 1][k & 1] = ex2_approx(x[k >> 1][k & 1]);
    const uint32_t tm = MODE == 1 ? tri : ~tri;
#pragma unroll
    for (int j = 0; j < 4; j++) {
      p[MODE == 1 ? 2 * j + 1 : 8 + 2 * j] = pack_bf16x2(x[j][0], x[j][1]);
      p[MODE == 1 ? 8 + 2 * j : 2 * j + 1] = 0u;
    }
    p[MODE == 1 ? 0 : 15] = pack_bf16x2(x[4][0], x[4][1]) & (w == 0 ? tm : 0xffffffffu);
    p[MODE == 1 ? 9 : 6] = pack_bf16x2(x[5][0], x[5][1]) & (w == 3 ? tm : 0xffffffffu);
#pragma unroll
    for (int u = 1; u < 4; u++) {
      const uint32_t q = pack_bf16x2(x[5 + u][0], x[5 + u][1]);
      p[MODE == 1 ? 2 * u : 2 * (7 - u) + 1] = q & (w > u ? 0xffffffffu : (w == u ? tm : 0u));
      p[MODE == 1 ? 2 * (8 - u) + 1 : 2 * (u - 1)] = q & (w < u - 1 ? 0xffffffffu : (w == u - 1 ? tm : 0u));
    }
  }
  wgmma_fence();
#pragma unroll
  for (int k = 0; k < 4; k++) wgmma_n32_rs_tb1(o, p + 4 * k, desc_lo(vdesc + k * 128), 1);
  wgmma_commit();
#pragma unroll
  for (int r = 0; r < 2; r++) {
    float t = 0.f;
#pragma unroll
    for (int hf = 0; hf < 2; hf++) {
      if (MODE != 0 && r == MODE - 1 && hf == 2 - MODE) continue;
      const uint32_t* q = p + 8 * hf + r;
      const uint32_t v = add_bf16x2(add_bf16x2(q[0], q[2]), add_bf16x2(q[4], q[6]));
      t = (MODE != 0 && r == MODE - 1) || hf == 0 ? bf_lo(v) + bf_hi(v) : t + (bf_lo(v) + bf_hi(v));
    }
    if (valid) l[r] += t;
  }
  if (NEXT) {
    wgmma_wait<1>();
    reg_fence<32>(sn);
  }
}

__device__ __forceinline__ void attn_a_slow(const uint8_t* __restrict__ kvimg, int L, int gb, int hp,
                                         int hh, int wwarp, int lane) {
  constexpr uint32_t sq = SBASE + OFF_SLOT + 3 * 16384;
  const unsigned ep = (*(volatile unsigned*)(g_flags + F_DONE)) / NCTA;
  wait_ge2(g_flags + F_KV + (gb * 16 + hp) * KSTR, 4u * ep + L + 1u, 2u * ep + (L >> 1) + 1u);
#pragma unroll 1
  for (int t = 0; t < 32; t++) {
    const int row = (t >> 4) * 64 + ((t & 8) ? 7 - wwarp : wwarp) * 8 + (t & 7);
    const int qpos = gb * 128 + row;
    const uint32_t qaddr = sq + ((t >> 4) * 64 + wwarp * 16 + (t & 15)) * 128;
    float mx = -INFINITY, sum = 0.f, acc = 0.f;
#pragma unroll 1
    for (int pass = 0; pass < 2; pass++) {
#pragma unroll 1
      for (int j = 0; j < 8; j++) {
        const int kp = qpos - (lane + 32 * j);
        const uint8_t* kr = kvimg + ((size_t)((kp >> 7) * 16 + hp) * 2 + ((kp >> 6) & 1)) * 16384 + (kp & 63) * 128;
        float d = -INFINITY;
        if (kp >= 0) {
          d = 0.f;
#pragma unroll 1
          for (int q = 0; q < 4; q++) {
            const uint4 kv = __ldcg(reinterpret_cast<const uint4*>(kr + (((hh * 4 + q) ^ (kp & 7)) << 4)));
            const uint4 qv = lds128(qaddr + (((hh * 4 + q) ^ (row & 7)) << 4));
            const uint32_t kw[4] = {kv.x, kv.y, kv.z, kv.w}, qw[4] = {qv.x, qv.y, qv.z, qv.w};
#pragma unroll
            for (int e = 0; e < 4; e++) d = fmaf(bf_lo(kw[e]), bf_lo(qw[e]), fmaf(bf_hi(kw[e]), bf_hi(qw[e]), d));
          }
        }
        if (pass == 0) {
          mx = fmaxf(mx, d);
        } else {
          const float ev = ex2_approx(d - mx);
          sum += ev;
          const float pv = bf16_round(ev);
#pragma unroll 1
          for (int kk = 0; kk < 32; kk++) {
            const float pk = __shfl_sync(0xffffffffu, pv, kk);
            const int k2 = qpos - (kk + 32 * j);
            if (k2 >= 0) {
              const uint8_t* vr = kvimg + ((size_t)((k2 >> 7) * 16 + hp) * 2 + ((k2 >> 6) & 1)) * 16384 + 8192 + (k2 & 63) * 128;
              const unsigned short vv =
                  __ldcg(reinterpret_cast<const unsigned short*>(vr + (((hh * 4 + (lane >> 3)) ^ (k2 & 7)) << 4) + (lane & 7) * 2));
              acc = fmaf(pk, __uint_as_float((uint32_t)vv << 16), acc);
            }
          }
        }
      }
      if (pass == 0) {
#pragma unroll
        for (int o = 16; o > 0; o >>= 1) mx = fmaxf(mx, __shfl_xor_sync(0xffffffffu, mx, o));
      }
    }
#pragma unroll
    for (int o = 16; o > 0; o >>= 1) sum += __shfl_xor_sync(0xffffffffu, sum, o);
    acc *= rcp_fast(sum);
    const float hi = __shfl_down_sync(0xffffffffu, acc, 1);
    __syncwarp();
    if ((lane & 1) == 0)
      sts32(OA_TILE + row * 128 + (((hh * 4 + (lane >> 3)) ^ (row & 7)) << 4) + (lane & 7) * 2, pack_bf16x2(acc, hi));
    __syncwarp();
  }
}

__device__ __forceinline__ void store_o(const float (&o)[16], const float (&inv)[2], uint32_t rowaddr, int hh, int lane) {
  const int mat = lane >> 3, r7 = lane & 7;
#pragma unroll
  for (int jp = 0; jp < 2; jp++)
    stmatrix_x4(rowaddr + (((hh * 4 + 2 * jp + (mat >> 1)) ^ r7) << 4),
                pack_bf16x2(o[8 * jp] * inv[0], o[8 * jp + 1] * inv[0]),
                pack_bf16x2(o[8 * jp + 2] * inv[1], o[8 * jp + 3] * inv[1]),
                pack_bf16x2(o[8 * jp + 4] * inv[0], o[8 * jp + 5] * inv[0]),
                pack_bf16x2(o[8 * jp + 6] * inv[1], o[8 * jp + 7] * inv[1]));
}

__device__ __forceinline__ void attention_a(int HH, int L, int gb, int hp, uint32_t par0, uint32_t parA, int wwarp, int lane,
                                            uint32_t zero) {
  constexpr uint32_t bars = SBASE + OFF_BAR;
  const uint32_t dslot = ((SBASE + OFF_SLOT) >> 4) + 0x10000u + HH * 4;
  const uint32_t dq = dslot + 3 * 1024;
  float sa[32], sb[32], o[2][16], l[2][2];
  auto dch = [&](int n) { return dslot + 1024u * (n % 3 == 0 ? 1 : (n % 3 == 1 ? 0 : 2)); };
  wgmma_fence();
  wgmma_n64_ssz_ta0_tb0(sa, desc_lo(dq + 512), desc_lo(dch(0)));
  wgmma_n64_ss_ta0_tb0(sa, desc_lo(dq + 512 + 2), desc_lo(dch(0) + 2), 1);
  wgmma_commit();
#pragma unroll
  for (int h = 0; h < 2; h++) {
#pragma unroll
    for (int i = 0; i < 16; i++) o[h][i] = 0.f;
    l[h][0] = l[h][1] = 0.f;
  }
  const int dg = (lane >> 2) - 2 * (lane & 3);
  const uint32_t tri = (dg >= 0 ? 0xffffu : 0u) | (dg >= 1 ? 0xffff0000u : 0u);
  const int nmax = 2 * gb + 1;
  wgmma_wait<0>();
  reg_fence<32>(sa);
#define STON false
  auto publish = [&]() {
    if (HH && wwarp == 1 && lane == 0) {
      bulk_wait0();
      fence_proxy_async_all();
      red_relaxed_add(g_flags + F_KV + (gb * 16 + hp) * KSTR + 1, 1u);
    }
    __syncwarp();
  };
#define ATT_STEP(i, MODE)                                                                                            \
  attn_unit<MODE, true>(sa, sb, o[1], l[1], i <= nmax, dch(i) + 512, dq, dch(i + 1), tri, wwarp,                     \
                        i >= 1 ? bars + 8u * (B_HALO + i - 1) : 0u, i == 1 ? par0 : parA, 0u, zero, STON); if (i == 0 && PUBPOS == 0) publish();                \
  attn_unit<MODE, (i < 4)>(sb, sa, o[0], l[0], i + 1 <= nmax, dch(i + 1) + 512, dq + 512, dch(i + 1), tri, wwarp, 0u, \
                           0u, i < 3 && lane == 0 ? bars + 8u * (B_REL + i) : 0u, zero);
  ATT_STEP(0, 1)
  if (PUBPOS == 1) publish();
  ATT_STEP(1, 0)
  ATT_STEP(2, 0)
  ATT_STEP(3, 0)
  ATT_STEP(4, 2)
#undef ATT_STEP
  const uint32_t ra = OA_TILE + (((lane & 8) ? 7 - wwarp : wwarp) * 8 + (lane & 7)) * 128;
  bool bad = false;
#pragma unroll
  for (int h = 1; h >= 0; h--) {
    float inv[2];
#pragma unroll
    for (int r = 0; r < 2; r++) {
      float v = l[h][r];
      v += __shfl_xor_sync(0xffffffffu, v, 1);
      v += __shfl_xor_sync(0xffffffffu, v, 2);
      bad |= !(v <= 1.152921504606846976e18f && v >= 8.673617379884035e-19f);
      inv[r] = rcp_fast(v);
    }
    if (h == 0) wgmma_wait<0>();
    reg_fence<16>(o[h]);
    store_o(o[h], inv, ra + h * 8192, HH, lane);
  }
  if (HH == 0) GTL(45);
  if (__any_sync(0xffffffffu, bad)) attn_a_slow(g_kvA[L >> 1][0][0][0], L, gb, hp, HH, wwarp, lane);
}

constexpr uint32_t KB_ROW0 = SBASE + OFF_SLOT + 2048, VB_ROW0 = SBASE + OFF_SLOT + 24576 + 2048;

__device__ __forceinline__ void attnB_soft(const float (&s)[40], int wwarp, int D, bool edge, bool odd,
                                           uint32_t (&p)[5][4], float (&sum)[2]) {
  float z[2][3];
#define GATHER_(W)                                                                                  \
  _Pragma("unroll") for (int r = 0; r < 2; r++) _Pragma("unroll") for (int t = 0; t < 3; t++)       \
      z[r][t] = odd ? s[4 * (2 * W + r + t) + 2 * r + 1] : s[4 * (2 * W + r + t) + 2 * r];
  if (wwarp < 2) {
    if (wwarp == 0) { GATHER_(0) } else { GATHER_(1) }
  } else {
    if (wwarp == 2) { GATHER_(2) } else { GATHER_(3) }
  }
#undef GATHER_
  float y[2];
  y[0] = D >= 2 ? z[0][0] : z[0][2];
  y[1] = D >= 2 ? z[1][0] : z[1][2];
  if (edge) {
    z[0][1] = -INFINITY;
    if (D >= 2) y[0] = y[1] = -INFINITY;
  }
  float m0 = fmaxf(z[0][1], y[0]), m1 = fmaxf(z[1][1], y[1]);
  m0 = fmaxf(m0, __shfl_xor_sync(0xffffffffu, m0, 1));
  m1 = fmaxf(m1, __shfl_xor_sync(0xffffffffu, m1, 1));
  m0 = fmaxf(m0, __shfl_xor_sync(0xffffffffu, m0, 2));
  m1 = fmaxf(m1, __shfl_xor_sync(0xffffffffu, m1, 2));
  const float e00 = ex2_approx(z[0][1] - m0), e01 = ex2_approx(y[0] - m0);
  const float e10 = ex2_approx(z[1][1] - m1), e11 = ex2_approx(y[1] - m1);
  sum[0] = e00 + e01;
  sum[1] = e10 + e11;
  const int sh = odd ? 16 : 0;
  const uint32_t a0 = pack_bf16x2(e00, 0.f) << sh, a1 = pack_bf16x2(e10, 0.f) << sh;
  const uint32_t b0 = pack_bf16x2(e01, 0.f) << sh, b1 = pack_bf16x2(e11, 0.f) << sh;
  const int kb = wwarp + (D >= 2 ? 0 : 1);
#pragma unroll
  for (int k = 0; k < 5; k++) {
    p[k][0] = k == kb ? b0 : 0u;
    p[k][1] = k == wwarp + 1 ? a1 : 0u;
    p[k][2] = k == wwarp ? a0 : 0u;
    p[k][3] = k == kb ? b1 : 0u;
#pragma unroll
    for (int q = 0; q < 4; q++) asm volatile("" : "+r"(p[k][q]));
  }
}

__device__ __forceinline__ void attnB_s(float (&s)[40], int HH, int h) {
  constexpr uint32_t sq = SBASE + OFF_SLOT + 3 * 16384;
#pragma unroll
  for (int ks = 0; ks < 2; ks++)
    wgmma_n80_ss_ta0_tb0(s, make_desc(sq + h * 8192 + HH * 64 + ks * 32, 16),
                         make_desc(KB_ROW0 + h * 8192 - 2048 + HH * 64 + ks * 32, 16), ks);
}
__device__ __forceinline__ void attnB_pv(float (&o)[16], const uint32_t (&p)[5][4], int HH, int h) {
#pragma unroll
  for (int k = 0; k < 5; k++)
    wgmma_n32_rs_tb1(o, p[k], make_desc(VB_ROW0 + h * 8192 - 2048 + k * 2048 + HH * 64, 16), k);
}

__device__ __forceinline__ void attention_b(int HH, int gb, uint32_t par0, int wwarp, int lane) {
  constexpr uint32_t bars = SBASE + OFF_BAR, sq = SBASE + OFF_SLOT + 3 * 16384;
  float s[40];
  reg_define<40>(s);
  wgmma_fence();
  attnB_s(s, HH, 1);
  wgmma_commit();
  const int g = lane >> 2;
  const bool odd = g & 1;
  const int D = 2 * (lane & 3) + (g & 1) - g;
  const uint32_t ra = sq + (wwarp * 16 + ((lane >> 3) & 1) * 8 + (lane & 7)) * 128;
  wgmma_wait<0>();
  reg_fence<40>(s);
#pragma unroll 1
  for (int h = 1; h >= 0; h--) {
    float o[16], inv[2];
    uint32_t p[5][4];
    reg_define<16>(o);
    attnB_soft(s, wwarp, D, h == 0 && gb == 0 && wwarp == 0, odd, p, inv);
    if (h == 1) {
      mbar_wait(bars + 8u * B_HALO, par0);
      wgmma_fence();
      attnB_s(s, HH, 0);
    }
    wgmma_fence();
    attnB_pv(o, p, HH, h);
    wgmma_commit();
#pragma unroll
    for (int r = 0; r < 2; r++) {
      inv[r] += __shfl_xor_sync(0xffffffffu, inv[r], 1);
      inv[r] += __shfl_xor_sync(0xffffffffu, inv[r], 2);
      inv[r] = rcp_fast(inv[r]);
    }
    wgmma_wait<0>();
    reg_fence<40>(s);
    reg_fence<16>(o);
    store_o(o, inv, ra + h * 8192, HH, lane);
  }
}

#define KTQM 0
#define TRICKLE 300
#define CSI 1
#define PCA 1
#define PCB 3
#define PXB 4
#define EPW1 4
#define EPW0 12
#define PRENS 200
#define LOCE 1
#define QTURN 2
struct Params {
  CUtensorMap xq[2], xr[3], o, wqkv[2], wo[2];
  const __nv_bfloat16* in_x;
  const __nv_bfloat16* wqkv_p[2];
  const __nv_bfloat16* wo_p[2];
  __nv_bfloat16* out;
  uint32_t zero;
};

__device__ __forceinline__ void colsum_part(const CUtensorMap* wmap, int ty, int qr, int hp) {
  constexpr uint32_t bars = SBASE + OFF_BAR, slots = SBASE + OFF_SLOT;
  PHASE_IDS
  const unsigned ep1 = (*(volatile unsigned*)(g_flags + F_DONE)) / NCTA + 1u;
  if (wwarp == 0 && elect_one()) {
    mbar_expect_tx(bars + 8u * B_CS, 6 * UNIT);
#pragma unroll 1
    for (int j = 0; j < 2; j++) {
      if (ty == 0) mbar_pace(bars + 8u * (B_EMPTY + PCA + PCB * j), 0);
      else __nanosleep(1000);
      tma_load_3d(slots + j * 3 * UNIT, wmap, bars + 8u * B_CS, hp * 64, qr * 128 + j * 64, 0);
    }
  }
  mbar_wait(bars + 8u * B_CS, ty);
  STAMP(KSQ == 0 && ty == 0, 49);
  const uint32_t src = slots + (tid >> 3) * 128 + (((tid & 7) ^ ((tid >> 3) & 7)) << 4);
#pragma unroll 1
  for (int p = 0; p < 3; p++) {
    float s[8];
#pragma unroll
    for (int e = 0; e < 8; e++) s[e] = 0.f;
#pragma unroll
    for (int j = 0; j < 8; j++) {
      const uint4 v = lds128(src + p * UNIT + (j >> 2) * 3 * UNIT + (j & 3) * 2048);
      const uint32_t x[4] = {v.x, v.y, v.z, v.w};
#pragma unroll
      for (int e = 0; e < 4; e++) {
        s[2 * e] += bf_lo(x[e]);
        s[2 * e + 1] += bf_hi(x[e]);
      }
    }
#pragma unroll
    for (int st = 0; st < 2; st++) {
      const bool up = (lane >> (st + 3)) & 1;
#pragma unroll
      for (int e = 0; e < (4 >> st); e++) {
        const float keep = up ? s[e + (4 >> st)] : s[e], give = up ? s[e] : s[e + (4 >> st)];
        s[e] = keep + __shfl_xor_sync(0xffffffffu, give, 8 << st);
      }
    }
    const uint32_t dst = slots + 6 * UNIT + ((wwarp * 3 + p) * 64 + (lane & 7) * 8 + ((lane >> 3) & 1) * 4 + (lane >> 4) * 2) * 4;
    sts32(dst, __float_as_uint(s[0]));
    sts32(dst + 4, __float_as_uint(s[1]));
  }
  named_bar_sync(6, 128);
  if (tid < 64) {
    float r[3] = {0.f, 0.f, 0.f};
#pragma unroll
    for (int e = 0; e < 12; e++) r[e % 3] += __uint_as_float(lds32(slots + 6 * UNIT + (e * 64 + tid) * 4));
    st_rec(&g_cs[ty][hp][qr][tid], r[0], r[1], r[2], ep1);
    STAMP(KSQ == 0 && ty == 0, 50);
  }
  named_bar_sync(6, 128);
}

__device__ __forceinline__ void cs_put(int blk, int ty, int col, float v) {
  const uint32_t hi = pack_bf16x2(v, 0.f), lo = pack_bf16x2(v - bf_lo(hi), 0.f);
  const uint32_t a = SBASE + OFF_CS + blk * 512 + ty * 256 + col * 2;
  asm volatile("st.shared.b16 [%0], %1;" ::"r"(sw(a ^ (((a >> 7) & 7) << 4))), "h"((unsigned short)hi) : "memory");
  asm volatile("st.shared.b16 [%0], %1;" ::"r"(sw((a + 128) ^ ((((a >> 7) + 1) & 7) << 4))), "h"((unsigned short)lo) : "memory");
}

__device__ __forceinline__ uint32_t ln_params(float s1, float s2) {
  const float mean = s1 * (1.0f / DM);
  const float var = fmaxf(fmaf(-mean, mean, s2 * (1.0f / DM)), 0.f);
  float sd;
  asm("sqrt.approx.f32 %0, %1;" : "=f"(sd) : "f"(bf16_round(bf16_round(var) + 1e-5f)));
  return pack_bf16x2(mean, sd);
}

#define SPLITS 0x086755488ull
__device__ __forceinline__ int q_split(int inst) { return (int)((SPLITS >> (4 * inst)) & 15ull); }
__device__ __forceinline__ int q_first(int inst) { return inst == 0 ? 0 : 32 * inst - 16; }
__device__ __forceinline__ int w_first(int inst) { return 32 * inst + 16 + 2 * q_split(inst + 1); }
#define PREMASK 0x3Cu
#define WBUF 0x0400103000201000ull
static_assert((PREMASK & 0xC0u) == 0, "");
__device__ __forceinline__ bool w_pre(int inst) { return (PREMASK >> inst) & 1u; }
struct WPlan {
  int v[6][21];
  int own[28], len;
};
__host__ __device__ constexpr WPlan w_plan(int mode) {
  WPlan p{};
  for (int u = 0; u < 28; u++) p.own[u] = u < 20 ? u / 5 - 4 : -16;
  if (mode == 2) {
    const WPlan q = w_plan(0);
    for (int u = 0; u < 20; u++) p.own[u] = q.own[(u + q.len) % 20] - 16;
  }
  int pos = 0, mx = -16;
  for (int kt = 0; kt < 21; kt++) {
    const int code = mode == 1 && kt < 16 ? (int)(WBUF >> (4 * kt)) & 15 : 0, st = kt > 16 ? kt - 1 : kt;
    const int na = kt == 16 ? 0 : (kt < 16 ? 1 : 2), nb = kt < 17 ? 2 : 3;
    const bool hole = code == 0 || (code & 8), swap = kt < 16 && hole && pos % 10 == 8;
    const int ua = (pos + (swap ? 2 : 0)) % 20, ub = code ? NUNITS - 2 + 2 * (code & 7) : (pos + (swap ? 0 : na)) % 20;
    int ra = st - 8, rb = kt == 16 ? -16 : st - 8;
    for (int i = 0; i < na; i++) ra = p.own[ua + i] > ra ? p.own[ua + i] : ra;
    for (int i = 0; i < nb; i++) rb = p.own[ub + i] > rb ? p.own[ub + i] : rb;
    p.v[0][kt] = ua;
    p.v[1][kt] = ub;
    p.v[2][kt] = st - ra;
    p.v[3][kt] = st - rb;
    p.v[4][kt] = rb > mx;
    p.v[5][kt] = p.own[ub] == -16;
    mx = rb > mx ? rb : mx;
    if (kt < 17) {
      for (int i = 0; i < na; i++) p.own[ua + i] = kt;
      for (int i = 0; i < nb; i++) p.own[ub + i] = kt < 16 ? kt : 15;
    }
    pos += na + (hole ? nb : 0);
    if (kt == 16) p.len = pos;
  }
  return p;
}
__host__ __device__ constexpr uint64_t w_tab(int f, int mode, int k0, int dk, int n, int bits) {
  const WPlan p = w_plan(mode);
  uint64_t r = 0;
  for (int j = 0; j < n; j++) r |= (uint64_t)p.v[f][k0 + j * dk] << (bits * j);
  return r;
}
template <int F, int MODE>
__device__ __forceinline__ int w_get(int kt) {
  constexpr uint64_t t0 = w_tab(F, MODE, 0, 1, 8, 8), t1 = w_tab(F, MODE, 8, 1, 8, 8), t2 = w_tab(F, MODE, 16, 1, 1, 8);
  return (int)((kt < 8 ? t0 : (kt < 16 ? t1 : t2)) >> (8 * (kt & 7))) & 255;
}
__host__ __device__ constexpr uint32_t q_backs(bool act, int rank, bool pre) {
  return act ? 0x44444400u | (uint32_t)w_tab(2, pre, 17 + rank, 2, 2, 4) : 0x44440000u | (uint32_t)w_tab(3, pre, 17, 1, 4, 4);
}
__host__ __device__ constexpr uint32_t w_early() {
  const WPlan p = w_plan(1);
  uint32_t r = 0;
  for (int kt = 0; kt < 16; kt++)
    if (p.v[5][kt]) r |= (uint32_t)kt << (2 * (p.v[1][kt] - NUNITS));
  return r;
}
static_assert(w_plan(1).len % 10 == 0 && w_tab(2, 0, 0, 2, 8, 4) == 0x77776654u && w_tab(2, 2, 1, 2, 8, 4) == 0x77777666u &&
              q_backs(false, 0, false) == 0x44444445u && q_backs(true, 0, false) == 0x44444456u, "");
constexpr bool PRE_FLIP = w_plan(1).len % 20 != 0;
__device__ __forceinline__ int w_flips(int n) { return PRE_FLIP ? n : __popc(~PREMASK & ((1u << n) - 1u)); }
#define GRID 0
#define GD 128
#define GK0 0
#define GALL 0
__device__ __forceinline__ void grid_wait(int kt) {
#pragma unroll 1
  for (int it = 0; it < 256; it++) {
    uint32_t c;
    asm volatile("mov.u32 %0, %%clock;" : "=r"(c));
    if (((c - 256u * kt) & (GRID - 1u)) < GD) break;
  }
}
__device__ __forceinline__ uint32_t unit_off(int u, uint32_t dl) { return u * UNIT + (u < 10 ? dl : (u < 20 ? 0u - dl : 0u)); }

__global__ void __cluster_dims__(2, 1, 1) __launch_bounds__(512, 1) fused_kernel(const __grid_constant__ Params P) {
  constexpr uint32_t base = SBASE, bars = base + OFF_BAR, slots = base + OFF_SLOT;
  const int warp = __shfl_sync(0xffffffffu, threadIdx.x >> 5, 0), lane = threadIdx.x & 31;
  const int b = blockIdx.x, rank = b & 1;
  if (smem_u32(smem_raw) != base + (rank << 24)) __trap();
  const int tc = (b >> 1) - 4;
  const int grp = tc < 0 ? 0 : (tc < 32 ? tc & 7 : (tc - 32) % 7 + 1);
  const int qr = tc < 0 ? tc + 8 : (tc < 32 ? tc >> 3 : 4 + (tc - 32) / 7);
  const int hp = 2 * grp + rank;
  const int rt = (grp & 1) * 8 + qr;
  const int ct = (grp & 6) + rank;

  if (warp == 12) {
    if (elect_one()) {
#pragma unroll
      for (int s = 0; s < 8; s++) {
        mbar_init(bars + 8u * (B_FULL + s), 1);
        mbar_init(bars + 8u * (B_EMPTY + s), LOCE ? 2 : 4);
        mbar_init(bars + 8u * (B_LOC + s), 2);
      }
      mbar_init(bars + 8u * B_GO, 1);
      fence_barrier_init();
    }
    __syncwarp();
    named_bar_arrive(0, 512);
  }
  asm volatile("barrier.cluster.arrive.relaxed.aligned;" ::: "memory");
  if (threadIdx.x == 0) {
    mbar_init(bars + 8u * B_PREP, 1);
    mbar_init(bars + 8u * (B_PREP + 1), 1);
    for (int s = 0; s < 4; s++) mbar_init(bars + 8u * (B_HALO + s), 1);
    for (int s = 0; s < 3; s++) mbar_init(bars + 8u * (B_REL + s), 8);
    mbar_init(bars + 8u * B_AFREE, 2);
    mbar_init(bars + 8u * B_TURN, 4);
    mbar_init(bars + 8u * (B_TURN + 1), 4);
    mbar_init(bars + 8u * B_CS, 1);
    for (int s = 0; s < 4; s++) mbar_init(bars + 8u * (B_PRE + s), 1);
    mbar_init(bars + 8u * B_RESF, 1);
    mbar_init(bars + 8u * B_RESE, 4);
    mbar_init(bars + 8u * B_CSD, 4);
    mbar_init(bars + 8u * B_XRDY, 1);
    mbar_init(bars + 8u * (B_XRDY + 1), 1);
    fence_barrier_init();
  }
  if (warp != 12) named_bar_sync(0, 512);
  if (warp != 12 && warp >= 4) asm volatile("barrier.cluster.wait.aligned;" ::: "memory");

  if (warp >= 12) {
    setmaxnreg_dec<32>();
    if (warp == 12) {
#pragma unroll 1
      for (int s = 0; s < 16; s++) {
        const uint32_t fb = bars + 8u * (B_FULL + (s & 7)), sa = base + (s & 3) * 5 * UNIT;
        if (s == 4) asm volatile("barrier.cluster.wait.aligned;" ::: "memory");
        if (s >= 4) mbar_wait(bars + 8u * (B_EMPTY + ((s - 4) & 7)), ((s - 4) >> 3) & 1);
        if (elect_one()) {
          mbar_expect_tx(fb, 5 * UNIT);
          if (s < 4) tma_load_3d(sa, &P.xq[0], fb, 0, qr * 128, s);
          else if ((s & 1) == rank) tma_load_3d_mc(sa, &P.xq[0], fb, 0, qr * 128, s);
          tma_load_3d(sa + 2 * UNIT, &P.wqkv[0], fb, hp * 64, s * 64, 0);
        }
      }
      if (elect_one()) mbar_arrive(bars + 8u * B_GO);
      uint32_t n = 16, dl = 0;
      int aw = 0;
      uint32_t back = 0x44444444u;
#pragma unroll 1
      for (int sg = 4; sg < 34; sg++) {
        const int part = sg & 3, si = (sg >> 2) - (part & 1), L = si >> 1, ch = si & 1;
        const int k0 = part == 2 ? 2 * q_split(si) : 0, k1 = part == 0 ? 2 * q_split(si) : 16;
        if (part == 3) continue;
        if (part != 1) {
#pragma unroll 1
          for (int k2 = k0; k2 < k1; k2 += 2, aw--, dl ^= 10u * UNIT) {
#pragma unroll
            for (int ks = 0; ks < 2; ks++, n++, back = (back >> 4) | 0x40000000u) {
              const uint32_t nw = n - (back & 15u), fb = bars + 8u * (B_FULL + (n & 7u));
              mbar_wait(bars + 8u * ((LOCE ? B_LOC : B_EMPTY) + (nw & 7u)), (nw >> 3) & 1u);
              if (ks == 1 && aw == 1) mbar_wait(bars + 8u * B_RESE, (part == 2) ^ ch);
              if (elect_one()) {
                mbar_expect_tx(fb, 5 * UNIT);
                tma_load_3d(base + (ks * 5 + 2) * UNIT + dl, &P.wqkv[L & 1], fb, hp * 64, (k2 + ks) * 64, 0);
              }
            }
          }
        } else {
          const bool pre = w_pre(si);
          auto wjob = [&](auto mode_) {
            constexpr int mode = decltype(mode_)::value;
#pragma unroll
            for (int kt = 0; kt < 17; kt++) {
              const uint32_t nw = n + kt - (mode == 0 && aw == 2 ? w_get<3, 2>(kt) : w_get<3, mode>(kt));
              const uint32_t fb = bars + 8u * (kt == 16 ? B_RESF : B_FULL + ((n + kt) & 7u));
              if (w_get<4, mode>(kt) || (mode == 0 && w_get<4, 2>(kt)))
                mbar_wait(bars + 8u * ((LOCE ? B_LOC : B_EMPTY) + (nw & 7u)), (nw >> 3) & 1u);
              if (mode == 0 && kt == 6 && aw == 2) mbar_wait(bars + 8u * B_RESE, ch ^ 1);
              if (GRID && kt < 16 && kt >= GK0 && !w_get<5, mode>(kt) && (mode == 1 || GALL)) grid_wait(kt);
              if (elect_one()) {
                mbar_expect_tx(fb, kt == 16 ? 2 * UNIT : (w_get<5, mode>(kt) ? UNIT : 3 * UNIT));
                if (kt == 16)
                  tma_load_3d(base + unit_off(w_get<1, mode>(16), dl), &P.xr[L == 0 ? 0 : 1], fb, 0, ch * 1024 + rt * 64, ct * 2);
                else if (!w_get<5, mode>(kt))
                  tma_load_3d(base + unit_off(w_get<1, mode>(kt), dl), &P.wo[L & 1], fb, 0, kt * 64, ct * 2);
              }
            }
          };
          if (pre) wjob(std::integral_constant<int, 1>());
          else wjob(std::integral_constant<int, 0>());
          n += 16;
          if (!pre || PRE_FLIP) dl ^= 10u * UNIT;
          constexpr uint32_t qb0 = q_backs(false, 0, false), qb1 = q_backs(false, 0, true);
          back = pre ? qb1 : qb0;
          aw = 2;
        }
      }
    } else if (warp == 13) {
      uint32_t n = 16 + rank, dl = 0;
      uint32_t back = 0x44444444u;
      mbar_wait(bars + 8u * B_GO, 0);
      const unsigned ep1 = __shfl_sync(0xffffffffu, (*(volatile unsigned*)(g_flags + F_DONE)) / NCTA + 1u, 0);
#pragma unroll 1
      for (int sg = 4; sg < 34; sg++) {
        const int part = sg & 3, si = (sg >> 2) - (part & 1), L = si >> 1, ch = si & 1;
        const int k0 = part == 2 ? 2 * q_split(si) : 0, k1 = part == 0 ? 2 * q_split(si) : 16;
        if (part == 3 || k0 == k1) continue;
        const bool wj = part == 1;
        uint32_t seen = 0u;
        if (!wj && (L == 0 || __any_sync(0xffffffffu, mbar_test(bars + 8u * (B_XRDY + ch), (L & 1) ^ 1)))) {
          seen = 0xFFFFu;
          fence_proxy_async_all();
        }
        const CUtensorMap* map = wj ? &P.o : &P.xq[L == 0 ? 0 : 1];
        const unsigned* fl = g_flags + (wj ? F_O + (ch * 16 + rt) * OSTR : F_X + (ch * 8 + qr) * XSTR);
        const unsigned target = wj ? 4u * ep1 - 3u + L : 6u * ep1 - 6u + 2u * L;
        const int row = ch * 1024 + (wj ? rt * 64 : qr * 128);
        const bool pre = w_pre(si);
        uint64_t units = rank ? 0x0f050f050f050f05ull : 0x0a000a000a000a00ull;
        if (wj) {
          constexpr uint32_t b00 = (uint32_t)w_tab(2, 0, 0, 2, 8, 4), b01 = (uint32_t)w_tab(2, 0, 1, 2, 8, 4), b10 = (uint32_t)w_tab(2, 1, 0, 2, 8, 4),
                             b11 = (uint32_t)w_tab(2, 1, 1, 2, 8, 4), b20 = (uint32_t)w_tab(2, 2, 0, 2, 8, 4), b21 = (uint32_t)w_tab(2, 2, 1, 2, 8, 4);
          constexpr uint64_t u00 = w_tab(0, 0, 0, 2, 8, 8), u01 = w_tab(0, 0, 1, 2, 8, 8), u10 = w_tab(0, 1, 0, 2, 8, 8), u11 = w_tab(0, 1, 1, 2, 8, 8);
          back = pre ? (rank ? b11 : b10) : (si == 7 ? (rank ? b21 : b20) : (rank ? b01 : b00));
          units = pre ? (rank ? u11 : u10) : (rank ? u01 : u00);
        }
#pragma unroll 1
        for (int kt = k0 + rank; kt < k1; kt += 2, n += 2, back = (back >> 4) | 0x40000000u, units >>= 8) {
          wait_mask<false>(fl, 16, target, 1u << (wj ? kt : kt >> 1), seen, lane);
          const uint32_t nw = n - (back & 15u), pos = ((uint32_t)units & 31u) * UNIT + dl;
          mbar_wait(bars + 8u * (B_EMPTY + (nw & 7u)), (nw >> 3) & 1u);
          if (elect_one())
            tma_load_3d_mc(base + (pos >= 20 * UNIT ? pos - 20 * UNIT : pos), map, bars + 8u * (B_FULL + (n & 7u)), 0, row, kt);
        }
        if (wj ? !pre || PRE_FLIP : ((k1 - k0) & 2)) dl ^= 10u * UNIT;
        constexpr uint32_t q00 = q_backs(true, 0, false), q01 = q_backs(true, 1, false), q10 = q_backs(true, 0, true), q11 = q_backs(true, 1, true);
        if (wj) back = pre ? (rank ? q11 : q10) : (rank ? q01 : q00);
      }
    } else if (warp == 14) {
      const unsigned ep1 = (*(volatile unsigned*)(g_flags + F_DONE)) / NCTA + 1u;
#pragma unroll 1
      for (int inst = 0; inst < 8; inst++) {
        const int L = inst >> 1, ch = inst & 1, gb = ch * 8 + qr;
        const unsigned* fp = g_flags + F_KV + (max(gb - 1 - ((lane >> 1) & 1), 0) * 16 + hp) * KSTR + (lane & 1);
        const unsigned target = (lane & 1) ? 2u * ep1 - 1u + (L >> 1) : 4u * ep1 - 3u + L;
        uint32_t seen = gb == 0 ? 15u : (gb == 1 ? 12u : 0u);
        named_bar_sync(3, 192);
        STA(34);
        __nanosleep(HDELAY);
        if ((L & 1) == 0) {
#pragma unroll 1
          for (int i = 0; i < 4; i++) {
            wait_lanes(fp, target, 1u << i, seen);
            STA(36 + i);
            if (i > 0) mbar_wait_lazy<RELNS>(bars + 8u * (B_REL + i - 1), ch);
            if (elect_one()) {
              mbar_expect_tx(bars + 8u * (B_HALO + i), 16384);
              bulk_load(slots + (i == 3 ? 2 : 2 - i) * 16384, gb > (i >> 1) ? g_kvA[L >> 1][gb - 1 - (i >> 1)][hp][(i & 1) ^ 1] : g_zero,
                        16384, bars + 8u * (B_HALO + i));
            }
          }
        } else {
          wait_lanes(fp, target, 1u, seen);
        }
        if (elect_one()) {
          if (L & 1) {
            const uint8_t* s1 = gb >= 1 ? g_kvB[L >> 1][gb - 1][hp] : g_zero;
            mbar_expect_tx(bars + 8u * B_HALO, 4096);
            bulk_load(KB_ROW0 - 2048, s1, 2048, bars + 8u * B_HALO);
            bulk_load(VB_ROW0 - 2048, s1 + 2048, 2048, bars + 8u * B_HALO);
          }
          if (w_pre(inst)) {
            mbar_wait(bars + 8u * B_AFREE, (inst & 1) ^ 1);
            if (inst == CSI) mbar_wait(bars + 8u * B_CSD, 0);
#pragma unroll 1
            for (int j = 0; j < 4; j++) {
              constexpr uint32_t early = w_early();
              mbar_expect_tx(bars + 8u * (B_PRE + j), 2 * UNIT);
              tma_load_3d(slots + j * 2 * UNIT, &P.wo[L & 1], bars + 8u * (B_PRE + j), 0, ((early >> (4 * j)) & 15) * 64, ct * 2);
              __nanosleep(PRENS);
            }
          }
        }
        __syncwarp();
      }
    } else {
      const unsigned ep1 = (*(volatile unsigned*)(g_flags + F_DONE)) / NCTA + 1u;
      mbar_wait(bars + 8u * B_GO, 0);
#pragma unroll 1
      for (int i = 0; i < 20; i++) {
        const char* src = i < 4 ? reinterpret_cast<const char*>(P.wo_p[0]) + (size_t)b * 16384 + i * 4096
                                : (i < 16 ? reinterpret_cast<const char*>(P.wqkv_p[1]) + (size_t)b * 49152 + (i - 4) * 4096
                                          : reinterpret_cast<const char*>(P.wo_p[1]) + (size_t)b * 16384 + (i - 16) * 4096);
        asm volatile("prefetch.global.L2 [%0];" ::"l"(src + lane * 128));
        __nanosleep(TRICKLE);
      }
#pragma unroll 1
      for (int inst = 2; inst < 8; inst++) {
        const int L = inst >> 1, ch = inst & 1, gb = ch * 8 + qr;
        uint32_t seen = 0;
        wait_mask<true>(g_flags + F_X + gb * XSTR, 8, 6u * ep1 - 6u + 2u * L, 0xFFu, seen, lane);
        if (lane == 0) mbar_arrive(bars + 8u * (B_XRDY + ch));
#pragma unroll 1
        for (int h = 0; h < 4; h++) {
          const float4* sp = &g_stats[L][0][gb * 128 + h * 32 + lane];
          const float4 s0 = sum_recs<4>(sp, S_LEN, ep1), s1 = sum_recs<4>(sp + 4 * S_LEN, S_LEN, ep1);
          sts32(base + OFF_RS + (ch * 128 + h * 32 + lane) * 4, ln_params(s0.x + s1.x, s0.y + s1.y));
        }
        if (inst == 2) {
          mbar_wait(bars + 8u * B_CSD, 0);
#pragma unroll 1
          for (int hf = 0; hf < 2; hf++) {
            const float4* cp = &g_cs[1][hp][0][hf * 32 + lane];
            const float4 s0 = sum_recs<4>(cp, 64, ep1), s1 = sum_recs<4>(cp + 4 * 64, 64, ep1);
            cs_put(0, 1, hf * 32 + lane, s0.x + s1.x);
            cs_put(1, 1, hf * 32 + lane, s0.y + s1.y);
            cs_put(2, 1, hf * 32 + lane, s0.z + s1.z);
          }
          fence_proxy_async_smem();
        }
        __syncwarp();
        if (lane == 0) mbar_arrive(bars + 8u * (B_PREP + ch));
      }
    }
  } else {
    const bool asst = warp >= 8;
    uint32_t tpar = 0;
    const uint32_t ebar = LOCE && (warp & 2) ? bars + 8u * B_LOC + (rank << 24) : bars + 8u * B_EMPTY + ((warp & 1) << 24);
    GTL(0);
    if (asst) {
      colsum_part(&P.wqkv[0], 0, qr, hp);
      if ((threadIdx.x & 127) < 2) mbar_arrive(bars + 8u * B_AFREE);
    } else if (warp >= 4) {
      PHASE_IDS
      {
        const unsigned ep1 = (*(volatile unsigned*)(g_flags + F_DONE)) / NCTA + 1u;
        const int row = b * 16 + (tid >> 3);
        const uint4* src = reinterpret_cast<const uint4*>(P.in_x + (size_t)row * DM) + (tid & 7);
        float s1 = 0.f, s2 = 0.f;
#pragma unroll 1
        for (int k = 0; k < 4; k++) {
          mbar_pace(bars + 8u * (B_EMPTY + PXB * k / 2), 0);
          uint4 v[4];
#pragma unroll
          for (int j = 0; j < 4; j++) v[j] = __ldg(src + (k * 4 + j) * 8);
#pragma unroll
          for (int j = 0; j < 4; j++) {
            const uint32_t w[4] = {v[j].x, v[j].y, v[j].z, v[j].w};
#pragma unroll
            for (int e = 0; e < 4; e++) {
              const float x0 = bf_lo(w[e]), x1 = bf_hi(w[e]);
              s1 += x0 + x1;
              s2 = fmaf(x0, x0, fmaf(x1, x1, s2));
            }
          }
        }
#pragma unroll
        for (int o = 1; o < 8; o <<= 1) {
          s1 += __shfl_xor_sync(0xffffffffu, s1, o);
          s2 += __shfl_xor_sync(0xffffffffu, s2, o);
        }
        if ((tid & 7) == 0) st_rec(&g_stats[0][0][row], s1, s2, 0.f, ep1);
        if (tid == 0) sts32(base + OFF_EPOCH, ep1);
        STAMP(KSQ == 0, 51);
        float4 v[6];
#pragma unroll 1
        for (uint32_t it = 0; it < (1u << 17); ++it) {
          bool ok = true;
#pragma unroll
          for (int t = 0; t < 6; t++) {
            v[t] = ld_rec(t < 2 ? &g_stats[0][0][(t * 8 + qr) * 128 + tid] : &g_cs[0][hp][(tid & 1) * 4 + t - 2][tid >> 1]);
            ok &= __float_as_uint(v[t].w) == ep1;
          }
          STAMP(KSQ == 0 && it == 0, 18);
          if (ok) break;
          __nanosleep(100);
        }
        STAMP(KSQ == 0, 17);
        __syncwarp();
        STAMP(KSQ == 0, 19);
#pragma unroll
        for (int cc = 0; cc < 2; cc++) sts32(base + OFF_RS + (cc * 128 + tid) * 4, ln_params(v[cc].x, v[cc].y));
        const float cs[3] = {(v[2].x + v[3].x) + (v[4].x + v[5].x), (v[2].y + v[3].y) + (v[4].y + v[5].y),
                             (v[2].z + v[3].z) + (v[4].z + v[5].z)};
#pragma unroll
        for (int blk = 0; blk < 3; blk++) {
          const float t = cs[blk] + __shfl_xor_sync(0xffffffffu, cs[blk], 1);
          cs_put(blk, tid & 1, tid >> 1, (tid & 1) ? 0.f : t);
        }
        fence_proxy_async_smem();
        named_bar_sync(2, 128);
        if (tid < 2) mbar_arrive(bars + 8u * (B_PREP + tid));
        STAMP(KSQ == 0, 48);
      }
    }
#pragma unroll 1
    for (int inst = asst ? 0 : warp >> 2; inst < 8; inst += asst ? 1 : 2) {
      const int L = inst >> 1, ch = inst & 1, gb = ch * 8 + qr;
      if (asst) {
        setmaxnreg_dec<24>();
        if (warp == 8) {
          named_bar_sync(3, 192);
          STA(32);
          if (elect_one()) {
            if ((L & 1) == 0) {
              bulk_store(g_kvA[L >> 1][gb][hp][1], slots + 16384, 16384);
            } else {
              bulk_store(g_kvB[L >> 1][gb][hp], KB_ROW0 + 112 * 128, 2048);
              bulk_store(g_kvB[L >> 1][gb][hp] + 2048, VB_ROW0 + 112 * 128, 2048);
            }
            bulk_commit();
            bulk_wait0();
            fence_proxy_async_all();
            red_relaxed_add(g_flags + F_KV + (gb * 16 + hp) * KSTR, 1u);
            STA(33);
          }
          __syncwarp();
        } else if (warp == 9 && (L & 1) == 0) {
          named_bar_sync(7, 160);
          if ((fresh_tid() & 31) == 0) {
            bulk_store(g_kvA[L >> 1][gb][hp][0], slots, 16384);
            bulk_commit();
          }
          __syncwarp();
        }
        named_bar_sync(4, 256);
        setmaxnreg_inc<128>();
      } else {
      setmaxnreg_inc<224>();
      {
        float acc[2][96];
        const int ksp = q_split(inst);
        int n = q_first(inst);
        uint32_t dlt = inst > 0 && (w_flips(inst - 1) & 1) ? 10u * (UNIT >> 4) : 0u;
        if (inst == 1 || (inst > 1 && q_split(inst - 1) != 8)) {
          mbar_wait_lazy<100>(bars + 8u * (B_TURN + ch), tpar);
          tpar ^= 1u;
        }
        if (L == 3) GTL(37);
        mbar_wait(bars + 8u * (B_FULL + (n & 7)), (n >> 3) & 1);
        GTL(1 + L * 8);
        {
          const uint32_t da = (base >> 4) + 0x10000u + dlt;
          const uint64_t db = desc_lo(da - 0x10000u + ((UNIT >> 4) << 16) + 2 * (UNIT >> 4));
          wgmma_fence();
          wgmma_n192_ssz_ta0_tb1(acc[0], desc_lo(da), db);
          wgmma_commit();
          wgmma_n192_ssz_ta0_tb1(acc[1], desc_lo(da + (UNIT >> 4)), db);
          wgmma_commit();
          if (inst == 0) asm volatile("barrier.cluster.wait.aligned;" ::: "memory");
        }
#pragma unroll 1
        for (int k2 = 0; k2 < 7; k2++) {
          const bool brk = k2 + 1 == ksp;
#pragma unroll
          for (int ks = 0; ks < 2; ks++, n++) {
            STAMP(inst == KSQ, k2 * 2 + ks);
            const uint32_t da = ((base + ks * 5 * UNIT) >> 4) + 0x10000u + dlt;
            const uint32_t dbb = da - 0x10000u + ((UNIT >> 4) << 16) + 2 * (UNIT >> 4);
#pragma unroll
            for (int k16 = 0; k16 < 4; k16++) {
              if (ks == 0 && k16 == 0 && k2 == 0) continue;
              const uint64_t db = desc_lo(dbb + k16 * 128);
              wgmma_fence();
              wgmma_n192_ss_ta0_tb1(acc[0], desc_lo(da + k16 * 2), db, 1);
              wgmma_commit();
              wgmma_wait<1>();
              if (k16 == 0) warp_arrive_cl(ebar + 8u * ((n - 1) & 7), ks != 0 || k2 != ksp);
              wgmma_fence();
              wgmma_n192_ss_ta0_tb1(acc[1], desc_lo(da + (UNIT >> 4) + k16 * 2), db, 1);
              wgmma_commit();
              bool ok = true;
              if (k16 == 2) ok = mbar_test(bars + 8u * (B_FULL + ((n + 1) & 7)), ((n + 1) >> 3) & 1) || (ks == 1 && brk);
              if (k16 == QTURN && ks == 1) warp_arrive(bars + 8u * (B_TURN + (ch ^ 1)), brk);
              if (ks == 0 || k16 < 3) wgmma_wait<1>();
              if (k16 == 2 && !ok) mbar_wait(bars + 8u * (B_FULL + ((n + 1) & 7)), ((n + 1) >> 3) & 1);
            }
          }
          if (brk) {
            wgmma_wait<0>();
            warp_arrive_cl(ebar + 8u * ((n - 1) & 7));
            n += 16;
            mbar_wait_lazy<100>(bars + 8u * (B_TURN + ch), tpar);
            tpar ^= 1u;
            STAMP(inst == KSQ, 17);
            mbar_wait(bars + 8u * (B_FULL + (n & 7)), (n >> 3) & 1);
          }
          if (!brk || (!PRE_FLIP && w_pre(inst - 1))) dlt ^= 10u * (UNIT >> 4);
        }
        auto tail_group = [&](int u) {
          const uint32_t da = ((base + (u & 1) * 5 * UNIT) >> 4) + 0x10000u + dlt;
          const uint32_t dbb = da - 0x10000u + ((UNIT >> 4) << 16) + 2 * (UNIT >> 4);
          if (u < 3) wgmma_fence();
#pragma unroll
          for (int k16 = 0; k16 < 4; k16++)
            wgmma_n192_ss_ta0_tb1(acc[u < 2], desc_lo(da + (u < 2 ? UNIT >> 4 : 0) + k16 * 2), desc_lo(dbb + k16 * 128), 1);
          wgmma_commit();
        };
        STAMP(inst == KSQ, 14);
        tail_group(0);
        wgmma_wait<1>();
        STAMP(inst == KSQ && KSPN, 42);
        warp_arrive_cl(ebar + 8u * ((n - 1) & 7), ksp != 7);
        PHASE_IDS
        mbar_wait(bars + 8u * (B_PREP + ch), L & 1);
        STAMP(inst == KSQ && KSPN, 43);
        uint32_t rs[4];
#pragma unroll
        for (int i = 0; i < 4; i++)
          rs[i] = lds32(base + OFF_RS + (ch * 128 + (i >> 1) * 64 + wwarp * 16 + g + 8 * (i & 1)) * 4);
        auto fold = [&](int h) {
          uint32_t a[2];
#pragma unroll
          for (int r = 0; r < 2; r++) a[r] = c == (L & 1) ? __byte_perm(rs[2 * h + r], 0, 0x1010) ^ 0x80008000u : 0u;
          uint64_t d;
          asm("mov.b64 %0, {%1, %2};" : "=l"(d) : "r"(((base + OFF_CS) >> 4) + ((512 >> 4) << 16)), "r"(0x40000000u));
          wgmma_fence();
          wgmma_n192_rs_tb1(acc[h], a[0], a[1], d);
        };
        fold(1);
        wgmma_commit();
        mbar_wait(bars + 8u * (B_FULL + ((n + 1) & 7)), ((n + 1) >> 3) & 1);
        STAMP(inst == KSQ && KSPN, 44);
        tail_group(1);
        tail_group(2);
        STAMP(inst == KSQ && KSPN, 45);
        const bool ppre = ksp == 7 && w_pre(inst - 1);
        const uint32_t fbar = bars + 8u * (ppre ? (LOCE ? B_LOC : B_EMPTY) + ((n - 1) & 7) : (inst == CSI + 1 ? B_CSD : B_AFREE));
        const uint32_t fpar = ppre ? ((n - 1) >> 3) & 1 : (inst == CSI + 1 ? 0 : ch);
        const bool afree = mbar_test(fbar, fpar);
        float rinv[2][2];
#pragma unroll
        for (int i = 0; i < 4; i++) rinv[i >> 1][i & 1] = rcp_fast(bf_hi(rs[i]));
        const int mat = lane >> 3;
        const uint32_t soff = (wwarp * 16 + (mat & 1) * 8 + (lane & 7)) * 128;
        const uint32_t kdst = ((L & 1) ? KB_ROW0 : slots) + soff, vdst = ((L & 1) ? VB_ROW0 : slots + 8192) + soff;
        const uint32_t hs = (L & 1) ? 8192 : 16384;
        const int rg = 2 * wwarp + (mat & 1);
        const uint32_t qdst = slots + 3 * 16384 + ((L & 1) ? soff : ((rg < 4 ? 2 * rg : 15 - 2 * rg) * 8 + (lane & 7)) * 128);
        wgmma_wait<2>();
        STAMP(inst == KSQ && KSPN, 46);
        fold(0);
        tail_group(3);
        STAMP(inst == KSQ && KSPN, 47);
        warp_arrive(bars + 8u * (B_TURN + (ch ^ 1)));
        if (!afree) {
          wgmma_wait<1>();
          warp_arrive_cl(ebar + 8u * (n & 7));
          wgmma_wait<0>();
          warp_arrive_cl(ebar + 8u * ((n + 1) & 7));
          mbar_wait(fbar, fpar);
        }
        wgmma_wait<2>();
        reg_fence<96>(acc[1]);
        STAMP(inst == KSQ, 15);
#pragma unroll
        for (int t = 0; t < 24; t++) {
          const int h = t < 12 ? 1 : 0, p = (t % 12 / 4 + 1) % 3, jp = t & 3;
          if (t == EPW1) {
            wgmma_wait<1>();
            warp_arrive_cl(ebar + 8u * (n & 7), afree);
          }
          if (t == EPW0) {
            wgmma_wait<0>();
            reg_fence<96>(acc[0]);
            warp_arrive_cl(ebar + 8u * ((n + 1) & 7), afree);
            STAMP(inst == KSQ, 16);
            GTL(2 + L * 8);
          }
          if (t % 12 == 8) {
            rinv[h][0] *= SM_C;
            rinv[h][1] *= SM_C;
          }
          const uint32_t swz = ((2 * jp + (mat >> 1)) ^ (lane & 7)) << 4;
          const float* a = &acc[h][32 * p + 8 * jp];
          const uint32_t dst = p == 0 ? qdst + h * 8192 : (p == 1 ? kdst : vdst) + h * hs;
          stmatrix_x4(dst + swz, pack_bf16x2(a[0] * rinv[h][0], a[1] * rinv[h][0]), pack_bf16x2(a[2] * rinv[h][1], a[3] * rinv[h][1]),
                      pack_bf16x2(a[4] * rinv[h][0], a[5] * rinv[h][0]), pack_bf16x2(a[6] * rinv[h][1], a[7] * rinv[h][1]));
          if (t % 12 == 7) {
            fence_proxy_async_smem();
            if (t == 7) named_bar_arrive(3, 192);
            else if ((L & 1) == 0) named_bar_arrive(7, 160);
            if (t > EPW0) sched_fence(P.zero);
          }
        }
      }
      fence_proxy_async_smem();
      setmaxnreg_dec<128>();
      named_bar_sync(4, 256);
      }
      GTL(3 + L * 8);
      {
        PHASE_IDS
        if ((L & 1) == 0) attention_a(asst, L, gb, hp, inst & 1, ch, (tid_ >> 5) & 3, lane, P.zero);
        else attention_b(asst, gb, inst & 1, wwarp, lane);
        GTL(4 + L * 8);
        fence_proxy_async_smem();
      }
      if (asst) {
        named_bar_arrive(5, 256);
        if (inst == CSI) {
          mbar_wait(bars + 8u * B_AFREE, CSI ^ 1);
          colsum_part(&P.wqkv[1], 1, qr, hp);
          warp_arrive(bars + 8u * B_CSD);
        }
        continue;
      }
      {
        named_bar_sync(5, 256);
        const int wwarp = warp & 3;
        if (wwarp < 2 && elect_one()) {
          tma_store_3d(&P.o, ((L & 1) ? slots + 3 * 16384 : OA_TILE) + wwarp * 8192, 0, gb * 128 + wwarp * 64, hp);
          bulk_commit();
          bulk_wait0();
          mbar_arrive(bars + 8u * B_AFREE);
          fence_proxy_async_all();
          red_relaxed_add(g_flags + F_O + (gb * 2 + wwarp) * OSTR + hp, 1u);
        }
        __syncwarp();
      }
      GTL(5 + L * 8);

      {
        float acc[64];
        const int n0 = w_first(inst);
        const bool pre = w_pre(inst);
        const uint32_t dl = ((w_flips(inst) + q_split(inst + 1)) & 1) * 10u * UNIT;
        mbar_wait_lazy<100>(bars + 8u * (B_TURN + ch), tpar);
        tpar ^= 1u;
        mbar_wait(bars + 8u * (B_FULL + (n0 & 7)), (n0 >> 3) & 1);
        GTL(6 + L * 8);
#pragma unroll
        for (int kt = 0; kt < 16; kt++) {
          const int n = n0 + kt;
          STAMP(inst == KSW, 20 + kt);
          const uint32_t da = ((base + (pre ? unit_off(w_get<0, 1>(kt), dl) : unit_off(w_get<0, 0>(kt), dl))) >> 4) + 0x10000u;
          const uint32_t db = ((base + (pre ? unit_off(w_get<1, 1>(kt), dl) : unit_off(w_get<1, 0>(kt), dl))) >> 4) + ((UNIT >> 4) << 16);
          if (w_get<5, 1>(kt) && pre) mbar_wait(bars + 8u * (B_PRE + (w_get<1, 1>(kt) - NUNITS) / 2), __popc(PREMASK & ((1u << inst) - 1u)) & 1);
          if (kt == 15) warp_arrive(bars + 8u * (B_TURN + (ch ^ 1)), inst >= 6 || q_split(inst + 1) != 8);
          wgmma_fence();
          if (kt == 0) wgmma_n128_ssz_ta0_tb1(acc, desc_lo(da), desc_lo(db));
#pragma unroll
          for (int k16 = kt == 0 ? 1 : 0; k16 < 4; k16++) wgmma_n128_ss_ta0_tb1(acc, desc_lo(da + 2 * k16), desc_lo(db + 128 * k16), 1);
          wgmma_commit();
          const uint32_t nb = bars + 8u * (kt == 15 ? B_RESF : B_FULL + ((n + 1) & 7)), np = kt == 15 ? ch : ((n + 1) >> 3) & 1;
          const bool ok = mbar_test(nb, np);
          if (kt > 0) {
            wgmma_wait<1>();
            warp_arrive_cl(ebar + 8u * ((n - 1) & 7));
          }
          if (!ok) mbar_wait(nb, np);
        }
        PHASE_IDS
        const uint32_t xb = base + (pre ? unit_off(w_get<1, 1>(16), dl) : unit_off(w_get<1, 0>(16), dl));
        const int mat = lane >> 3;
        const uint32_t xrow = xb + (wwarp * 16 + (mat & 1) * 8 + (lane & 7)) * 128;
        uint32_t xv[8][4];
#pragma unroll
        for (int jp = 0; jp < 8; jp++)
          ldmatrix_x4(xv[jp], xrow + (jp >> 2) * UNIT + (((2 * (jp & 3) + (mat >> 1)) ^ (lane & 7)) << 4));
        wgmma_wait<0>();
        reg_fence<64>(acc);
        warp_arrive_cl(ebar + 8u * ((n0 + 15) & 7));
        STAMP(inst == KSW, 36);
        GTL(7 + L * 8);
#pragma unroll
        for (int jp = 0; jp < 8; jp++) {
#pragma unroll
          for (int q = 0; q < 4; q++) xv[jp][q] = add_bf16x2(xv[jp][q], pack_bf16x2(acc[8 * jp + 2 * q], acc[8 * jp + 2 * q + 1]));
          stmatrix_x4(xrow + (jp >> 2) * UNIT + (((2 * (jp & 3) + (mat >> 1)) ^ (lane & 7)) << 4), xv[jp][0], xv[jp][1],
                      xv[jp][2], xv[jp][3]);
        }
        fence_proxy_async_smem();
        named_bar_sync(1 + ch, 128);
        const int grow = ch * 1024 + rt * 64;
        if (wwarp == 0) {
          if (elect_one()) {
            tma_store_3d(&P.xr[L == 3 ? 2 : 1], xb, 0, grow, ct * 2);
            bulk_commit();
            bulk_wait_read0();
            mbar_arrive(bars + 8u * B_RESE);
            bulk_wait0();
            TGET(t35);
            fence_proxy_async_all();
            if (L < 3) red_relaxed_add(g_flags + F_X + (ch * 8 + (rt >> 1)) * XSTR + ct, 1u);
            if (L == 2) TPUT(ch, 35, t35);
          }
          __syncwarp();
        } else if (lane == 0) {
          mbar_arrive(bars + 8u * B_RESE);
        }
        if (L < 3) {
          const unsigned ep1 = lds32(base + OFF_EPOCH);
          float s1[2] = {0.f, 0.f}, s2[2] = {0.f, 0.f};
#pragma unroll
          for (int jp = 0; jp < 8; jp++)
#pragma unroll
            for (int q = 0; q < 4; q++) {
              const float x0 = bf_lo(xv[jp][q]), x1 = bf_hi(xv[jp][q]);
              s1[q & 1] += x0 + x1;
              s2[q & 1] = fmaf(x0, x0, fmaf(x1, x1, s2[q & 1]));
            }
#pragma unroll
          for (int r = 0; r < 2; r++) {
            s1[r] += __shfl_xor_sync(0xffffffffu, s1[r], 1);
            s2[r] += __shfl_xor_sync(0xffffffffu, s2[r], 1);
            s1[r] += __shfl_xor_sync(0xffffffffu, s1[r], 2);
            s2[r] += __shfl_xor_sync(0xffffffffu, s2[r], 2);
            if (c == 0) st_rec(&g_stats[L + 1][ct][grow + wwarp * 16 + g + 8 * r], s1[r], s2[r], 0.f, ep1);
          }
        }
        GTL(8 + L * 8);
      }
    }
    if (threadIdx.x == 128) atomicAdd(g_flags + F_DONE, 1u);
    if (!asst) asm volatile("barrier.cluster.arrive.relaxed.aligned;\nbarrier.cluster.wait.aligned;" ::: "memory");
  }
}

typedef CUresult (*PFN_tmEncode)(CUtensorMap*, CUtensorMapDataType, cuuint32_t, void*, const cuuint64_t*,
                                 const cuuint64_t*, const cuuint32_t*, const cuuint32_t*, CUtensorMapInterleave,
                                 CUtensorMapSwizzle, CUtensorMapL2promotion, CUtensorMapFloatOOBfill);

PFN_tmEncode get_encode_fn() {
  static PFN_tmEncode fn = nullptr;
  if (!fn) {
    cudaDriverEntryPointQueryResult qr;
    void* p = nullptr;
    cudaGetDriverEntryPoint("cuTensorMapEncodeTiled", &p, cudaEnableDefault, &qr);
    fn = (PFN_tmEncode)p;
  }
  return fn;
}

CUtensorMap make_map(const void* ptr, int rows, int cols, int inner, int box_rows, int box_blk) {
  CUtensorMap m;
  cuuint64_t gdim[3] = {(cuuint64_t)inner, (cuuint64_t)rows, (cuuint64_t)(cols / inner)};
  cuuint64_t gstr[2] = {(cuuint64_t)cols * 2, (cuuint64_t)inner * 2};
  cuuint32_t box[3] = {64, (cuuint32_t)box_rows, (cuuint32_t)box_blk};
  cuuint32_t estr[3] = {1, 1, 1};
  get_encode_fn()(&m, CU_TENSOR_MAP_DATA_TYPE_BFLOAT16, 3, const_cast<void*>(ptr), gdim, gstr, box, estr,
                  CU_TENSOR_MAP_INTERLEAVE_NONE, CU_TENSOR_MAP_SWIZZLE_128B, CU_TENSOR_MAP_L2_PROMOTION_L2_128B,
                  CU_TENSOR_MAP_FLOAT_OOB_FILL_NONE);
  return m;
}

}

extern "C" void kernel_launch(void* const* d_in, const int* in_sizes, int n_in, void* d_out, int out_size) {
  (void)in_sizes; (void)n_in; (void)out_size;
  void *p_o, *p_x;
  cudaGetSymbolAddress(&p_o, g_o);
  cudaGetSymbolAddress(&p_x, g_x);
  static bool attr_done = false;
  if (!attr_done) {
    cudaFuncSetAttribute(fused_kernel, cudaFuncAttributeMaxDynamicSharedMemorySize, SMEM_BYTES);
    attr_done = true;
  }
  Params P;
  P.in_x = (const __nv_bfloat16*)d_in[0];
  P.wqkv_p[0] = (const __nv_bfloat16*)d_in[1];
  P.wo_p[0] = (const __nv_bfloat16*)d_in[2];
  P.wqkv_p[1] = (const __nv_bfloat16*)d_in[4];
  P.wo_p[1] = (const __nv_bfloat16*)d_in[5];
  P.out = (__nv_bfloat16*)d_out;
  P.zero = 0;
  P.xq[0] = make_map(P.in_x, S_LEN, DM, 64, 128, 1);
  P.xq[1] = make_map(p_x, S_LEN, DM, 64, 128, 1);
  P.xr[0] = make_map(P.in_x, S_LEN, DM, 64, 64, 2);
  P.xr[1] = make_map(p_x, S_LEN, DM, 64, 64, 2);
  P.xr[2] = make_map(d_out, S_LEN, DM, 64, 64, 2);
  P.o = make_map(p_o, S_LEN, DM, 64, 64, 1);
  for (int t = 0; t < 2; t++) {
    P.wqkv[t] = make_map(P.wqkv_p[t], DM, NQKV, 1024, 64, 3);
    P.wo[t] = make_map(P.wo_p[t], DM, DM, 64, 64, 2);
  }
  fused_kernel<<<NCTA, 512, SMEM_BYTES>>>(P);
}
```

```cpp
#include <cuda_runtime.h>
#include <cuda_bf16.h>
#include <cuda.h>
#include <stdint.h>
#include <type_traits>

namespace {

constexpr int S_LEN = 2048;
constexpr int DM = 1024;
constexpr int NQKV = 3072;
constexpr int NCTA = 128;

__device__ __align__(1024) uint8_t g_kvA[2][16][16][2][16384];
__device__ __align__(1024) uint8_t g_kvB[2][16][16][4096];
__device__ __align__(1024) uint8_t g_zero[16384];
__device__ __align__(1024) __nv_bfloat16 g_o[S_LEN * DM];
__device__ __align__(1024) __nv_bfloat16 g_x[S_LEN * DM];
__device__ __align__(1024) float4 g_stats[4][8][S_LEN];
__device__ __align__(1024) float4 g_cs[2][16][8][64];
#define RSTR 1
constexpr int F_X = 0;
constexpr int XSTR = 32, OSTR = 32, KSTR = 32;
constexpr int F_O = F_X + 16 * XSTR;
constexpr int F_KV = F_O + 32 * OSTR;
constexpr int F_DONE = F_KV + 256 * KSTR;
constexpr int F_ROLE = F_DONE + 32;
__device__ __align__(1024) unsigned g_flags[F_ROLE + 64 * RSTR];

constexpr uint32_t SBASE = 1024;
constexpr int UNIT = 8192;
constexpr int NUNITS = 20;
constexpr int OFF_SLOT = NUNITS * UNIT;
constexpr int OFF_CS = OFF_SLOT + 4 * 16384;
constexpr int OFF_RS = OFF_CS + 1536;
constexpr int OFF_BAR = OFF_RS + 1024;
constexpr int OFF_EPOCH = OFF_BAR + 392, OFF_ROLE = OFF_BAR + 396;
constexpr int OFF_TS = OFF_BAR + 400;
constexpr int SMEM_BYTES = OFF_TS;
constexpr int B_FULL = 0, B_EMPTY = 8, B_PREP = 16, B_HALO = 18, B_REL = 22, B_AFREE = 25, B_TURN = 26, B_XRDY = 28,
              B_CS = 30, B_CSD = 31, B_GO = 32, B_RESF = 33, B_RESE = 34, B_PRE = 35, B_ROLE = 39, B_LOC = 40;

__device__ __forceinline__ uint32_t smem_u32(const void* p) { return (uint32_t)__cvta_generic_to_shared(p); }
extern __shared__ __align__(1024) uint8_t smem_raw[];
__device__ __forceinline__ uint32_t sw(uint32_t a) {
  uint32_t r;
  asm volatile("add.u32 %0, %1, %2;" : "=r"(r) : "r"(a), "r"(smem_u32(smem_raw) - SBASE));
  return r;
}

__device__ __forceinline__ void mbar_init(uint32_t bar, uint32_t cnt) {
  asm volatile("mbarrier.init.shared::cta.b64 [%0], %1;" ::"r"(sw(bar)), "r"(cnt));
}
__device__ __forceinline__ void mbar_expect_tx(uint32_t bar, uint32_t bytes) {
  asm volatile("mbarrier.arrive.expect_tx.shared::cta.b64 _, [%0], %1;" ::"r"(sw(bar)), "r"(bytes) : "memory");
}
__device__ __forceinline__ void mbar_arrive(uint32_t bar) {
  asm volatile("mbarrier.arrive.shared::cta.b64 _, [%0];" ::"r"(sw(bar)) : "memory");
}
__device__ __forceinline__ void warp_arrive(uint32_t bar, bool cond = true) {
  asm volatile("{\n.reg .pred p;\nelect.sync _|p, 0xffffffff;\nsetp.ne.and.b32 p, %1, 0, p;\n"
               "@p mbarrier.arrive.shared::cta.b64 _, [%0];\n}\n" ::"r"(sw(bar)), "r"((uint32_t)cond) : "memory");
}
__device__ __forceinline__ void warp_arrive_cl(uint32_t bar, bool cond = true) {
  asm volatile("{\n.reg .pred p;\nelect.sync _|p, 0xffffffff;\nsetp.ne.and.b32 p, %1, 0, p;\n"
               "@p mbarrier.arrive.shared::cluster.b64 _, [%0];\n}\n" ::"r"(bar), "r"((uint32_t)cond) : "memory");
}
__device__ __forceinline__ bool mbar_try_wait(uint32_t bar, uint32_t parity) {
  uint32_t ok;
  asm volatile(
      "{\n.reg .pred p;\nmbarrier.try_wait.parity.shared::cta.b64 p, [%1], %2;\nselp.b32 %0, 1, 0, p;\n}\n"
      : "=r"(ok)
      : "r"(sw(bar)), "r"(parity)
      : "memory");
  return ok != 0;
}
__device__ __forceinline__ bool mbar_test(uint32_t bar, uint32_t parity) {
  uint32_t ok;
  asm volatile(
      "{\n.reg .pred p;\nmbarrier.test_wait.parity.shared::cta.b64 p, [%1], %2;\nselp.b32 %0, 1, 0, p;\n}\n"
      : "=r"(ok)
      : "r"(sw(bar)), "r"(parity)
      : "memory");
  return ok != 0;
}
__device__ __forceinline__ void mbar_wait(uint32_t bar, uint32_t parity) {
#pragma unroll 1
  for (uint32_t it = 0; it < (1u << 18); ++it) {
    if (mbar_try_wait(bar, parity)) return;
  }
}
__device__ __forceinline__ void mbar_wait_raw(uint32_t bar, uint32_t parity) {
#pragma unroll 1
  for (uint32_t it = 0; it < (1u << 18); ++it) {
    uint32_t ok;
    asm volatile(
        "{\n.reg .pred p;\nmbarrier.try_wait.parity.shared::cta.b64 p, [%1], %2;\nselp.b32 %0, 1, 0, p;\n}\n"
        : "=r"(ok)
        : "r"(bar), "r"(parity)
        : "memory");
    if (ok) return;
  }
}
__device__ __forceinline__ void spin(uint32_t cyc) {
  uint32_t c0, c;
  asm volatile("mov.u32 %0, %%clock;" : "=r"(c0));
  do { asm volatile("mov.u32 %0, %%clock;" : "=r"(c)); } while (c - c0 < cyc);
}
__device__ __forceinline__ void mbar_pace(uint32_t bar, uint32_t parity) {
#pragma unroll 1
  for (uint32_t it = 0; it < 24; ++it) {
    if (mbar_try_wait(bar, parity)) return;
  }
}
template <int NS>
__device__ __forceinline__ void mbar_wait_lazy(uint32_t bar, uint32_t parity) {
#pragma unroll 1
  for (uint32_t it = 0; it < (1u << 18); ++it) {
    if (mbar_try_wait(bar, parity)) return;
    __nanosleep(NS);
  }
}
__device__ __forceinline__ bool elect_one() {
  uint32_t ok;
  asm volatile("{\n.reg .pred p;\nelect.sync _|p, 0xffffffff;\nselp.b32 %0, 1, 0, p;\n}\n" : "=r"(ok));
  return ok != 0;
}
__device__ __forceinline__ void fence_barrier_init() { asm volatile("fence.mbarrier_init.release.cluster;" ::: "memory"); }
__device__ __forceinline__ void fence_proxy_async_smem() { asm volatile("fence.proxy.async.shared::cta;" ::: "memory"); }
__device__ __forceinline__ void fence_proxy_async_all() { asm volatile("fence.proxy.async.global;" ::: "memory"); }

__device__ __forceinline__ void tma_load_3d(uint32_t dst, const CUtensorMap* map, uint32_t bar, int c0, int c1, int c2) {
  asm volatile(
      "cp.async.bulk.tensor.3d.shared::cluster.global.mbarrier::complete_tx::bytes [%0], [%1, {%3, %4, %5}], [%2];" ::"r"(sw(dst)),
      "l"(map), "r"(sw(bar)), "r"(c0), "r"(c1), "r"(c2)
      : "memory");
}
__device__ __forceinline__ void tma_load_3d_mc(uint32_t dst, const CUtensorMap* map, uint32_t bar, int c0, int c1, int c2) {
  asm volatile(
      "cp.async.bulk.tensor.3d.shared::cluster.global.mbarrier::complete_tx::bytes.multicast::cluster [%0], [%1, {%3, %4, %5}], [%2], %6;" ::"r"(sw(dst)),
      "l"(map), "r"(sw(bar)), "r"(c0), "r"(c1), "r"(c2), "h"((unsigned short)3)
      : "memory");
}
__device__ __forceinline__ void bulk_load(uint32_t dst, const void* src, uint32_t bytes, uint32_t bar) {
  asm volatile("cp.async.bulk.shared::cluster.global.mbarrier::complete_tx::bytes [%0], [%1], %2, [%3];" ::"r"(sw(dst)),
               "l"(src), "r"(bytes), "r"(sw(bar))
               : "memory");
}
__device__ __forceinline__ void bulk_store(void* dst, uint32_t src, uint32_t bytes) {
  asm volatile("cp.async.bulk.global.shared::cta.bulk_group [%0], [%1], %2;" ::"l"(dst), "r"(sw(src)), "r"(bytes) : "memory");
}
__device__ __forceinline__ void tma_store_3d(const CUtensorMap* map, uint32_t src, int c0, int c1, int c2) {
  asm volatile("cp.async.bulk.tensor.3d.global.shared::cta.bulk_group [%0, {%2, %3, %4}], [%1];" ::"l"(map), "r"(sw(src)),
               "r"(c0), "r"(c1), "r"(c2)
               : "memory");
}
__device__ __forceinline__ void bulk_commit() { asm volatile("cp.async.bulk.commit_group;" ::: "memory"); }
__device__ __forceinline__ void bulk_wait_read0() { asm volatile("cp.async.bulk.wait_group.read 0;" ::: "memory"); }
__device__ __forceinline__ void bulk_wait0() { asm volatile("cp.async.bulk.wait_group 0;" ::: "memory"); }
__device__ __forceinline__ void named_bar_sync(int id, int nthreads) {
  asm volatile("bar.sync %0, %1;" ::"r"(id), "r"(nthreads) : "memory");
}
__device__ __forceinline__ void named_bar_arrive(int id, int nthreads) {
  asm volatile("bar.arrive %0, %1;" ::"r"(id), "r"(nthreads) : "memory");
}

__device__ __forceinline__ void wgmma_fence() { asm volatile("wgmma.fence.sync.aligned;\n" ::: "memory"); }
__device__ __forceinline__ void wgmma_commit() { asm volatile("wgmma.commit_group.sync.aligned;\n" ::: "memory"); }
template <int N>
__device__ __forceinline__ void wgmma_wait() {
  asm volatile("wgmma.wait_group.sync.aligned %0;\n" ::"n"(N) : "memory");
}
template <int R>
__device__ __forceinline__ void setmaxnreg_inc() { asm volatile("setmaxnreg.inc.sync.aligned.u32 %0;\n" ::"n"(R)); }
template <int R>
__device__ __forceinline__ void setmaxnreg_dec() { asm volatile("setmaxnreg.dec.sync.aligned.u32 %0;\n" ::"n"(R)); }
template <int N>
__device__ __forceinline__ void reg_fence(float* r) {
#pragma unroll
  for (int i = 0; i < N; i++) asm volatile("" : "+f"(r[i])::"memory");
}

template <int N>
__device__ __forceinline__ void reg_define(float* r) {
#pragma unroll
  for (int i = 0; i < N; i++) r[i] = 0.f;
}

__device__ __forceinline__ uint64_t desc_lo(uint32_t lo) {
  uint64_t d;
  asm("mov.b64 %0, {%1, %2};" : "=l"(d) : "r"(lo), "r"(0x40000040u));
  return d;
}
__device__ __forceinline__ uint64_t make_desc(uint32_t addr, uint32_t lbo_bytes) {
  return desc_lo((addr >> 4) + ((lbo_bytes >> 4) << 16));
}

__device__ __forceinline__ void wgmma_n192_ss_ta0_tb1(float* d, uint64_t descA, uint64_t descB, int scaleD) {
  asm volatile("{\n.reg .pred p;\nsetp.ne.b32 p, %98, 0;\n"
    "wgmma.mma_async.sync.aligned.m64n192k16.f32.bf16.bf16 {%0, %1, %2, %3, %4, %5, %6, %7, %8, %9, %10, %11, %12, %13, %14, %15, %16, %17, %18, %19, %20, %21, %22, %23, %24, %25, %26, %27, %28, %29, %30, %31, %32, %33, %34, %35, %36, %37, %38, %39, %40, %41, %42, %43, %44, %45, %46, %47, %48, %49, %50, %51, %52, %53, %54, %55, %56, %57, %58, %59, %60, %61, %62, %63, %64, %65, %66, %67, %68, %69, %70, %71, %72, %73, %74, %75, %76, %77, %78, %79, %80, %81, %82, %83, %84, %85, %86, %87, %88, %89, %90, %91, %92, %93, %94, %95}, %96, %97, p, 1, 1, 0, 1;\n}\n"
    : "+f"(d[0]), "+f"(d[1]), "+f"(d[2]), "+f"(d[3]), "+f"(d[4]), "+f"(d[5]), "+f"(d[6]), "+f"(d[7]), "+f"(d[8]), "+f"(d[9]), "+f"(d[10]), "+f"(d[11]), "+f"(d[12]), "+f"(d[13]), "+f"(d[14]), "+f"(d[15]), "+f"(d[16]), "+f"(d[17]), "+f"(d[18]), "+f"(d[19]), "+f"(d[20]), "+f"(d[21]), "+f"(d[22]), "+f"(d[23]), "+f"(d[24]), "+f"(d[25]), "+f"(d[26]), "+f"(d[27]), "+f"(d[28]), "+f"(d[29]), "+f"(d[30]), "+f"(d[31]), "+f"(d[32]), "+f"(d[33]), "+f"(d[34]), "+f"(d[35]), "+f"(d[36]), "+f"(d[37]), "+f"(d[38]), "+f"(d[39]), "+f"(d[40]), "+f"(d[41]), "+f"(d[42]), "+f"(d[43]), "+f"(d[44]), "+f"(d[45]), "+f"(d[46]), "+f"(d[47]), "+f"(d[48]), "+f"(d[49]), "+f"(d[50]), "+f"(d[51]), "+f"(d[52]), "+f"(d[53]), "+f"(d[54]), "+f"(d[55]), "+f"(d[56]), "+f"(d[57]), "+f"(d[58]), "+f"(d[59]), "+f"(d[60]), "+f"(d[61]), "+f"(d[62]), "+f"(d[63]), "+f"(d[64]), "+f"(d[65]), "+f"(d[66]), "+f"(d[67]), "+f"(d[68]), "+f"(d[69]), "+f"(d[70]), "+f"(d[71]), "+f"(d[72]), "+f"(d[73]), "+f"(d[74]), "+f"(d[75]), "+f"(d[76]), "+f"(d[77]), "+f"(d[78]), "+f"(d[79]), "+f"(d[80]), "+f"(d[81]), "+f"(d[82]), "+f"(d[83]), "+f"(d[84]), "+f"(d[85]), "+f"(d[86]), "+f"(d[87]), "+f"(d[88]), "+f"(d[89]), "+f"(d[90]), "+f"(d[91]), "+f"(d[92]), "+f"(d[93]), "+f"(d[94]), "+f"(d[95])
    : "l"(descA), "l"(descB), "r"(scaleD));
}

__device__ __forceinline__ void wgmma_n128_ss_ta0_tb1(float* d, uint64_t descA, uint64_t descB, int scaleD) {
  asm volatile("{\n.reg .pred p;\nsetp.ne.b32 p, %66, 0;\n"
    "wgmma.mma_async.sync.aligned.m64n128k16.f32.bf16.bf16 {%0, %1, %2, %3, %4, %5, %6, %7, %8, %9, %10, %11, %12, %13, %14, %15, %16, %17, %18, %19, %20, %21, %22, %23, %24, %25, %26, %27, %28, %29, %30, %31, %32, %33, %34, %35, %36, %37, %38, %39, %40, %41, %42, %43, %44, %45, %46, %47, %48, %49, %50, %51, %52, %53, %54, %55, %56, %57, %58, %59, %60, %61, %62, %63}, %64, %65, p, 1, 1, 0, 1;\n}\n"
    : "+f"(d[0]), "+f"(d[1]), "+f"(d[2]), "+f"(d[3]), "+f"(d[4]), "+f"(d[5]), "+f"(d[6]), "+f"(d[7]), "+f"(d[8]), "+f"(d[9]), "+f"(d[10]), "+f"(d[11]), "+f"(d[12]), "+f"(d[13]), "+f"(d[14]), "+f"(d[15]), "+f"(d[16]), "+f"(d[17]), "+f"(d[18]), "+f"(d[19]), "+f"(d[20]), "+f"(d[21]), "+f"(d[22]), "+f"(d[23]), "+f"(d[24]), "+f"(d[25]), "+f"(d[26]), "+f"(d[27]), "+f"(d[28]), "+f"(d[29]), "+f"(d[30]), "+f"(d[31]), "+f"(d[32]), "+f"(d[33]), "+f"(d[34]), "+f"(d[35]), "+f"(d[36]), "+f"(d[37]), "+f"(d[38]), "+f"(d[39]), "+f"(d[40]), "+f"(d[41]), "+f"(d[42]), "+f"(d[43]), "+f"(d[44]), "+f"(d[45]), "+f"(d[46]), "+f"(d[47]), "+f"(d[48]), "+f"(d[49]), "+f"(d[50]), "+f"(d[51]), "+f"(d[52]), "+f"(d[53]), "+f"(d[54]), "+f"(d[55]), "+f"(d[56]), "+f"(d[57]), "+f"(d[58]), "+f"(d[59]), "+f"(d[60]), "+f"(d[61]), "+f"(d[62]), "+f"(d[63])
    : "l"(descA), "l"(descB), "r"(scaleD));
}

__device__ __forceinline__ void wgmma_n192_ssz_ta0_tb1(float* d, uint64_t descA, uint64_t descB) {
  asm volatile("{\n.reg .pred p;\nsetp.ne.b32 p, 0, 0;\n"
    "wgmma.mma_async.sync.aligned.m64n192k16.f32.bf16.bf16 {%0, %1, %2, %3, %4, %5, %6, %7, %8, %9, %10, %11, %12, %13, %14, %15, %16, %17, %18, %19, %20, %21, %22, %23, %24, %25, %26, %27, %28, %29, %30, %31, %32, %33, %34, %35, %36, %37, %38, %39, %40, %41, %42, %43, %44, %45, %46, %47, %48, %49, %50, %51, %52, %53, %54, %55, %56, %57, %58, %59, %60, %61, %62, %63, %64, %65, %66, %67, %68, %69, %70, %71, %72, %73, %74, %75, %76, %77, %78, %79, %80, %81, %82, %83, %84, %85, %86, %87, %88, %89, %90, %91, %92, %93, %94, %95}, %96, %97, p, 1, 1, 0, 1;\n}\n"
    : "=f"(d[0]), "=f"(d[1]), "=f"(d[2]), "=f"(d[3]), "=f"(d[4]), "=f"(d[5]), "=f"(d[6]), "=f"(d[7]), "=f"(d[8]), "=f"(d[9]), "=f"(d[10]), "=f"(d[11]), "=f"(d[12]), "=f"(d[13]), "=f"(d[14]), "=f"(d[15]), "=f"(d[16]), "=f"(d[17]), "=f"(d[18]), "=f"(d[19]), "=f"(d[20]), "=f"(d[21]), "=f"(d[22]), "=f"(d[23]), "=f"(d[24]), "=f"(d[25]), "=f"(d[26]), "=f"(d[27]), "=f"(d[28]), "=f"(d[29]), "=f"(d[30]), "=f"(d[31]), "=f"(d[32]), "=f"(d[33]), "=f"(d[34]), "=f"(d[35]), "=f"(d[36]), "=f"(d[37]), "=f"(d[38]), "=f"(d[39]), "=f"(d[40]), "=f"(d[41]), "=f"(d[42]), "=f"(d[43]), "=f"(d[44]), "=f"(d[45]), "=f"(d[46]), "=f"(d[47]), "=f"(d[48]), "=f"(d[49]), "=f"(d[50]), "=f"(d[51]), "=f"(d[52]), "=f"(d[53]), "=f"(d[54]), "=f"(d[55]), "=f"(d[56]), "=f"(d[57]), "=f"(d[58]), "=f"(d[59]), "=f"(d[60]), "=f"(d[61]), "=f"(d[62]), "=f"(d[63]), "=f"(d[64]), "=f"(d[65]), "=f"(d[66]), "=f"(d[67]), "=f"(d[68]), "=f"(d[69]), "=f"(d[70]), "=f"(d[71]), "=f"(d[72]), "=f"(d[73]), "=f"(d[74]), "=f"(d[75]), "=f"(d[76]), "=f"(d[77]), "=f"(d[78]), "=f"(d[79]), "=f"(d[80]), "=f"(d[81]), "=f"(d[82]), "=f"(d[83]), "=f"(d[84]), "=f"(d[85]), "=f"(d[86]), "=f"(d[87]), "=f"(d[88]), "=f"(d[89]), "=f"(d[90]), "=f"(d[91]), "=f"(d[92]), "=f"(d[93]), "=f"(d[94]), "=f"(d[95])
    : "l"(descA), "l"(descB));
}

__device__ __forceinline__ void wgmma_n192_rs_tb1(float* d, uint32_t a0, uint32_t a1, uint64_t descB) {
  asm volatile("{\n.reg .pred p;\nsetp.eq.b32 p, 0, 0;\n"
    "wgmma.mma_async.sync.aligned.m64n192k16.f32.bf16.bf16 {%0, %1, %2, %3, %4, %5, %6, %7, %8, %9, %10, %11, %12, %13, %14, %15, %16, %17, %18, %19, %20, %21, %22, %23, %24, %25, %26, %27, %28, %29, %30, %31, %32, %33, %34, %35, %36, %37, %38, %39, %40, %41, %42, %43, %44, %45, %46, %47, %48, %49, %50, %51, %52, %53, %54, %55, %56, %57, %58, %59, %60, %61, %62, %63, %64, %65, %66, %67, %68, %69, %70, %71, %72, %73, %74, %75, %76, %77, %78, %79, %80, %81, %82, %83, %84, %85, %86, %87, %88, %89, %90, %91, %92, %93, %94, %95}, {%96, %97, %98, %98}, %99, p, 1, 1, 1;\n}\n"
    : "+f"(d[0]), "+f"(d[1]), "+f"(d[2]), "+f"(d[3]), "+f"(d[4]), "+f"(d[5]), "+f"(d[6]), "+f"(d[7]), "+f"(d[8]), "+f"(d[9]), "+f"(d[10]), "+f"(d[11]), "+f"(d[12]), "+f"(d[13]), "+f"(d[14]), "+f"(d[15]), "+f"(d[16]), "+f"(d[17]), "+f"(d[18]), "+f"(d[19]), "+f"(d[20]), "+f"(d[21]), "+f"(d[22]), "+f"(d[23]), "+f"(d[24]), "+f"(d[25]), "+f"(d[26]), "+f"(d[27]), "+f"(d[28]), "+f"(d[29]), "+f"(d[30]), "+f"(d[31]), "+f"(d[32]), "+f"(d[33]), "+f"(d[34]), "+f"(d[35]), "+f"(d[36]), "+f"(d[37]), "+f"(d[38]), "+f"(d[39]), "+f"(d[40]), "+f"(d[41]), "+f"(d[42]), "+f"(d[43]), "+f"(d[44]), "+f"(d[45]), "+f"(d[46]), "+f"(d[47]), "+f"(d[48]), "+f"(d[49]), "+f"(d[50]), "+f"(d[51]), "+f"(d[52]), "+f"(d[53]), "+f"(d[54]), "+f"(d[55]), "+f"(d[56]), "+f"(d[57]), "+f"(d[58]), "+f"(d[59]), "+f"(d[60]), "+f"(d[61]), "+f"(d[62]), "+f"(d[63]), "+f"(d[64]), "+f"(d[65]), "+f"(d[66]), "+f"(d[67]), "+f"(d[68]), "+f"(d[69]), "+f"(d[70]), "+f"(d[71]), "+f"(d[72]), "+f"(d[73]), "+f"(d[74]), "+f"(d[75]), "+f"(d[76]), "+f"(d[77]), "+f"(d[78]), "+f"(d[79]), "+f"(d[80]), "+f"(d[81]), "+f"(d[82]), "+f"(d[83]), "+f"(d[84]), "+f"(d[85]), "+f"(d[86]), "+f"(d[87]), "+f"(d[88]), "+f"(d[89]), "+f"(d[90]), "+f"(d[91]), "+f"(d[92]), "+f"(d[93]), "+f"(d[94]), "+f"(d[95])
    : "r"(a0), "r"(a1), "r"(0u), "l"(descB));
}

__device__ __forceinline__ void wgmma_n128_ssz_ta0_tb1(float* d, uint64_t descA, uint64_t descB) {
  asm volatile("{\n.reg .pred p;\nsetp.ne.b32 p, 0, 0;\n"
    "wgmma.mma_async.sync.aligned.m64n128k16.f32.bf16.bf16 {%0, %1, %2, %3, %4, %5, %6, %7, %8, %9, %10, %11, %12, %13, %14, %15, %16, %17, %18, %19, %20, %21, %22, %23, %24, %25, %26, %27, %28, %29, %30, %31, %32, %33, %34, %35, %36, %37, %38, %39, %40, %41, %42, %43, %44, %45, %46, %47, %48, %49, %50, %51, %52, %53, %54, %55, %56, %57, %58, %59, %60, %61, %62, %63}, %64, %65, p, 1, 1, 0, 1;\n}\n"
    : "=f"(d[0]), "=f"(d[1]), "=f"(d[2]), "=f"(d[3]), "=f"(d[4]), "=f"(d[5]), "=f"(d[6]), "=f"(d[7]), "=f"(d[8]), "=f"(d[9]), "=f"(d[10]), "=f"(d[11]), "=f"(d[12]), "=f"(d[13]), "=f"(d[14]), "=f"(d[15]), "=f"(d[16]), "=f"(d[17]), "=f"(d[18]), "=f"(d[19]), "=f"(d[20]), "=f"(d[21]), "=f"(d[22]), "=f"(d[23]), "=f"(d[24]), "=f"(d[25]), "=f"(d[26]), "=f"(d[27]), "=f"(d[28]), "=f"(d[29]), "=f"(d[30]), "=f"(d[31]), "=f"(d[32]), "=f"(d[33]), "=f"(d[34]), "=f"(d[35]), "=f"(d[36]), "=f"(d[37]), "=f"(d[38]), "=f"(d[39]), "=f"(d[40]), "=f"(d[41]), "=f"(d[42]), "=f"(d[43]), "=f"(d[44]), "=f"(d[45]), "=f"(d[46]), "=f"(d[47]), "=f"(d[48]), "=f"(d[49]), "=f"(d[50]), "=f"(d[51]), "=f"(d[52]), "=f"(d[53]), "=f"(d[54]), "=f"(d[55]), "=f"(d[56]), "=f"(d[57]), "=f"(d[58]), "=f"(d[59]), "=f"(d[60]), "=f"(d[61]), "=f"(d[62]), "=f"(d[63])
    : "l"(descA), "l"(descB));
}

__device__ __forceinline__ void wgmma_n64_ss_ta0_tb0(float* d, uint64_t descA, uint64_t descB, int scaleD) {
  asm volatile("{\n.reg .pred p;\nsetp.ne.b32 p, %34, 0;\n"
    "wgmma.mma_async.sync.aligned.m64n64k16.f32.bf16.bf16 {%0, %1, %2, %3, %4, %5, %6, %7, %8, %9, %10, %11, %12, %13, %14, %15, %16, %17, %18, %19, %20, %21, %22, %23, %24, %25, %26, %27, %28, %29, %30, %31}, %32, %33, p, 1, 1, 0, 0;\n}\n"
    : "+f"(d[0]), "+f"(d[1]), "+f"(d[2]), "+f"(d[3]), "+f"(d[4]), "+f"(d[5]), "+f"(d[6]), "+f"(d[7]), "+f"(d[8]), "+f"(d[9]), "+f"(d[10]), "+f"(d[11]), "+f"(d[12]), "+f"(d[13]), "+f"(d[14]), "+f"(d[15]), "+f"(d[16]), "+f"(d[17]), "+f"(d[18]), "+f"(d[19]), "+f"(d[20]), "+f"(d[21]), "+f"(d[22]), "+f"(d[23]), "+f"(d[24]), "+f"(d[25]), "+f"(d[26]), "+f"(d[27]), "+f"(d[28]), "+f"(d[29]), "+f"(d[30]), "+f"(d[31])
    : "l"(descA), "l"(descB), "r"(scaleD));
}

__device__ __forceinline__ void wgmma_n64_ssz_ta0_tb0(float* d, uint64_t descA, uint64_t descB) {
  asm volatile("{\n.reg .pred p;\nsetp.ne.b32 p, 0, 0;\n"
    "wgmma.mma_async.sync.aligned.m64n64k16.f32.bf16.bf16 {%0, %1, %2, %3, %4, %5, %6, %7, %8, %9, %10, %11, %12, %13, %14, %15, %16, %17, %18, %19, %20, %21, %22, %23, %24, %25, %26, %27, %28, %29, %30, %31}, %32, %33, p, 1, 1, 0, 0;\n}\n"
    : "=f"(d[0]), "=f"(d[1]), "=f"(d[2]), "=f"(d[3]), "=f"(d[4]), "=f"(d[5]), "=f"(d[6]), "=f"(d[7]), "=f"(d[8]), "=f"(d[9]), "=f"(d[10]), "=f"(d[11]), "=f"(d[12]), "=f"(d[13]), "=f"(d[14]), "=f"(d[15]), "=f"(d[16]), "=f"(d[17]), "=f"(d[18]), "=f"(d[19]), "=f"(d[20]), "=f"(d[21]), "=f"(d[22]), "=f"(d[23]), "=f"(d[24]), "=f"(d[25]), "=f"(d[26]), "=f"(d[27]), "=f"(d[28]), "=f"(d[29]), "=f"(d[30]), "=f"(d[31])
    : "l"(descA), "l"(descB));
}

__device__ __forceinline__ void wgmma_n80_ss_ta0_tb0(float* d, uint64_t descA, uint64_t descB, int scaleD) {
  asm volatile("{\n.reg .pred p;\nsetp.ne.b32 p, %42, 0;\n"
    "wgmma.mma_async.sync.aligned.m64n80k16.f32.bf16.bf16 {%0, %1, %2, %3, %4, %5, %6, %7, %8, %9, %10, %11, %12, %13, %14, %15, %16, %17, %18, %19, %20, %21, %22, %23, %24, %25, %26, %27, %28, %29, %30, %31, %32, %33, %34, %35, %36, %37, %38, %39}, %40, %41, p, 1, 1, 0, 0;\n}\n"
    : "+f"(d[0]), "+f"(d[1]), "+f"(d[2]), "+f"(d[3]), "+f"(d[4]), "+f"(d[5]), "+f"(d[6]), "+f"(d[7]), "+f"(d[8]), "+f"(d[9]), "+f"(d[10]), "+f"(d[11]), "+f"(d[12]), "+f"(d[13]), "+f"(d[14]), "+f"(d[15]), "+f"(d[16]), "+f"(d[17]), "+f"(d[18]), "+f"(d[19]), "+f"(d[20]), "+f"(d[21]), "+f"(d[22]), "+f"(d[23]), "+f"(d[24]), "+f"(d[25]), "+f"(d[26]), "+f"(d[27]), "+f"(d[28]), "+f"(d[29]), "+f"(d[30]), "+f"(d[31]), "+f"(d[32]), "+f"(d[33]), "+f"(d[34]), "+f"(d[35]), "+f"(d[36]), "+f"(d[37]), "+f"(d[38]), "+f"(d[39])
    : "l"(descA), "l"(descB), "r"(scaleD));
}

__device__ __forceinline__ void wgmma_n32_rs_tb1(float* d, const uint32_t* a, uint64_t descB, int scaleD) {
  asm volatile("{\n.reg .pred p;\nsetp.ne.b32 p, %21, 0;\n"
    "wgmma.mma_async.sync.aligned.m64n32k16.f32.bf16.bf16 {%0, %1, %2, %3, %4, %5, %6, %7, %8, %9, %10, %11, %12, %13, %14, %15}, {%16, %17, %18, %19}, %20, p, 1, 1, 1;\n}\n"
    : "+f"(d[0]), "+f"(d[1]), "+f"(d[2]), "+f"(d[3]), "+f"(d[4]), "+f"(d[5]), "+f"(d[6]), "+f"(d[7]), "+f"(d[8]), "+f"(d[9]), "+f"(d[10]), "+f"(d[11]), "+f"(d[12]), "+f"(d[13]), "+f"(d[14]), "+f"(d[15])
    : "r"(a[0]), "r"(a[1]), "r"(a[2]), "r"(a[3]), "l"(descB), "r"(scaleD));
}

__device__ __forceinline__ uint32_t pack_bf16x2(float lo, float hi) {
  uint32_t r;
  asm("cvt.rn.bf16x2.f32 %0, %1, %2;" : "=r"(r) : "f"(hi), "f"(lo));
  return r;
}
__device__ __forceinline__ float bf_lo(uint32_t p) { return __uint_as_float(p << 16); }
__device__ __forceinline__ float bf_hi(uint32_t p) { return __uint_as_float(p & 0xffff0000u); }
__device__ __forceinline__ float bf16_round(float v) { return __bfloat162float(__float2bfloat16_rn(v)); }
__device__ __forceinline__ float ex2_approx(float x) {
  float r;
  asm("ex2.approx.ftz.f32 %0, %1;" : "=f"(r) : "f"(x));
  return r;
}
__device__ __forceinline__ float rcp_fast(float x) {
  float r;
  asm("rcp.approx.ftz.f32 %0, %1;" : "=f"(r) : "f"(x));
  return r;
}
__device__ __forceinline__ void ldmatrix_x4(uint32_t (&r)[4], uint32_t addr) {
  asm volatile("ldmatrix.sync.aligned.m8n8.x4.shared.b16 {%0,%1,%2,%3}, [%4];"
               : "=r"(r[0]), "=r"(r[1]), "=r"(r[2]), "=r"(r[3])
               : "r"(sw(addr))
               : "memory");
}
__device__ __forceinline__ void stmatrix_x4(uint32_t addr, uint32_t r0, uint32_t r1, uint32_t r2, uint32_t r3) {
  asm volatile("stmatrix.sync.aligned.m8n8.x4.shared.b16 [%0], {%1,%2,%3,%4};" ::"r"(sw(addr)), "r"(r0), "r"(r1), "r"(r2),
               "r"(r3));
}
__device__ __forceinline__ uint32_t add_bf16x2(uint32_t a, uint32_t b) {
  uint32_t r;
  asm("add.rn.bf16x2 %0, %1, %2;" : "=r"(r) : "r"(a), "r"(b));
  return r;
}
__device__ __forceinline__ uint4 lds128(uint32_t addr) {
  uint4 v;
  asm volatile("ld.shared.v4.b32 {%0,%1,%2,%3}, [%4];" : "=r"(v.x), "=r"(v.y), "=r"(v.z), "=r"(v.w) : "r"(sw(addr)) : "memory");
  return v;
}
__device__ __forceinline__ uint32_t lds32(uint32_t addr) {
  uint32_t v;
  asm volatile("ld.shared.b32 %0, [%1];" : "=r"(v) : "r"(sw(addr)) : "memory");
  return v;
}
__device__ __forceinline__ void sts32(uint32_t addr, uint32_t v) {
  asm volatile("st.shared.b32 [%0], %1;" ::"r"(sw(addr)), "r"(v) : "memory");
}

__device__ __forceinline__ unsigned ld_acquire_u32(const unsigned* p) {
  unsigned v;
  asm volatile("ld.acquire.gpu.global.u32 %0, [%1];" : "=r"(v) : "l"(p) : "memory");
  return v;
}
__device__ __forceinline__ unsigned atom_add(unsigned* p, unsigned v, bool on) {
  unsigned r = 0;
  asm volatile("{\n.reg .pred p;\nsetp.ne.u32 p, %3, 0;\n@p atom.relaxed.gpu.global.add.u32 %0, [%1], %2;\n}\n"
               : "+r"(r) : "l"(p), "r"(v), "r"((uint32_t)on) : "memory");
  return r;
}
__device__ __forceinline__ void red_relaxed_add(unsigned* p, unsigned v) {
  asm volatile("red.relaxed.gpu.global.add.u32 [%0], %1;" ::"l"(p), "r"(v) : "memory");
}
__device__ __forceinline__ void red_release_add(unsigned* p, unsigned v) {
  asm volatile("red.release.gpu.global.add.u32 [%0], %1;" ::"l"(p), "r"(v) : "memory");
}
#define RED_O red_relaxed_add
#define RED_X red_relaxed_add
#define RED_K red_relaxed_add
template <int N>
__device__ __forceinline__ unsigned read_back(const void* p, int stride, uint32_t zero) {
  uint32_t v[N];
#pragma unroll
  for (int i = 0; i < N; i++)
    asm volatile("ld.relaxed.gpu.global.u32 %0, [%1];" : "=r"(v[i]) : "l"(static_cast<const char*>(p) + i * stride) : "memory");
  uint32_t x = v[0];
#pragma unroll
  for (int i = 1; i < N; i++) x |= v[i];
  return (x & zero) + 1u;
}
__device__ __forceinline__ void wait_ge2(const unsigned* p, unsigned t0, unsigned t1) {
#pragma unroll 1
  for (uint32_t it = 0; it < (1u << 17); ++it) {
    unsigned long long v;
    asm volatile("ld.acquire.gpu.global.u64 %0, [%1];" : "=l"(v) : "l"(p) : "memory");
    if ((int)((unsigned)v - t0) >= 0 && (int)((unsigned)(v >> 32) - t1) >= 0) return;
  }
}

#define PDEPTH 1
#define RELNS 100
#define HDELAY 500
#define WU 3
constexpr int WUNR = WU;
#define PCS 1024
#define PCN 30
#define PUBPOS 0
#define PGAP 100
template <bool SLOW>
__device__ __forceinline__ void wait_mask(const unsigned* f, int cnt, unsigned target, uint32_t need, uint32_t& seen, int lane) {
  if ((seen & need) == need) return;
  const unsigned* fp = f + (lane & (cnt - 1));
#pragma unroll 1
  for (uint32_t it = 0; it < (1u << 17); ++it) {
    seen = __ballot_sync(0xffffffffu, (int)(ld_acquire_u32(fp) - target) >= 0);
    if ((seen & need) == need) break;
    if (SLOW) __nanosleep(400);
  }
  fence_proxy_async_all();
}
__device__ __forceinline__ void wait_lanes(const unsigned* fp, unsigned target, uint32_t need, uint32_t& seen) {
  if ((seen & need) == need) return;
  unsigned v[PDEPTH];
#pragma unroll
  for (int i = 0; i < PDEPTH; i++) {
    asm volatile("ld.relaxed.gpu.global.u32 %0, [%1];" : "=r"(v[i]) : "l"(fp) : "memory");
    if (i + 1 < PDEPTH) __nanosleep(PGAP);
  }
#pragma unroll 1
  for (uint32_t it = 0; it < (1u << 16); ++it) {
#pragma unroll
    for (int i = 0; i < PDEPTH; i++) {
      seen |= __ballot_sync(0xffffffffu, (int)(v[i] - target) >= 0);
      if ((seen & need) == need) goto done;
      asm volatile("ld.relaxed.gpu.global.u32 %0, [%1];" : "=r"(v[i]) : "l"(fp) : "memory");
    }
  }
done:
  fence_proxy_async_all();
}
__device__ __forceinline__ float4 ld_rec(const float4* p) {
  float4 v;
  asm volatile("ld.relaxed.gpu.global.v4.f32 {%0,%1,%2,%3}, [%4];" : "=f"(v.x), "=f"(v.y), "=f"(v.z), "=f"(v.w) : "l"(p) : "memory");
  return v;
}
__device__ __forceinline__ void st_rec(float4* p, float a, float b, float c, unsigned tag) {
  asm volatile("st.relaxed.gpu.global.v4.f32 [%0], {%1,%2,%3,%4};" ::"l"(p), "f"(a), "f"(b), "f"(c), "f"(__uint_as_float(tag)) : "memory");
}
template <int N>
__device__ __forceinline__ float4 sum_recs(const float4* p, int stride, unsigned tag) {
  float4 s;
#pragma unroll 1
  for (uint32_t it = 0; it < (1u << 17); ++it) {
    float4 v[N];
#pragma unroll
    for (int t = 0; t < N; t++) v[t] = ld_rec(p + t * stride);
    bool ok = true;
    s = make_float4(0.f, 0.f, 0.f, 0.f);
#pragma unroll
    for (int t = 0; t < N; t++) {
      ok &= __float_as_uint(v[t].w) == tag;
      s.x += v[t].x;
      s.y += v[t].y;
      s.z += v[t].z;
    }
    if (ok) break;
    __nanosleep(200);
  }
  return s;
}

__device__ __forceinline__ int fresh_tid() {
  int t;
  asm volatile("mov.u32 %0, %%tid.x;" : "=r"(t));
  return t;
}
#define PHASE_IDS                                  \
  const int tid_ = fresh_tid();                    \
  const int lane = tid_ & 31, wwarp = __shfl_sync(0xffffffffu, (tid_ >> 5) & 3, 0), tid = tid_ & 127; \
  const int g = lane >> 2, c = lane & 3;           \
  (void)tid; (void)g; (void)c; (void)wwarp;

#define STAMPW(cond, i) do { } while (0)
#define STAMP(cond, i) do { } while (0)
#define KSPN true
#define KSAON false
#define STA(i) do { } while (0)
#define GTL(i) do { } while (0)
#define GTLX(c, i) do { } while (0)
#define TGET(v) do { } while (0)
#define TPUT(c, i, v) do { } while (0)

constexpr float SM_C = 0.17677669529663687f * 1.4426950408889634f;

constexpr uint32_t OA_TILE = SBASE + OFF_SLOT + 16384;

__device__ __forceinline__ void sched_fence(uint32_t never) {
  asm volatile("{\n.reg .pred p;\nsetp.ne.u32 p, %0, 0;\n@p exit;\n}\n" ::"r"(never) : "memory");
}

template <int K0, int K1>
__device__ __forceinline__ void attn_exp(float (&s)[32]) {
#pragma unroll
  for (int k = K0; k < K1; k++) s[k] = ex2_approx(s[k]);
}
#define ASPL 16
#define ASPM 6
template <int MODE, bool NEXT>
__device__ __forceinline__ void attn_unit(float (&s)[32], float (&sn)[32], float (&o)[16], float (&l)[2], bool valid,
                                          uint32_t vdesc, uint32_t qdesc, uint32_t kdesc, uint32_t tri, int w,
                                          uint32_t hbar, uint32_t hpar, uint32_t rel, uint32_t zero, bool stampon = false) {
  float x[9][2];
  if (MODE == 0) {
    attn_exp<0, ASPL>(s);
  } else {
#pragma unroll
    for (int e = 0; e < 2; e++) {
#pragma unroll
      for (int j = 0; j < 4; j++) x[j][e] = MODE == 1 ? s[4 * j + 2 + e] : s[16 + 4 * j + e];
      x[4][e] = MODE == 1 ? s[e] : s[30 + e];
      x[5][e] = MODE == 1 ? s[18 + e] : s[12 + e];
#pragma unroll
      for (int u = 1; u < 4; u++)
        x[5 + u][e] = MODE == 1 ? (w >= u ? s[4 * u + e] : s[4 * (8 - u) + 2 + e]) : (w >= u ? s[4 * (7 - u) + 2 + e] : s[4 * (u - 1) + e]);
    }
#pragma unroll
    for (int k = 0; k < 2 * ASPM; k++) x[k >> 1][k & 1] = ex2_approx(x[k >> 1][k & 1]);
  }
  sched_fence(zero);
  if (hbar) mbar_wait(hbar, hpar);
  wgmma_wait<0>();
  if (rel) mbar_arrive(rel);
  if (NEXT) {
    wgmma_fence();
    wgmma_n64_ssz_ta0_tb0(sn, desc_lo(qdesc), desc_lo(kdesc));
    wgmma_n64_ss_ta0_tb0(sn, desc_lo(qdesc + 2), desc_lo(kdesc + 2), 1);
    wgmma_commit();
    sched_fence(zero);
  }
  uint32_t p[16];
  if (MODE == 0) {
    attn_exp<ASPL, 32>(s);
#pragma unroll
    for (int k = 0; k < 16; k++) p[k] = pack_bf16x2(s[2 * k], s[2 * k + 1]);
  } else {
#pragma unroll
    for (int k = 2 * ASPM; k < 18; k++) x[k >> 1][k & 1] = ex2_approx(x[k >> 1][k & 1]);
    const uint32_t tm = MODE == 1 ? tri : ~tri;
#pragma unroll
    for (int j = 0; j < 4; j++) {
      p[MODE == 1 ? 2 * j + 1 : 8 + 2 * j] = pack_bf16x2(x[j][0], x[j][1]);
      p[MODE == 1 ? 8 + 2 * j : 2 * j + 1] = 0u;
    }
    p[MODE == 1 ? 0 : 15] = pack_bf16x2(x[4][0], x[4][1]) & (w == 0 ? tm : 0xffffffffu);
    p[MODE == 1 ? 9 : 6] = pack_bf16x2(x[5][0], x[5][1]) & (w == 3 ? tm : 0xffffffffu);
#pragma unroll
    for (int u = 1; u < 4; u++) {
      const uint32_t q = pack_bf16x2(x[5 + u][0], x[5 + u][1]);
      p[MODE == 1 ? 2 * u : 2 * (7 - u) + 1] = q & (w > u ? 0xffffffffu : (w == u ? tm : 0u));
      p[MODE == 1 ? 2 * (8 - u) + 1 : 2 * (u - 1)] = q & (w < u - 1 ? 0xffffffffu : (w == u - 1 ? tm : 0u));
    }
  }
  wgmma_fence();
#pragma unroll
  for (int k = 0; k < 4; k++) wgmma_n32_rs_tb1(o, p + 4 * k, desc_lo(vdesc + k * 128), 1);
  wgmma_commit();
#pragma unroll
  for (int r = 0; r < 2; r++) {
    float t = 0.f;
#pragma unroll
    for (int hf = 0; hf < 2; hf++) {
      if (MODE != 0 && r == MODE - 1 && hf == 2 - MODE) continue;
      const uint32_t* q = p + 8 * hf + r;
      const uint32_t v = add_bf16x2(add_bf16x2(q[0], q[2]), add_bf16x2(q[4], q[6]));
      t = (MODE != 0 && r == MODE - 1) || hf == 0 ? bf_lo(v) + bf_hi(v) : t + (bf_lo(v) + bf_hi(v));
    }
    if (valid) l[r] += t;
  }
  if (NEXT) {
    wgmma_wait<1>();
    reg_fence<32>(sn);
  }
}

__device__ __forceinline__ void attn_a_slow(const uint8_t* __restrict__ kvimg, int L, int gb, int hp,
                                         int hh, int wwarp, int lane) {
  constexpr uint32_t sq = SBASE + OFF_SLOT + 3 * 16384;
  const unsigned ep = (*(volatile unsigned*)(g_flags + F_DONE)) / NCTA;
  wait_ge2(g_flags + F_KV + (gb * 16 + hp) * KSTR, 4u * ep + L + 1u, 2u * ep + (L >> 1) + 1u);
#pragma unroll 1
  for (int t = 0; t < 32; t++) {
    const int row = (t >> 4) * 64 + ((t & 8) ? 7 - wwarp : wwarp) * 8 + (t & 7);
    const int qpos = gb * 128 + row;
    const uint32_t qaddr = sq + ((t >> 4) * 64 + wwarp * 16 + (t & 15)) * 128;
    float mx = -INFINITY, sum = 0.f, acc = 0.f;
#pragma unroll 1
    for (int pass = 0; pass < 2; pass++) {
#pragma unroll 1
      for (int j = 0; j < 8; j++) {
        const int kp = qpos - (lane + 32 * j);
        const uint8_t* kr = kvimg + ((size_t)((kp >> 7) * 16 + hp) * 2 + ((kp >> 6) & 1)) * 16384 + (kp & 63) * 128;
        float d = -INFINITY;
        if (kp >= 0) {
          d = 0.f;
#pragma unroll 1
          for (int q = 0; q < 4; q++) {
            const uint4 kv = __ldcg(reinterpret_cast<const uint4*>(kr + (((hh * 4 + q) ^ (kp & 7)) << 4)));
            const uint4 qv = lds128(qaddr + (((hh * 4 + q) ^ (row & 7)) << 4));
            const uint32_t kw[4] = {kv.x, kv.y, kv.z, kv.w}, qw[4] = {qv.x, qv.y, qv.z, qv.w};
#pragma unroll
            for (int e = 0; e < 4; e++) d = fmaf(bf_lo(kw[e]), bf_lo(qw[e]), fmaf(bf_hi(kw[e]), bf_hi(qw[e]), d));
          }
        }
        if (pass == 0) {
          mx = fmaxf(mx, d);
        } else {
          const float ev = ex2_approx(d - mx);
          sum += ev;
          const float pv = bf16_round(ev);
#pragma unroll 1
          for (int kk = 0; kk < 32; kk++) {
            const float pk = __shfl_sync(0xffffffffu, pv, kk);
            const int k2 = qpos - (kk + 32 * j);
            if (k2 >= 0) {
              const uint8_t* vr = kvimg + ((size_t)((k2 >> 7) * 16 + hp) * 2 + ((k2 >> 6) & 1)) * 16384 + 8192 + (k2 & 63) * 128;
              const unsigned short vv =
                  __ldcg(reinterpret_cast<const unsigned short*>(vr + (((hh * 4 + (lane >> 3)) ^ (k2 & 7)) << 4) + (lane & 7) * 2));
              acc = fmaf(pk, __uint_as_float((uint32_t)vv << 16), acc);
            }
          }
        }
      }
      if (pass == 0) {
#pragma unroll
        for (int o = 16; o > 0; o >>= 1) mx = fmaxf(mx, __shfl_xor_sync(0xffffffffu, mx, o));
      }
    }
#pragma unroll
    for (int o = 16; o > 0; o >>= 1) sum += __shfl_xor_sync(0xffffffffu, sum, o);
    acc *= rcp_fast(sum);
    const float hi = __shfl_down_sync(0xffffffffu, acc, 1);
    __syncwarp();
    if ((lane & 1) == 0)
      sts32(OA_TILE + row * 128 + (((hh * 4 + (lane >> 3)) ^ (row & 7)) << 4) + (lane & 7) * 2, pack_bf16x2(acc, hi));
    __syncwarp();
  }
}

__device__ __forceinline__ void store_o(const float (&o)[16], const float (&inv)[2], uint32_t rowaddr, int hh, int lane) {
  const int mat = lane >> 3, r7 = lane & 7;
#pragma unroll
  for (int jp = 0; jp < 2; jp++)
    stmatrix_x4(rowaddr + (((hh * 4 + 2 * jp + (mat >> 1)) ^ r7) << 4),
                pack_bf16x2(o[8 * jp] * inv[0], o[8 * jp + 1] * inv[0]),
                pack_bf16x2(o[8 * jp + 2] * inv[1], o[8 * jp + 3] * inv[1]),
                pack_bf16x2(o[8 * jp + 4] * inv[0], o[8 * jp + 5] * inv[0]),
                pack_bf16x2(o[8 * jp + 6] * inv[1], o[8 * jp + 7] * inv[1]));
}

__device__ __forceinline__ void attention_a(int HH, int L, int gb, int hp, uint32_t par0, uint32_t parA, int wwarp, int lane,
                                            uint32_t zero) {
  constexpr uint32_t bars = SBASE + OFF_BAR;
  const uint32_t dslot = ((SBASE + OFF_SLOT) >> 4) + 0x10000u + HH * 4;
  const uint32_t dq = dslot + 3 * 1024;
  float sa[32], sb[32], o[2][16], l[2][2];
  auto dch = [&](int n) { return dslot + 1024u * (n % 3 == 0 ? 1 : (n % 3 == 1 ? 0 : 2)); };
  wgmma_fence();
  wgmma_n64_ssz_ta0_tb0(sa, desc_lo(dq + 512), desc_lo(dch(0)));
  wgmma_n64_ss_ta0_tb0(sa, desc_lo(dq + 512 + 2), desc_lo(dch(0) + 2), 1);
  wgmma_commit();
#pragma unroll
  for (int h = 0; h < 2; h++) {
#pragma unroll
    for (int i = 0; i < 16; i++) o[h][i] = 0.f;
    l[h][0] = l[h][1] = 0.f;
  }
  const int dg = (lane >> 2) - 2 * (lane & 3);
  const uint32_t tri = (dg >= 0 ? 0xffffu : 0u) | (dg >= 1 ? 0xffff0000u : 0u);
  const int nmax = 2 * gb + 1;
  wgmma_wait<0>();
  reg_fence<32>(sa);
#define STON false
  auto publish = [&]() {
    if (HH && wwarp == 1) {
      if (lane == 0) {
        bulk_wait0();
        fence_proxy_async_all();
      }
      __syncwarp();
      const unsigned one = read_back<4>(g_kvA[L >> 1][gb][hp][0] + lane * 128, 4096, zero);
      if (lane == 0) RED_K(g_flags + F_KV + (gb * 16 + hp) * KSTR + 1, one);
    }
    __syncwarp();
  };
#define ATT_STEP(i, MODE)                                                                                            \
  attn_unit<MODE, true>(sa, sb, o[1], l[1], i <= nmax, dch(i) + 512, dq, dch(i + 1), tri, wwarp,                     \
                        i >= 1 ? bars + 8u * (B_HALO + i - 1) : 0u, i == 1 ? par0 : parA, 0u, zero, STON); if (i == 0 && PUBPOS == 0) publish();                \
  attn_unit<MODE, (i < 4)>(sb, sa, o[0], l[0], i + 1 <= nmax, dch(i + 1) + 512, dq + 512, dch(i + 1), tri, wwarp, 0u, \
                           0u, i < 3 && lane == 0 ? bars + 8u * (B_REL + i) : 0u, zero);
  ATT_STEP(0, 1)
  if (PUBPOS == 1) publish();
  ATT_STEP(1, 0)
  ATT_STEP(2, 0)
  ATT_STEP(3, 0)
  ATT_STEP(4, 2)
#undef ATT_STEP
  const uint32_t ra = OA_TILE + (((lane & 8) ? 7 - wwarp : wwarp) * 8 + (lane & 7)) * 128;
  bool bad = false;
#pragma unroll
  for (int h = 1; h >= 0; h--) {
    float inv[2];
#pragma unroll
    for (int r = 0; r < 2; r++) {
      float v = l[h][r];
      v += __shfl_xor_sync(0xffffffffu, v, 1);
      v += __shfl_xor_sync(0xffffffffu, v, 2);
      bad |= !(v <= 1.152921504606846976e18f && v >= 8.673617379884035e-19f);
      inv[r] = rcp_fast(v);
    }
    if (h == 0) wgmma_wait<0>();
    reg_fence<16>(o[h]);
    store_o(o[h], inv, ra + h * 8192, HH, lane);
  }
  if (HH == 0) GTL(45);
  if (__any_sync(0xffffffffu, bad)) attn_a_slow(g_kvA[L >> 1][0][0][0], L, gb, hp, HH, wwarp, lane);
}

constexpr uint32_t KB_ROW0 = SBASE + OFF_SLOT + 2048, VB_ROW0 = SBASE + OFF_SLOT + 24576 + 2048;

__device__ __forceinline__ void attnB_soft(const float (&s)[40], int wwarp, int D, bool edge, bool odd,
                                           uint32_t (&p)[5][4], float (&sum)[2]) {
  float z[2][3];
#define GATHER_(W)                                                                                  \
  _Pragma("unroll") for (int r = 0; r < 2; r++) _Pragma("unroll") for (int t = 0; t < 3; t++)       \
      z[r][t] = odd ? s[4 * (2 * W + r + t) + 2 * r + 1] : s[4 * (2 * W + r + t) + 2 * r];
  if (wwarp < 2) {
    if (wwarp == 0) { GATHER_(0) } else { GATHER_(1) }
  } else {
    if (wwarp == 2) { GATHER_(2) } else { GATHER_(3) }
  }
#undef GATHER_
  float y[2];
  y[0] = D >= 2 ? z[0][0] : z[0][2];
  y[1] = D >= 2 ? z[1][0] : z[1][2];
  if (edge) {
    z[0][1] = -INFINITY;
    if (D >= 2) y[0] = y[1] = -INFINITY;
  }
  float m0 = fmaxf(z[0][1], y[0]), m1 = fmaxf(z[1][1], y[1]);
  m0 = fmaxf(m0, __shfl_xor_sync(0xffffffffu, m0, 1));
  m1 = fmaxf(m1, __shfl_xor_sync(0xffffffffu, m1, 1));
  m0 = fmaxf(m0, __shfl_xor_sync(0xffffffffu, m0, 2));
  m1 = fmaxf(m1, __shfl_xor_sync(0xffffffffu, m1, 2));
  const float e00 = ex2_approx(z[0][1] - m0), e01 = ex2_approx(y[0] - m0);
  const float e10 = ex2_approx(z[1][1] - m1), e11 = ex2_approx(y[1] - m1);
  sum[0] = e00 + e01;
  sum[1] = e10 + e11;
  const int sh = odd ? 16 : 0;
  const uint32_t a0 = pack_bf16x2(e00, 0.f) << sh, a1 = pack_bf16x2(e10, 0.f) << sh;
  const uint32_t b0 = pack_bf16x2(e01, 0.f) << sh, b1 = pack_bf16x2(e11, 0.f) << sh;
  const int kb = wwarp + (D >= 2 ? 0 : 1);
#pragma unroll
  for (int k = 0; k < 5; k++) {
    p[k][0] = k == kb ? b0 : 0u;
    p[k][1] = k == wwarp + 1 ? a1 : 0u;
    p[k][2] = k == wwarp ? a0 : 0u;
    p[k][3] = k == kb ? b1 : 0u;
#pragma unroll
    for (int q = 0; q < 4; q++) asm volatile("" : "+r"(p[k][q]));
  }
}

__device__ __forceinline__ void attnB_s(float (&s)[40], int HH, int h) {
  constexpr uint32_t sq = SBASE + OFF_SLOT + 3 * 16384;
#pragma unroll
  for (int ks = 0; ks < 2; ks++)
    wgmma_n80_ss_ta0_tb0(s, make_desc(sq + h * 8192 + HH * 64 + ks * 32, 16),
                         make_desc(KB_ROW0 + h * 8192 - 2048 + HH * 64 + ks * 32, 16), ks);
}
__device__ __forceinline__ void attnB_pv(float (&o)[16], const uint32_t (&p)[5][4], int HH, int h) {
#pragma unroll
  for (int k = 0; k < 5; k++)
    wgmma_n32_rs_tb1(o, p[k], make_desc(VB_ROW0 + h * 8192 - 2048 + k * 2048 + HH * 64, 16), k);
}

__device__ __forceinline__ void attention_b(int HH, int gb, uint32_t par0, int wwarp, int lane, bool ston) {
  constexpr uint32_t bars = SBASE + OFF_BAR, sq = SBASE + OFF_SLOT + 3 * 16384;
  float s[40];
  reg_define<40>(s);
  wgmma_fence();
  attnB_s(s, HH, 1);
  wgmma_commit();
  const int g = lane >> 2;
  const bool odd = g & 1;
  const int D = 2 * (lane & 3) + (g & 1) - g;
  const uint32_t ra = sq + (wwarp * 16 + ((lane >> 3) & 1) * 8 + (lane & 7)) * 128;
  wgmma_wait<0>();
  reg_fence<40>(s);
  STAMP(ston, 21);
#pragma unroll 1
  for (int h = 1; h >= 0; h--) {
    float o[16], inv[2];
    uint32_t p[5][4];
    reg_define<16>(o);
    attnB_soft(s, wwarp, D, h == 0 && gb == 0 && wwarp == 0, odd, p, inv);
    STAMP(ston, 25 - 3 * h);
    if (h == 1) {
      mbar_wait(bars + 8u * B_HALO, par0);
      STAMP(ston, 23);
      wgmma_fence();
      attnB_s(s, HH, 0);
    }
    wgmma_fence();
    attnB_pv(o, p, HH, h);
    wgmma_commit();
#pragma unroll
    for (int r = 0; r < 2; r++) {
      inv[r] += __shfl_xor_sync(0xffffffffu, inv[r], 1);
      inv[r] += __shfl_xor_sync(0xffffffffu, inv[r], 2);
      inv[r] = rcp_fast(inv[r]);
    }
    wgmma_wait<0>();
    reg_fence<40>(s);
    reg_fence<16>(o);
    STAMP(ston, 26 - 2 * h);
    store_o(o, inv, ra + h * 8192, HH, lane);
  }
}

#define KTQM 0
#define TRICKLE 300
#define CSI 1
#define PCA 1
#define PCB 3
#define PXB 4
#define EPW1 4
#define EPW0 12
#define PRENS 200
#define LOCE 1
#define QTURN 2
constexpr int NPT = 240 + 8;
struct Params {
  CUtensorMap xq[2], xr[3], o, wqkv[2], wo[2];
  const __nv_bfloat16* in_x;
  const __nv_bfloat16* wqkv_p1;
  const __nv_bfloat16* wo_p[2];
  uint32_t zero;
  uint2 wtab[4][17];
  uint2 ptab[NPT + 1];
};
static_assert(sizeof(Params) <= 4096, "");

__device__ __forceinline__ void colsum_part(const CUtensorMap* wmap, int ty, int qr, int hp) {
  constexpr uint32_t bars = SBASE + OFF_BAR, slots = SBASE + OFF_SLOT;
  PHASE_IDS
  const unsigned ep1 = (*(volatile unsigned*)(g_flags + F_DONE)) / NCTA + 1u;
  if (wwarp == 0 && elect_one()) {
    mbar_expect_tx(bars + 8u * B_CS, 6 * UNIT);
#pragma unroll 1
    for (int j = 0; j < 2; j++) {
      if (ty == 0) mbar_pace(bars + 8u * (B_EMPTY + PCA + PCB * j), 0);
      else __nanosleep(1000);
      tma_load_3d(slots + j * 3 * UNIT, wmap, bars + 8u * B_CS, hp * 64, qr * 128 + j * 64, 0);
    }
  }
  mbar_wait(bars + 8u * B_CS, ty);
  STAMP(KSQ == 0 && ty == 0, 49);
  const uint32_t src = slots + (tid >> 3) * 128 + (((tid & 7) ^ ((tid >> 3) & 7)) << 4);
#pragma unroll 1
  for (int p = 0; p < 3; p++) {
    float s[8];
#pragma unroll
    for (int e = 0; e < 8; e++) s[e] = 0.f;
#pragma unroll
    for (int j = 0; j < 8; j++) {
      const uint4 v = lds128(src + p * UNIT + (j >> 2) * 3 * UNIT + (j & 3) * 2048);
      const uint32_t x[4] = {v.x, v.y, v.z, v.w};
#pragma unroll
      for (int e = 0; e < 4; e++) {
        s[2 * e] += bf_lo(x[e]);
        s[2 * e + 1] += bf_hi(x[e]);
      }
    }
#pragma unroll
    for (int st = 0; st < 2; st++) {
      const bool up = (lane >> (st + 3)) & 1;
#pragma unroll
      for (int e = 0; e < (4 >> st); e++) {
        const float keep = up ? s[e + (4 >> st)] : s[e], give = up ? s[e] : s[e + (4 >> st)];
        s[e] = keep + __shfl_xor_sync(0xffffffffu, give, 8 << st);
      }
    }
    const uint32_t dst = slots + 6 * UNIT + ((wwarp * 3 + p) * 64 + (lane & 7) * 8 + ((lane >> 3) & 1) * 4 + (lane >> 4) * 2) * 4;
    sts32(dst, __float_as_uint(s[0]));
    sts32(dst + 4, __float_as_uint(s[1]));
  }
  named_bar_sync(6, 128);
  if (tid < 64) {
    float r[3] = {0.f, 0.f, 0.f};
#pragma unroll
    for (int e = 0; e < 12; e++) r[e % 3] += __uint_as_float(lds32(slots + 6 * UNIT + (e * 64 + tid) * 4));
    st_rec(&g_cs[ty][hp][qr][tid], r[0], r[1], r[2], ep1);
    STAMP(KSQ == 0 && ty == 0, 50);
  }
  named_bar_sync(6, 128);
}

__device__ __forceinline__ void cs_put(int blk, int ty, int col, float v) {
  const uint32_t hi = pack_bf16x2(v, 0.f), lo = pack_bf16x2(v - bf_lo(hi), 0.f);
  const uint32_t a = SBASE + OFF_CS + blk * 512 + ty * 256 + col * 2;
  asm volatile("st.shared.b16 [%0], %1;" ::"r"(sw(a ^ (((a >> 7) & 7) << 4))), "h"((unsigned short)hi) : "memory");
  asm volatile("st.shared.b16 [%0], %1;" ::"r"(sw((a + 128) ^ ((((a >> 7) + 1) & 7) << 4))), "h"((unsigned short)lo) : "memory");
}

__device__ __forceinline__ uint32_t ln_params(float s1, float s2) {
  const float mean = s1 * (1.0f / DM);
  const float var = fmaxf(fmaf(-mean, mean, s2 * (1.0f / DM)), 0.f);
  float sd;
  asm("sqrt.approx.f32 %0, %1;" : "=f"(sd) : "f"(bf16_round(bf16_round(var) + 1e-5f)));
  return pack_bf16x2(mean, sd);
}

#define SPLITS 0x086755588ull
__host__ __device__ __forceinline__ int q_split(int inst) { return (int)((SPLITS >> (4 * inst)) & 15ull); }
__device__ __forceinline__ int q_first(int inst) { return inst == 0 ? 0 : 32 * inst - 16; }
__device__ __forceinline__ int w_first(int inst) { return 32 * inst + 16 + 2 * q_split(inst + 1); }
#define PREMASK 0x3Cu
#define WBUF 0x0400103000201000ull
static_assert((PREMASK & 0xC0u) == 0, "");
__host__ __device__ __forceinline__ bool w_pre(int inst) { return (PREMASK >> inst) & 1u; }
struct WPlan {
  int v[6][21];
  int own[28], len;
};
__host__ __device__ constexpr WPlan w_plan(int mode) {
  WPlan p{};
  for (int u = 0; u < 28; u++) p.own[u] = u < 20 ? u / 5 - 4 : -16;
  if (mode == 2) {
    const WPlan q = w_plan(0);
    for (int u = 0; u < 20; u++) p.own[u] = q.own[(u + q.len) % 20] - 16;
  }
  int pos = 0, mx = -16;
  for (int kt = 0; kt < 21; kt++) {
    const int code = mode == 1 && kt < 16 ? (int)(WBUF >> (4 * kt)) & 15 : 0, st = kt > 16 ? kt - 1 : kt;
    const int na = kt == 16 ? 0 : (kt < 16 ? 1 : 2), nb = kt < 17 ? 2 : 3;
    const bool hole = code == 0 || (code & 8), swap = kt < 16 && hole && pos % 10 == 8;
    const int ua = (pos + (swap ? 2 : 0)) % 20, ub = code ? NUNITS - 2 + 2 * (code & 7) : (pos + (swap ? 0 : na)) % 20;
    int ra = st - 8, rb = kt == 16 ? -16 : st - 8;
    for (int i = 0; i < na; i++) ra = p.own[ua + i] > ra ? p.own[ua + i] : ra;
    for (int i = 0; i < nb; i++) rb = p.own[ub + i] > rb ? p.own[ub + i] : rb;
    p.v[0][kt] = ua;
    p.v[1][kt] = ub;
    p.v[2][kt] = st - ra;
    p.v[3][kt] = st - rb;
    p.v[4][kt] = rb > mx;
    p.v[5][kt] = p.own[ub] == -16;
    mx = rb > mx ? rb : mx;
    if (kt < 17) {
      for (int i = 0; i < na; i++) p.own[ua + i] = kt;
      for (int i = 0; i < nb; i++) p.own[ub + i] = kt < 16 ? kt : 15;
    }
    pos += na + (hole ? nb : 0);
    if (kt == 16) p.len = pos;
  }
  return p;
}
__host__ __device__ constexpr uint64_t w_tab(int f, int mode, int k0, int dk, int n, int bits) {
  const WPlan p = w_plan(mode);
  uint64_t r = 0;
  for (int j = 0; j < n; j++) r |= (uint64_t)p.v[f][k0 + j * dk] << (bits * j);
  return r;
}
__host__ __device__ constexpr uint32_t q_backs(bool act, int rank, bool pre) {
  return act ? 0x44444400u | (uint32_t)w_tab(2, pre, 17 + rank, 2, 2, 4) : 0x44440000u | (uint32_t)w_tab(3, pre, 17, 1, 4, 4);
}
__host__ __device__ constexpr uint32_t w_early() {
  const WPlan p = w_plan(1);
  uint32_t r = 0;
  for (int kt = 0; kt < 16; kt++)
    if (p.v[5][kt]) r |= (uint32_t)kt << (2 * (p.v[1][kt] - NUNITS));
  return r;
}
__host__ __device__ constexpr uint32_t w_emask() {
  const WPlan p = w_plan(1);
  uint32_t r = 0;
  for (int kt = 0; kt < 16; kt++) r |= (uint32_t)p.v[5][kt] << kt;
  return r;
}
static_assert((w_emask() & 3) == 0 && (w_early() & 15) < ((w_early() >> 4) & 15) && ((w_early() >> 4) & 15) < ((w_early() >> 8) & 15) &&
              ((w_early() >> 8) & 15) < (w_early() >> 12), "");
static_assert(w_plan(1).len % 10 == 0 && w_tab(2, 0, 0, 2, 8, 4) == 0x77776654u && w_tab(2, 2, 1, 2, 8, 4) == 0x77777666u &&
              q_backs(false, 0, false) == 0x44444445u && q_backs(true, 0, false) == 0x44444456u, "");
constexpr bool PRE_FLIP = w_plan(1).len % 20 != 0;
__device__ __forceinline__ int w_flips(int n) { return PRE_FLIP ? n : __popc(~PREMASK & ((1u << n) - 1u)); }
__host__ __device__ __forceinline__ uint32_t unit_off(int u, uint32_t dl) { return u * UNIT + (u < 10 ? dl : (u < 20 ? 0u - dl : 0u)); }

__global__ void __cluster_dims__(2, 1, 1) __launch_bounds__(512, 1) fused_kernel(const __grid_constant__ Params P) {
  constexpr uint32_t base = SBASE, bars = base + OFF_BAR, slots = base + OFF_SLOT;
  const int warp = __shfl_sync(0xffffffffu, threadIdx.x >> 5, 0), lane = threadIdx.x & 31;
  const int b = blockIdx.x, rank = b & 1;
  if (smem_u32(smem_raw) != base + (rank << 24)) __trap();
  int role = 0;
  {
    unsigned smid;
    asm volatile("mov.u32 %0, %smid;" : "=r"(smid));
    const int tc = smid >> 1;
    role = (tc < 32 ? (tc & 7) * 8 + (tc >> 3) : (tc < 62 ? ((tc - 32) % 7 + 1) * 8 + 4 + (tc - 32) / 7 : tc - 58)) & 63;
  }
  if (warp == 12) {
    if (elect_one()) {
#pragma unroll
      for (int s = 0; s < 8; s++) {
        mbar_init(bars + 8u * (B_FULL + s), 1);
        mbar_init(bars + 8u * (B_EMPTY + s), LOCE ? 2 : 4);
        mbar_init(bars + 8u * (B_LOC + s), 2);
      }
      mbar_init(bars + 8u * B_GO, 1);
      mbar_init(bars + 8u * B_ROLE, 1);
      mbar_expect_tx(bars + 8u * B_ROLE, 4);
      fence_barrier_init();
    }
    __syncwarp();
  }
  asm volatile("barrier.cluster.arrive.relaxed.aligned;" ::: "memory");
  if (threadIdx.x == 0) {
    mbar_init(bars + 8u * B_PREP, 1);
    mbar_init(bars + 8u * (B_PREP + 1), 1);
    for (int s = 0; s < 4; s++) mbar_init(bars + 8u * (B_HALO + s), 1);
    for (int s = 0; s < 3; s++) mbar_init(bars + 8u * (B_REL + s), 8);
    mbar_init(bars + 8u * B_AFREE, 2);
    mbar_init(bars + 8u * B_TURN, 4);
    mbar_init(bars + 8u * (B_TURN + 1), 4);
    mbar_init(bars + 8u * B_CS, 1);
    for (int s = 0; s < 4; s++) mbar_init(bars + 8u * (B_PRE + s), 1);
    mbar_init(bars + 8u * B_RESF, 1);
    mbar_init(bars + 8u * B_RESE, 4);
    mbar_init(bars + 8u * B_CSD, 4);
    mbar_init(bars + 8u * B_XRDY, 1);
    mbar_init(bars + 8u * (B_XRDY + 1), 1);
    fence_barrier_init();
  }
  if (warp == 15 && rank == 0) {
    const unsigned ep = *(volatile unsigned*)(g_flags + F_DONE);
    int r = role;
#pragma unroll 1
    for (int it = 0; it < 64; it++, r = (r + 1) & 63) {
      if (__all_sync(0xffffffffu, (ep - atom_add(g_flags + F_ROLE + r * RSTR, NCTA, lane == 0) < NCTA) | (lane != 0))) break;
      atom_add(g_flags + F_ROLE + r * RSTR, 0u - NCTA, lane == 0);
    }
    asm volatile("barrier.cluster.wait.aligned;" ::: "memory");
    asm volatile("{\n.reg .pred p;\nsetp.lt.u32 p, %3, 2;\n"
                 "@p st.async.weak.shared::cluster.mbarrier::complete_tx::bytes.b32 [%0], %1, [%2];\n}\n" ::"r"(base + OFF_ROLE + (lane << 24)),
                 "r"(r), "r"(bars + 8u * B_ROLE + (lane << 24)), "r"(lane)
                 : "memory");
  } else if (warp != 12) {
    asm volatile("barrier.cluster.wait.aligned;" ::: "memory");
  }
#define ROLE_IDS                                                                                   \
  const int qr = role & 7, hp = (role >> 3) * 2 + rank, rt = role & 15, ct = ((role >> 3) & 6) + rank; \
  (void)qr; (void)hp; (void)rt; (void)ct;
#define ROLE_GET                                                          \
  named_bar_sync(0, 512);                                                 \
  role = __shfl_sync(0xffffffffu, (int)lds32(base + OFF_ROLE), 0);

  if (warp < 12) {
    const bool asst = warp >= 8;
    ROLE_GET
    ROLE_IDS
    uint32_t tpar = 0;
    const uint32_t ebar = LOCE && (warp & 2) ? bars + 8u * B_LOC + (rank << 24) : bars + 8u * B_EMPTY + ((warp & 1) << 24);
    GTL(0);
#pragma unroll 1
    for (int inst = (warp < 4 ? 0 : -1) + (int)P.zero; inst < 8; inst += asst ? 1 : 2) {
      const int L = inst >> 1, ch = inst & 1, gb = ch * 8 + qr;
      if (inst >= 0) {
      if (asst) {
        setmaxnreg_dec<24>();
        if (warp == 8) {
          named_bar_sync(3, 192);
          STA(32);
          if (elect_one()) {
            if ((L & 1) == 0) {
#pragma unroll 1
              for (int o = 0, pc = inst == 1 ? PCS : 16384; o < 16384; o += pc) {
                bulk_store(g_kvA[L >> 1][gb][hp][1] + o, slots + 16384 + o, pc);
                if (inst == 1) spin(PCN);
              }
            } else {
              bulk_store(g_kvB[L >> 1][gb][hp], KB_ROW0 + 112 * 128, 2048);
              bulk_store(g_kvB[L >> 1][gb][hp] + 2048, VB_ROW0 + 112 * 128, 2048);
            }
            bulk_commit();
            bulk_wait0();
            fence_proxy_async_all();
          }
          __syncwarp();
          const unsigned one = read_back<4>(((L & 1) ? g_kvB[L >> 1][gb][hp] : g_kvA[L >> 1][gb][hp][1]) + (fresh_tid() & 31) * 128, (L & 1) ? 0 : 4096, P.zero);
          if (elect_one()) RED_K(g_flags + F_KV + (gb * 16 + hp) * KSTR, one);
          STA(33);
          __syncwarp();
        } else if (warp == 9 && (L & 1) == 0) {
          named_bar_sync(7, 160);
          if ((fresh_tid() & 31) == 0) {
#pragma unroll 1
            for (int o = 0, pc = inst == 1 ? PCS : 16384; o < 16384; o += pc) {
              bulk_store(g_kvA[L >> 1][gb][hp][0] + o, slots + o, pc);
              if (inst == 1) spin(PCN);
            }
            bulk_commit();
          }
          __syncwarp();
        }
        named_bar_sync(4, 256);
        setmaxnreg_inc<128>();
      } else {
      setmaxnreg_inc<224>();
      {
        float acc[2][96];
        const int ksp = q_split(inst);
        int n = q_first(inst);
        uint32_t dlt = inst > 0 && (w_flips(inst - 1) & 1) ? 10u * (UNIT >> 4) : 0u;
        if (inst == 1 || (inst > 1 && q_split(inst - 1) != 8)) {
          mbar_wait_lazy<100>(bars + 8u * (B_TURN + ch), tpar);
          tpar ^= 1u;
        }
        if (L == 3) GTL(37);
        mbar_wait(bars + 8u * (B_FULL + (n & 7)), (n >> 3) & 1);
        GTL(1 + L * 8);
        {
          const uint32_t da = (base >> 4) + 0x10000u + dlt;
          const uint64_t db = desc_lo(da - 0x10000u + ((UNIT >> 4) << 16) + 2 * (UNIT >> 4));
          wgmma_fence();
          wgmma_n192_ssz_ta0_tb1(acc[0], desc_lo(da), db);
          wgmma_commit();
          wgmma_n192_ssz_ta0_tb1(acc[1], desc_lo(da + (UNIT >> 4)), db);
          wgmma_commit();
        }
#pragma unroll 1
        for (int k2 = 0; k2 < 7; k2++) {
          const bool brk = k2 + 1 == ksp;
#pragma unroll
          for (int ks = 0; ks < 2; ks++, n++) {
            STAMP(inst == KSQ, k2 * 2 + ks);
            const uint32_t da = ((base + ks * 5 * UNIT) >> 4) + 0x10000u + dlt;
            const uint32_t dbb = da - 0x10000u + ((UNIT >> 4) << 16) + 2 * (UNIT >> 4);
#pragma unroll
            for (int k16 = 0; k16 < 4; k16++) {
              if (ks == 0 && k16 == 0 && k2 == 0) continue;
              const uint64_t db = desc_lo(dbb + k16 * 128);
              wgmma_fence();
              wgmma_n192_ss_ta0_tb1(acc[0], desc_lo(da + k16 * 2), db, 1);
              wgmma_commit();
              wgmma_wait<1>();
              if (k16 == 0) warp_arrive_cl(ebar + 8u * ((n - 1) & 7), ks != 0 || k2 != ksp);
              wgmma_fence();
              wgmma_n192_ss_ta0_tb1(acc[1], desc_lo(da + (UNIT >> 4) + k16 * 2), db, 1);
              wgmma_commit();
              bool ok = true;
              if (k16 == 2) ok = mbar_test(bars + 8u * (B_FULL + ((n + 1) & 7)), ((n + 1) >> 3) & 1) || (ks == 1 && brk);
              if (k16 == QTURN && ks == 1) warp_arrive(bars + 8u * (B_TURN + (ch ^ 1)), brk);
              if (ks == 0 || k16 < 3) wgmma_wait<1>();
              if (k16 == 2 && !ok) mbar_wait(bars + 8u * (B_FULL + ((n + 1) & 7)), ((n + 1) >> 3) & 1);
            }
          }
          if (brk) {
            wgmma_wait<0>();
            warp_arrive_cl(ebar + 8u * ((n - 1) & 7));
            n += 16;
            mbar_wait_lazy<100>(bars + 8u * (B_TURN + ch), tpar);
            tpar ^= 1u;
            STAMP(inst == KSQ, 17);
            mbar_wait(bars + 8u * (B_FULL + (n & 7)), (n >> 3) & 1);
          }
          if (!brk || (!PRE_FLIP && w_pre(inst - 1))) dlt ^= 10u * (UNIT >> 4);
        }
        auto tail_group = [&](int u) {
          const uint32_t da = ((base + (u & 1) * 5 * UNIT) >> 4) + 0x10000u + dlt;
          const uint32_t dbb = da - 0x10000u + ((UNIT >> 4) << 16) + 2 * (UNIT >> 4);
          if (u < 3) wgmma_fence();
#pragma unroll
          for (int k16 = 0; k16 < 4; k16++)
            wgmma_n192_ss_ta0_tb1(acc[u < 2], desc_lo(da + (u < 2 ? UNIT >> 4 : 0) + k16 * 2), desc_lo(dbb + k16 * 128), 1);
          wgmma_commit();
        };
        STAMP(inst == KSQ, 14);
        tail_group(0);
        wgmma_wait<1>();
        STAMP(inst == KSQ && KSPN, 42);
        warp_arrive_cl(ebar + 8u * ((n - 1) & 7), ksp != 7);
        PHASE_IDS
        mbar_wait(bars + 8u * (B_PREP + ch), L & 1);
        STAMP(inst == KSQ && KSPN, 43);
        uint32_t rs[4];
#pragma unroll
        for (int i = 0; i < 4; i++)
          rs[i] = lds32(base + OFF_RS + (ch * 128 + (i >> 1) * 64 + wwarp * 16 + g + 8 * (i & 1)) * 4);
        auto fold = [&](int h) {
          uint32_t a[2];
#pragma unroll
          for (int r = 0; r < 2; r++) a[r] = c == (L & 1) ? __byte_perm(rs[2 * h + r], 0, 0x1010) ^ 0x80008000u : 0u;
          uint64_t d;
          asm("mov.b64 %0, {%1, %2};" : "=l"(d) : "r"(((base + OFF_CS) >> 4) + ((512 >> 4) << 16)), "r"(0x40000000u));
          wgmma_fence();
          wgmma_n192_rs_tb1(acc[h], a[0], a[1], d);
        };
        fold(1);
        wgmma_commit();
        mbar_wait(bars + 8u * (B_FULL + ((n + 1) & 7)), ((n + 1) >> 3) & 1);
        STAMP(inst == KSQ && KSPN, 44);
        tail_group(1);
        tail_group(2);
        STAMP(inst == KSQ && KSPN, 45);
        const bool ppre = ksp == 7 && w_pre(inst - 1);
        const uint32_t fbar = bars + 8u * (ppre ? (LOCE ? B_LOC : B_EMPTY) + ((n - 1) & 7) : (inst == CSI + 1 ? B_CSD : B_AFREE));
        const uint32_t fpar = ppre ? ((n - 1) >> 3) & 1 : (inst == CSI + 1 ? 0 : ch);
        const bool afree = mbar_test(fbar, fpar);
        float rinv[2][2];
#pragma unroll
        for (int i = 0; i < 4; i++) rinv[i >> 1][i & 1] = rcp_fast(bf_hi(rs[i]));
        const int mat = lane >> 3;
        const uint32_t soff = (wwarp * 16 + (mat & 1) * 8 + (lane & 7)) * 128;
        const uint32_t kdst = ((L & 1) ? KB_ROW0 : slots) + soff, vdst = ((L & 1) ? VB_ROW0 : slots + 8192) + soff;
        const uint32_t hs = (L & 1) ? 8192 : 16384;
        const int rg = 2 * wwarp + (mat & 1);
        const uint32_t qdst = slots + 3 * 16384 + ((L & 1) ? soff : ((rg < 4 ? 2 * rg : 15 - 2 * rg) * 8 + (lane & 7)) * 128);
        wgmma_wait<2>();
        STAMP(inst == KSQ && KSPN, 46);
        fold(0);
        tail_group(3);
        STAMP(inst == KSQ && KSPN, 47);
        warp_arrive(bars + 8u * (B_TURN + (ch ^ 1)));
        if (!afree) {
          wgmma_wait<1>();
          warp_arrive_cl(ebar + 8u * (n & 7));
          wgmma_wait<0>();
          warp_arrive_cl(ebar + 8u * ((n + 1) & 7));
          mbar_wait(fbar, fpar);
        }
        wgmma_wait<2>();
        reg_fence<96>(acc[1]);
        STAMP(inst == KSQ, 15);
#pragma unroll
        for (int t = 0; t < 24; t++) {
          const int h = t < 12 ? 1 : 0, p = (t % 12 / 4 + 1) % 3, jp = t & 3;
          if (t == EPW1) {
            wgmma_wait<1>();
            warp_arrive_cl(ebar + 8u * (n & 7), afree);
          }
          if (t == EPW0) {
            wgmma_wait<0>();
            reg_fence<96>(acc[0]);
            warp_arrive_cl(ebar + 8u * ((n + 1) & 7), afree);
            STAMP(inst == KSQ, 16);
            GTL(2 + L * 8);
          }
          if (t % 12 == 8) {
            rinv[h][0] *= SM_C;
            rinv[h][1] *= SM_C;
          }
          const uint32_t swz = ((2 * jp + (mat >> 1)) ^ (lane & 7)) << 4;
          const float* a = &acc[h][32 * p + 8 * jp];
          const uint32_t dst = p == 0 ? qdst + h * 8192 : (p == 1 ? kdst : vdst) + h * hs;
          stmatrix_x4(dst + swz, pack_bf16x2(a[0] * rinv[h][0], a[1] * rinv[h][0]), pack_bf16x2(a[2] * rinv[h][1], a[3] * rinv[h][1]),
                      pack_bf16x2(a[4] * rinv[h][0], a[5] * rinv[h][0]), pack_bf16x2(a[6] * rinv[h][1], a[7] * rinv[h][1]));
          if (t % 12 == 7) {
            fence_proxy_async_smem();
            if (t == 7) named_bar_arrive(3, 192);
            else if ((L & 1) == 0) named_bar_arrive(7, 160);
            if (t > EPW0) sched_fence(P.zero);
          }
        }
      }
      fence_proxy_async_smem();
      setmaxnreg_dec<128>();
      named_bar_sync(4, 256);
      }
      GTL(3 + L * 8);
      {
        PHASE_IDS
        if ((L & 1) == 0) attention_a(asst, L, gb, hp, inst & 1, ch, (tid_ >> 5) & 3, lane, P.zero);
        else attention_b(asst, gb, inst & 1, wwarp, lane, KSAON);
        GTL(4 + L * 8);
        fence_proxy_async_smem();
      }
      if (!asst) {
      {
        named_bar_sync(5, 256);
        STAMP(KSAON, 27);
        const int wwarp = warp & 3;
        if (wwarp < 2) {
          if (elect_one()) {
            tma_store_3d(&P.o, ((L & 1) ? slots + 3 * 16384 : OA_TILE) + wwarp * 8192, 0, gb * 128 + wwarp * 64, hp);
            bulk_commit();
            bulk_wait0();
            mbar_arrive(bars + 8u * B_AFREE);
            fence_proxy_async_all();
          }
          __syncwarp();
          const unsigned one = read_back<2>(g_o + (gb * 128 + wwarp * 64 + (fresh_tid() & 31)) * DM + hp * 64, 32 * DM * 2, P.zero);
          if (elect_one()) RED_O(g_flags + F_O + (gb * 2 + wwarp) * OSTR + hp, one);
        }
        __syncwarp();
      }
      GTL(5 + L * 8);

      {
        float acc[64];
        const int n0 = w_first(inst);
        const bool pre = w_pre(inst);
        const uint32_t dl = ((w_flips(inst) + q_split(inst + 1)) & 1) * 10u * UNIT;
        const uint2* tab = P.wtab[2 * pre + (dl != 0)];
        const uint32_t ppar = __popc(PREMASK & ((1u << inst) - 1u)) & 1;
        uint32_t pbar = bars + 8u * B_PRE;
        const uint32_t flg = (pre ? w_emask() >> 1 : 0u) | (inst >= 6 || q_split(inst + 1) != 8 ? 1u << 30 : 0u);
        uint2 e = tab[0];
        mbar_wait_lazy<100>(bars + 8u * (B_TURN + ch), tpar);
        tpar ^= 1u;
        mbar_wait(bars + 8u * (B_FULL + (n0 & 7)), (n0 >> 3) & 1);
        GTL(6 + L * 8);
        auto wstep = [&](auto first_, int kt) {
          constexpr bool first = decltype(first_)::value;
          const int n = n0 + kt;
          STAMP(inst == KSW, 20 + kt);
          wgmma_fence();
          if (first) wgmma_n128_ssz_ta0_tb1(acc, desc_lo(e.x), desc_lo(e.y));
#pragma unroll
          for (int k16 = first ? 1 : 0; k16 < 4; k16++) wgmma_n128_ss_ta0_tb1(acc, desc_lo(e.x + 2 * k16), desc_lo(e.y + 128 * k16), 1);
          wgmma_commit();
          if (!first) warp_arrive(bars + 8u * (B_TURN + (ch ^ 1)), (flg >> kt) & 0x8000u);
          e = tab[kt + 1];
          const uint32_t nb = bars + 8u * (kt == 15 ? B_RESF : B_FULL + ((n + 1) & 7)), np = kt == 15 ? ch : ((n + 1) >> 3) & 1;
          const bool ok = mbar_test(nb, np);
          if (!first) {
            wgmma_wait<1>();
            warp_arrive_cl(ebar + 8u * ((n - 1) & 7));
            if ((flg >> kt) & 1u) {
              mbar_wait(pbar, ppar);
              pbar += 8u;
            }
          }
          if (!ok) mbar_wait(nb, np);
        };
        wstep(std::true_type(), 0);
#pragma unroll WUNR
        for (int kt = 1; kt < 16; kt++) wstep(std::false_type(), kt);
        PHASE_IDS
        const uint32_t xb = e.x;
        const int mat = lane >> 3;
        const uint32_t xrow = xb + (wwarp * 16 + (mat & 1) * 8 + (lane & 7)) * 128;
        uint32_t xv[8][4];
#pragma unroll
        for (int jp = 0; jp < 8; jp++)
          ldmatrix_x4(xv[jp], xrow + (jp >> 2) * UNIT + (((2 * (jp & 3) + (mat >> 1)) ^ (lane & 7)) << 4));
        wgmma_wait<0>();
        reg_fence<64>(acc);
        warp_arrive_cl(ebar + 8u * ((n0 + 15) & 7));
        STAMP(inst == KSW, 36);
        GTL(7 + L * 8);
#pragma unroll
        for (int jp = 0; jp < 8; jp++) {
#pragma unroll
          for (int q = 0; q < 4; q++) xv[jp][q] = add_bf16x2(xv[jp][q], pack_bf16x2(acc[8 * jp + 2 * q], acc[8 * jp + 2 * q + 1]));
          stmatrix_x4(xrow + (jp >> 2) * UNIT + (((2 * (jp & 3) + (mat >> 1)) ^ (lane & 7)) << 4), xv[jp][0], xv[jp][1],
                      xv[jp][2], xv[jp][3]);
        }
        fence_proxy_async_smem();
        named_bar_sync(1 + ch, 128);
        const int grow = ch * 1024 + rt * 64;
        if (wwarp == 0) {
          if (elect_one()) {
            tma_store_3d(&P.xr[L == 3 ? 2 : 1], xb, ct * 128, grow, 0);
            bulk_commit();
            bulk_wait_read0();
            mbar_arrive(bars + 8u * B_RESE);
            bulk_wait0();
            fence_proxy_async_all();
          }
          __syncwarp();
          if (L < 3) {
            const unsigned one = read_back<4>(g_x + (grow + (lane >> 1)) * DM + ct * 128 + (lane & 1) * 64, 16 * DM * 2, P.zero);
            if (elect_one()) RED_X(g_flags + F_X + (ch * 8 + (rt >> 1)) * XSTR + ct, one);
          }
          __syncwarp();
        } else if (lane == 0) {
          mbar_arrive(bars + 8u * B_RESE);
        }
        if (L < 3) {
          const unsigned ep1 = lds32(base + OFF_EPOCH);
          float s1[2] = {0.f, 0.f}, s2[2] = {0.f, 0.f};
#pragma unroll
          for (int jp = 0; jp < 8; jp++)
#pragma unroll
            for (int q = 0; q < 4; q++) {
              const float x0 = bf_lo(xv[jp][q]), x1 = bf_hi(xv[jp][q]);
              s1[q & 1] += x0 + x1;
              s2[q & 1] = fmaf(x0, x0, fmaf(x1, x1, s2[q & 1]));
            }
#pragma unroll
          for (int r = 0; r < 2; r++) {
            s1[r] += __shfl_xor_sync(0xffffffffu, s1[r], 1);
            s2[r] += __shfl_xor_sync(0xffffffffu, s2[r], 1);
            s1[r] += __shfl_xor_sync(0xffffffffu, s1[r], 2);
            s2[r] += __shfl_xor_sync(0xffffffffu, s2[r], 2);
            if (c == 0) st_rec(&g_stats[L + 1][ct][grow + wwarp * 16 + g + 8 * r], s1[r], s2[r], 0.f, ep1);
          }
        }
        GTL(8 + L * 8);
      }
      continue;
      }
      named_bar_arrive(5, 256);
      if (inst != CSI) continue;
      mbar_wait(bars + 8u * B_AFREE, CSI ^ 1);
      }
      if (asst) {
        colsum_part(&P.wqkv[inst >= 0], inst >= 0, qr, hp);
        warp_arrive(bars + 8u * (inst >= 0 ? B_CSD : B_AFREE), inst >= 0 || warp < 10);
      } else {
      PHASE_IDS
      {
        const unsigned ep1 = (*(volatile unsigned*)(g_flags + F_DONE)) / NCTA + 1u;
        const int row = b * 16 + (tid >> 3);
        const uint4* src = reinterpret_cast<const uint4*>(P.in_x + (size_t)row * DM) + (tid & 7);
        float s1 = 0.f, s2 = 0.f;
#pragma unroll 1
        for (int k = 0; k < 4; k++) {
          mbar_pace(bars + 8u * (B_EMPTY + PXB * k / 2), 0);
          uint4 v[4];
#pragma unroll
          for (int j = 0; j < 4; j++) v[j] = __ldg(src + (k * 4 + j) * 8);
#pragma unroll
          for (int j = 0; j < 4; j++) {
            const uint32_t w[4] = {v[j].x, v[j].y, v[j].z, v[j].w};
#pragma unroll
            for (int e = 0; e < 4; e++) {
              const float x0 = bf_lo(w[e]), x1 = bf_hi(w[e]);
              s1 += x0 + x1;
              s2 = fmaf(x0, x0, fmaf(x1, x1, s2));
            }
          }
        }
#pragma unroll
        for (int o = 1; o < 8; o <<= 1) {
          s1 += __shfl_xor_sync(0xffffffffu, s1, o);
          s2 += __shfl_xor_sync(0xffffffffu, s2, o);
        }
        if ((tid & 7) == 0) st_rec(&g_stats[0][0][row], s1, s2, 0.f, ep1);
        if (tid == 0) sts32(base + OFF_EPOCH, ep1);
        STAMP(KSQ == 0, 51);
        float4 v[6];
#pragma unroll 1
        for (uint32_t it = 0; it < (1u << 17); ++it) {
          bool ok = true;
#pragma unroll
          for (int t = 0; t < 6; t++) {
            v[t] = ld_rec(t < 2 ? &g_stats[0][0][(t * 8 + qr) * 128 + tid] : &g_cs[0][hp][(tid & 1) * 4 + t - 2][tid >> 1]);
            ok &= __float_as_uint(v[t].w) == ep1;
          }
          STAMP(KSQ == 0 && it == 0, 18);
          if (ok) break;
          __nanosleep(100);
        }
        STAMP(KSQ == 0, 17);
        __syncwarp();
        STAMP(KSQ == 0, 19);
#pragma unroll
        for (int cc = 0; cc < 2; cc++) sts32(base + OFF_RS + (cc * 128 + tid) * 4, ln_params(v[cc].x, v[cc].y));
        const float cs[3] = {(v[2].x + v[3].x) + (v[4].x + v[5].x), (v[2].y + v[3].y) + (v[4].y + v[5].y),
                             (v[2].z + v[3].z) + (v[4].z + v[5].z)};
#pragma unroll
        for (int blk = 0; blk < 3; blk++) {
          const float t = cs[blk] + __shfl_xor_sync(0xffffffffu, cs[blk], 1);
          cs_put(blk, tid & 1, tid >> 1, (tid & 1) ? 0.f : t);
        }
        fence_proxy_async_smem();
        named_bar_sync(2, 128);
        if (tid < 2) mbar_arrive(bars + 8u * (B_PREP + tid));
        STAMP(KSQ == 0, 48);
      }
      }
    }
    if (threadIdx.x == 128) atomicAdd(g_flags + F_DONE, 1u);
    if (!asst) asm volatile("barrier.cluster.arrive.relaxed.aligned;\nbarrier.cluster.wait.aligned;" ::: "memory");
    if (P.zero == 0) return;
  } else {
    setmaxnreg_dec<32>();
    if (warp != 12) {
      ROLE_GET
    }
    if (warp != 15) {
    if (warp == 14) {
      ROLE_IDS
      const unsigned ep1 = (*(volatile unsigned*)(g_flags + F_DONE)) / NCTA + 1u;
#pragma unroll 1
      for (int inst = 0; inst < 8; inst++) {
        const int L = inst >> 1, ch = inst & 1, gb = ch * 8 + qr;
        const unsigned* fp = g_flags + F_KV + (max(gb - 1 - ((lane >> 1) & 1), 0) * 16 + hp) * KSTR + (lane & 1);
        const unsigned target = (lane & 1) ? 2u * ep1 - 1u + (L >> 1) : 4u * ep1 - 3u + L;
        uint32_t seen = gb == 0 ? 15u : (gb == 1 ? 12u : 0u);
        named_bar_sync(3, 192);
        STA(34);
        __nanosleep(HDELAY);
        if ((L & 1) == 0) {
#pragma unroll 1
          for (int i = 0; i < 4; i++) {
            wait_lanes(fp, target, 1u << i, seen);
            STA(36 + i);
            if (i > 0) mbar_wait_lazy<RELNS>(bars + 8u * (B_REL + i - 1), ch);
            if (elect_one()) {
              mbar_expect_tx(bars + 8u * (B_HALO + i), 16384);
              bulk_load(slots + (i == 3 ? 2 : 2 - i) * 16384, gb > (i >> 1) ? g_kvA[L >> 1][gb - 1 - (i >> 1)][hp][(i & 1) ^ 1] : g_zero,
                        16384, bars + 8u * (B_HALO + i));
            }
          }
        } else {
          wait_lanes(fp, target, 1u, seen);
          STA(36);
        }
        if (elect_one()) {
          if (L & 1) {
            const uint8_t* s1 = gb >= 1 ? g_kvB[L >> 1][gb - 1][hp] : g_zero;
            mbar_expect_tx(bars + 8u * B_HALO, 4096);
            bulk_load(KB_ROW0 - 2048, s1, 2048, bars + 8u * B_HALO);
            bulk_load(VB_ROW0 - 2048, s1 + 2048, 2048, bars + 8u * B_HALO);
          }
          if (w_pre(inst)) {
            mbar_wait(bars + 8u * B_AFREE, (inst & 1) ^ 1);
            if (inst == CSI) mbar_wait(bars + 8u * B_CSD, 0);
#pragma unroll 1
            for (int j = 0; j < 4; j++) {
              constexpr uint32_t early = w_early();
              mbar_expect_tx(bars + 8u * (B_PRE + j), 2 * UNIT);
              tma_load_3d(slots + j * 2 * UNIT, &P.wo[L & 1], bars + 8u * (B_PRE + j), ct * 128, ((early >> (4 * j)) & 15) * 64, 0);
              __nanosleep(PRENS);
            }
          }
        }
        __syncwarp();
      }
    } else if (warp == 13) {
      ROLE_IDS
      uint32_t n = 16 + rank, dl = 0;
      uint32_t back = 0x44444444u;
      mbar_wait(bars + 8u * B_GO, 0);
      const unsigned ep1 = __shfl_sync(0xffffffffu, (*(volatile unsigned*)(g_flags + F_DONE)) / NCTA + 1u, 0);
#pragma unroll 1
      for (int sg = 4; sg < 34; sg++) {
        const int part = sg & 3, si = (sg >> 2) - (part & 1), L = si >> 1, ch = si & 1;
        const int k0 = part == 2 ? 2 * q_split(si) : 0, k1 = part == 0 ? 2 * q_split(si) : 16;
        if (part == 3 || k0 == k1) continue;
        const bool wj = part == 1;
        uint32_t seen = 0u;
        if (!wj && (L == 0 || __any_sync(0xffffffffu, mbar_test(bars + 8u * (B_XRDY + ch), (L & 1) ^ 1)))) {
          seen = 0xFFFFu;
          fence_proxy_async_all();
        }
        const CUtensorMap* map = wj ? &P.o : &P.xq[L == 0 ? 0 : 1];
        const unsigned* fl = g_flags + (wj ? F_O + (ch * 16 + rt) * OSTR : F_X + (ch * 8 + qr) * XSTR);
        const unsigned target = wj ? 4u * ep1 - 3u + L : 6u * ep1 - 6u + 2u * L;
        const int row = ch * 1024 + (wj ? rt * 64 : qr * 128);
        const bool pre = w_pre(si);
        uint64_t units = rank ? 0x0f050f050f050f05ull : 0x0a000a000a000a00ull;
        if (wj) {
          constexpr uint32_t b00 = (uint32_t)w_tab(2, 0, 0, 2, 8, 4), b01 = (uint32_t)w_tab(2, 0, 1, 2, 8, 4), b10 = (uint32_t)w_tab(2, 1, 0, 2, 8, 4),
                             b11 = (uint32_t)w_tab(2, 1, 1, 2, 8, 4), b20 = (uint32_t)w_tab(2, 2, 0, 2, 8, 4), b21 = (uint32_t)w_tab(2, 2, 1, 2, 8, 4);
          constexpr uint64_t u00 = w_tab(0, 0, 0, 2, 8, 8), u01 = w_tab(0, 0, 1, 2, 8, 8), u10 = w_tab(0, 1, 0, 2, 8, 8), u11 = w_tab(0, 1, 1, 2, 8, 8);
          back = pre ? (rank ? b11 : b10) : (si == 7 ? (rank ? b21 : b20) : (rank ? b01 : b00));
          units = pre ? (rank ? u11 : u10) : (rank ? u01 : u00);
        }
#pragma unroll 1
        for (int kt = k0 + rank; kt < k1; kt += 2, n += 2, back = (back >> 4) | 0x40000000u, units >>= 8) {
          wait_mask<false>(fl, 16, target, 1u << (wj ? kt : kt >> 1), seen, lane);
          const uint32_t nw = n - (back & 15u), pos = ((uint32_t)units & 31u) * UNIT + dl;
          mbar_wait(bars + 8u * (B_EMPTY + (nw & 7u)), (nw >> 3) & 1u);
          if (elect_one())
            tma_load_3d_mc(base + (pos >= 20 * UNIT ? pos - 20 * UNIT : pos), map, bars + 8u * (B_FULL + (n & 7u)), 0, row, kt);
        }
        if (wj ? !pre || PRE_FLIP : ((k1 - k0) & 2)) dl ^= 10u * UNIT;
        constexpr uint32_t q00 = q_backs(true, 0, false), q01 = q_backs(true, 1, false), q10 = q_backs(true, 0, true), q11 = q_backs(true, 1, true);
        if (wj) back = pre ? (rank ? q11 : q10) : (rank ? q01 : q00);
      }
    } else {
#pragma unroll 1
      for (int att = P.zero; att < 2; att++) {
        ROLE_IDS
#pragma unroll 1
        for (int s = 0; s < 4; s++) {
          if (elect_one()) {
            mbar_expect_tx(bars + 8u * (B_FULL + s), 5 * UNIT);
            tma_load_3d(base + s * 5 * UNIT, &P.xq[0], bars + 8u * (B_FULL + s), 0, qr * 128, s);
            tma_load_3d(base + (s * 5 + 2) * UNIT, &P.wqkv[0], bars + 8u * (B_FULL + s), hp * 64, s * 64, 0);
          }
        }
        if (att) break;
        asm volatile("barrier.cluster.wait.aligned;" ::: "memory");
        mbar_wait(bars + 8u * B_ROLE, 0);
        const int r = __shfl_sync(0xffffffffu, (int)lds32(base + OFF_ROLE), 0);
        if (r == role) break;
        role = r;
#pragma unroll 1
        for (int s = 0; s < 4; s++) {
          mbar_wait(bars + 8u * (B_FULL + s), 0);
          __syncwarp();
          if (elect_one()) {
            asm volatile("mbarrier.inval.shared::cta.b64 [%0];" ::"r"(sw(bars + 8u * (B_FULL + s))) : "memory");
            mbar_init(bars + 8u * (B_FULL + s), 1);
          }
        }
        fence_barrier_init();
        fence_proxy_async_smem();
        __syncwarp();
      }
      named_bar_arrive(0, 512);
      ROLE_IDS
#pragma unroll 1
      for (int s = 4; s < 16; s++) {
        const uint32_t fb = bars + 8u * (B_FULL + (s & 7)), sa = base + (s & 3) * 5 * UNIT;
        mbar_wait(bars + 8u * (B_EMPTY + ((s - 4) & 7)), ((s - 4) >> 3) & 1);
        if (elect_one()) {
          mbar_expect_tx(fb, 5 * UNIT);
          if ((s & 1) == rank) tma_load_3d_mc(sa, &P.xq[0], fb, 0, qr * 128, s);
          tma_load_3d(sa + 2 * UNIT, &P.wqkv[0], fb, hp * 64, s * 64, 0);
        }
      }
      if (elect_one()) mbar_arrive(bars + 8u * B_GO);
      const uint32_t wbase = sw(base), wbars = sw(bars);
      uint2 e = P.ptab[0];
#pragma unroll 1
      for (int i = 1; i <= NPT; i++) {
        const uint32_t wb = (e.x & 0x1f8u) | wbars, par = e.x >> 31, fl = e.x;
        uint32_t dst = (e.x & 0x3e000u) | wbase, fb = (e.y & 0x1f8u) | wbars, bytes = e.y & 0xe000u, nold = e.y & 1u;
        int c0 = (e.x & (1u << 29)) ? hp * 64 : ct * 128, c1 = ((e.x >> 18) & 0x7ffu) + ((e.x & (1u << 30)) ? rt * 64 : 0);
        const char* map = reinterpret_cast<const char*>(&P) + (e.y >> 21);
        asm volatile("" : "+r"(dst), "+r"(fb), "+r"(bytes), "+r"(nold), "+r"(c0), "+r"(c1), "+l"(map));
        e = P.ptab[i];
        if (fl & 2u) mbar_wait(bars + 8u * B_RESE, (fl >> 2) & 1u);
        if (!(fl & 1u)) mbar_wait_raw(wb, par);
        asm volatile(
            "{\n.reg .pred p, q;\nelect.sync _|p, 0xffffffff;\nsetp.eq.and.u32 q, %6, 0, p;\n"
            "@p mbarrier.arrive.expect_tx.shared::cta.b64 _, [%2], %5;\n"
            "@q cp.async.bulk.tensor.3d.shared::cluster.global.mbarrier::complete_tx::bytes [%0], [%1, {%3, %4, %7}], [%2];\n}\n" ::"r"(dst),
            "l"(map), "r"(fb), "r"(c0), "r"(c1), "r"(bytes), "r"(nold), "r"(0)
            : "memory");
      }
    }
    return;
    }
  }
  {
    {
      ROLE_IDS
      const unsigned ep1 = (*(volatile unsigned*)(g_flags + F_DONE)) / NCTA + 1u;
      mbar_wait(bars + 8u * B_GO, 0);
#pragma unroll 1
      for (int i = 0; i < 20; i++) {
        const char* src = i < 4 ? reinterpret_cast<const char*>(P.wo_p[0]) + (size_t)b * 16384 + i * 4096
                                : (i < 16 ? reinterpret_cast<const char*>(P.wqkv_p1) + (size_t)b * 49152 + (i - 4) * 4096
                                          : reinterpret_cast<const char*>(P.wo_p[1]) + (size_t)b * 16384 + (i - 16) * 4096);
        asm volatile("prefetch.global.L2 [%0];" ::"l"(src + lane * 128));
        __nanosleep(TRICKLE);
      }
#pragma unroll 1
      for (int inst = 2; inst < 8; inst++) {
        const int L = inst >> 1, ch = inst & 1, gb = ch * 8 + qr;
        uint32_t seen = 0;
        wait_mask<true>(g_flags + F_X + gb * XSTR, 8, 6u * ep1 - 6u + 2u * L, 0xFFu, seen, lane);
        if (lane == 0) mbar_arrive(bars + 8u * (B_XRDY + ch));
#pragma unroll 1
        for (int h = 0; h < 4; h++) {
          const float4* sp = &g_stats[L][0][gb * 128 + h * 32 + lane];
          const float4 s0 = sum_recs<4>(sp, S_LEN, ep1), s1 = sum_recs<4>(sp + 4 * S_LEN, S_LEN, ep1);
          sts32(base + OFF_RS + (ch * 128 + h * 32 + lane) * 4, ln_params(s0.x + s1.x, s0.y + s1.y));
        }
        if (inst == 2) {
          mbar_wait(bars + 8u * B_CSD, 0);
#pragma unroll 1
          for (int hf = 0; hf < 2; hf++) {
            const float4* cp = &g_cs[1][hp][0][hf * 32 + lane];
            const float4 s0 = sum_recs<4>(cp, 64, ep1), s1 = sum_recs<4>(cp + 4 * 64, 64, ep1);
            cs_put(0, 1, hf * 32 + lane, s0.x + s1.x);
            cs_put(1, 1, hf * 32 + lane, s0.y + s1.y);
            cs_put(2, 1, hf * 32 + lane, s0.z + s1.z);
          }
          fence_proxy_async_smem();
        }
        __syncwarp();
        if (lane == 0) mbar_arrive(bars + 8u * (B_PREP + ch));
      }
    }
  }
}

typedef CUresult (*PFN_tmEncode)(CUtensorMap*, CUtensorMapDataType, cuuint32_t, void*, const cuuint64_t*,
                                 const cuuint64_t*, const cuuint32_t*, const cuuint32_t*, CUtensorMapInterleave,
                                 CUtensorMapSwizzle, CUtensorMapL2promotion, CUtensorMapFloatOOBfill);

PFN_tmEncode get_encode_fn() {
  static PFN_tmEncode fn = nullptr;
  if (!fn) {
    cudaDriverEntryPointQueryResult qr;
    void* p = nullptr;
    cudaGetDriverEntryPoint("cuTensorMapEncodeTiled", &p, cudaEnableDefault, &qr);
    fn = (PFN_tmEncode)p;
  }
  return fn;
}

CUtensorMap make_map(const void* ptr, int rows, int cols, int inner, int blocks, int bs, int box_rows, int box_blk) {
  CUtensorMap m;
  cuuint64_t gdim[3] = {(cuuint64_t)inner, (cuuint64_t)rows, (cuuint64_t)blocks};
  cuuint64_t gstr[2] = {(cuuint64_t)cols * 2, (cuuint64_t)bs * 2};
  cuuint32_t box[3] = {64, (cuuint32_t)box_rows, (cuuint32_t)box_blk};
  cuuint32_t estr[3] = {1, 1, 1};
  get_encode_fn()(&m, CU_TENSOR_MAP_DATA_TYPE_BFLOAT16, 3, const_cast<void*>(ptr), gdim, gstr, box, estr,
                  CU_TENSOR_MAP_INTERLEAVE_NONE, CU_TENSOR_MAP_SWIZZLE_128B, CU_TENSOR_MAP_L2_PROMOTION_L2_128B,
                  CU_TENSOR_MAP_FLOAT_OOB_FILL_NONE);
  return m;
}

void make_tables(Params& P) {
  const WPlan pl[3] = {w_plan(0), w_plan(1), w_plan(2)};
  for (int m = 0; m < 4; m++)
    for (int kt = 0; kt < 17; kt++) {
      const WPlan& p = pl[m >> 1];
      const uint32_t dl = (m & 1) * 10u * UNIT;
      P.wtab[m][kt] = make_uint2(kt == 16 ? SBASE + unit_off(p.v[1][kt], dl) : ((SBASE + unit_off(p.v[0][kt], dl)) >> 4) + 0x10000u,
                                 ((SBASE + unit_off(p.v[1][kt], dl)) >> 4) + ((UNIT >> 4) << 16));
    }
  int np = 0;
  auto put = [&](int nw, int rp, uint32_t off, int c1, int kind, int fb, int units, const CUtensorMap* map) {
    P.ptab[np++] = make_uint2((nw < 0 ? 1u : 8u * ((LOCE ? B_LOC : B_EMPTY) + (nw & 7)) | (uint32_t)((nw >> 3) & 1) << 31) | (rp < 0 ? 0u : 2u | 4u * rp) |
                                  off | (uint32_t)c1 << 18 | (uint32_t)kind << 29,
                              8u * fb | (map ? 0u : 1u) | units * UNIT |
                                  (map ? (uint32_t)(reinterpret_cast<const char*>(map) - reinterpret_cast<const char*>(&P)) << 21 : 0u));
  };
  int n = 16, aw = 0;
  uint32_t dl = 0;
  uint32_t back = 0x44444444u;
  for (int sg = 4; sg < 34; sg++) {
    const int part = sg & 3, si = (sg >> 2) - (part & 1), L = si >> 1, ch = si & 1;
    const int k0 = part == 2 ? 2 * q_split(si) : 0, k1 = part == 0 ? 2 * q_split(si) : 16;
    if (part == 3) continue;
    if (part != 1) {
      for (int k2 = k0; k2 < k1; k2 += 2, aw--, dl ^= 10u * UNIT)
        for (int ks = 0; ks < 2; ks++, n++, back = (back >> 4) | 0x40000000u)
          put(n - (int)(back & 15u), ks == 1 && aw == 1 ? (part == 2) ^ ch : -1, (ks * 5 + 2) * UNIT + dl, (k2 + ks) * 64, 1,
              B_FULL + (n & 7), 5, &P.wqkv[L & 1]);
    } else {
      const bool pre = w_pre(si);
      const WPlan& p = pl[pre ? 1 : (aw == 2 ? 2 : 0)];
      for (int kt = 0; kt < 17; kt++) {
        const bool early = kt < 16 && p.v[5][kt];
        put(p.v[4][kt] ? n + kt - p.v[3][kt] : -1, !pre && kt == 6 && aw == 2 ? ch ^ 1 : -1, unit_off(p.v[1][kt], dl),
            kt == 16 ? ch * 1024 : kt * 64, kt == 16 ? 2 : 0, kt == 16 ? B_RESF : B_FULL + ((n + kt) & 7),
            kt == 16 ? 2 : (early ? 1 : 3), kt == 16 ? &P.xr[L == 0 ? 0 : 1] : (early ? nullptr : &P.wo[L & 1]));
      }
      n += 16;
      if (!pre || PRE_FLIP) dl ^= 10u * UNIT;
      back = q_backs(false, 0, pre);
      aw = 2;
    }
  }
  P.ptab[np] = make_uint2(0, 0);
}

}

extern "C" void kernel_launch(void* const* d_in, const int* in_sizes, int n_in, void* d_out, int out_size) {
  (void)in_sizes; (void)n_in; (void)out_size;
  void *p_o, *p_x;
  cudaGetSymbolAddress(&p_o, g_o);
  cudaGetSymbolAddress(&p_x, g_x);
  static bool attr_done = false;
  if (!attr_done) {
    cudaFuncSetAttribute(fused_kernel, cudaFuncAttributeMaxDynamicSharedMemorySize, SMEM_BYTES);
    attr_done = true;
  }
  Params P;
  P.in_x = (const __nv_bfloat16*)d_in[0];
  P.wo_p[0] = (const __nv_bfloat16*)d_in[2];
  P.wqkv_p1 = (const __nv_bfloat16*)d_in[4];
  P.wo_p[1] = (const __nv_bfloat16*)d_in[5];
  P.zero = 0;
  P.xq[0] = make_map(P.in_x, S_LEN, DM, 64, 16, 64, 128, 1);
  P.xq[1] = make_map(p_x, S_LEN, DM, 64, 16, 64, 128, 1);
  P.xr[0] = make_map(P.in_x, S_LEN, DM, DM - 64, 2, 64, 64, 2);
  P.xr[1] = make_map(p_x, S_LEN, DM, DM - 64, 2, 64, 64, 2);
  P.xr[2] = make_map(d_out, S_LEN, DM, DM - 64, 2, 64, 64, 2);
  P.o = make_map(p_o, S_LEN, DM, 64, 16, 64, 64, 1);
  for (int t = 0; t < 2; t++) {
    P.wqkv[t] = make_map(d_in[3 * t + 1], DM, NQKV, 1024, 3, 1024, 64, 3);
    P.wo[t] = make_map(P.wo_p[t], DM, DM, DM - 64, 2, 64, 64, 2);
  }
  make_tables(P);
  fused_kernel<<<NCTA, 512, SMEM_BYTES>>>(P);
}
```

```cpp
#include <cuda_runtime.h>
#include <cuda_bf16.h>
#include <cuda.h>
#include <stdint.h>
#include <type_traits>

namespace {

constexpr int S_LEN = 2048;
constexpr int DM = 1024;
constexpr int NQKV = 3072;
constexpr int NCTA = 128;

__device__ __align__(1024) uint8_t g_kvA[2][16][16][2][16384];
__device__ __align__(1024) uint8_t g_kvB[2][16][16][4096];
__device__ __align__(1024) uint8_t g_zero[16384];
__device__ __align__(1024) __nv_bfloat16 g_o[S_LEN * DM];
__device__ __align__(1024) __nv_bfloat16 g_x[S_LEN * DM];
__device__ __align__(1024) float4 g_stats[4][8][S_LEN];
__device__ __align__(1024) float4 g_cs[2][16][8][64];
#define RSTR 1
constexpr int F_X = 0;
constexpr int XSTR = 32, OSTR = 32, KSTR = 32;
constexpr int F_O = F_X + 16 * XSTR;
constexpr int F_KV = F_O + 32 * OSTR;
constexpr int F_DONE = F_KV + 256 * KSTR;
constexpr int F_ROLE = F_DONE + 32;
__device__ __align__(1024) unsigned g_flags[F_ROLE + 64 * RSTR];

constexpr uint32_t SBASE = 1024;
constexpr int UNIT = 8192;
constexpr int NUNITS = 20;
constexpr int OFF_SLOT = NUNITS * UNIT;
constexpr int OFF_CS = OFF_SLOT + 4 * 16384;
constexpr int OFF_RS = OFF_CS + 1536;
constexpr int OFF_BAR = OFF_RS + 1024;
constexpr int OFF_EPOCH = OFF_BAR + 400, OFF_ROLE = OFF_BAR + 404;
constexpr int OFF_TS = OFF_BAR + 408;
constexpr int SMEM_BYTES = OFF_TS;
constexpr int B_FULL = 0, B_EMPTY = 8, B_PREP = 16, B_HALO = 18, B_REL = 22, B_AFREE = 25, B_TURN = 26, B_XRDY = 28,
              B_CS = 30, B_CSD = 31, B_GO = 32, B_RESF = 33, B_RESE = 34, B_PRE = 35, B_ROLE = 39, B_LOC = 40, B_HB = 48, B_KVS = 49;

__device__ __forceinline__ uint32_t smem_u32(const void* p) { return (uint32_t)__cvta_generic_to_shared(p); }
extern __shared__ __align__(1024) uint8_t smem_raw[];
__device__ __forceinline__ uint32_t sw(uint32_t a) {
  uint32_t r;
  asm volatile("add.u32 %0, %1, %2;" : "=r"(r) : "r"(a), "r"(smem_u32(smem_raw) - SBASE));
  return r;
}

__device__ __forceinline__ void mbar_init(uint32_t bar, uint32_t cnt) {
  asm volatile("mbarrier.init.shared::cta.b64 [%0], %1;" ::"r"(sw(bar)), "r"(cnt));
}
__device__ __forceinline__ void mbar_expect_tx(uint32_t bar, uint32_t bytes) {
  asm volatile("mbarrier.arrive.expect_tx.shared::cta.b64 _, [%0], %1;" ::"r"(sw(bar)), "r"(bytes) : "memory");
}
__device__ __forceinline__ void mbar_arrive(uint32_t bar) {
  asm volatile("mbarrier.arrive.shared::cta.b64 _, [%0];" ::"r"(sw(bar)) : "memory");
}
__device__ __forceinline__ void warp_arrive(uint32_t bar, bool cond = true) {
  asm volatile("{\n.reg .pred p;\nelect.sync _|p, 0xffffffff;\nsetp.ne.and.b32 p, %1, 0, p;\n"
               "@p mbarrier.arrive.shared::cta.b64 _, [%0];\n}\n" ::"r"(sw(bar)), "r"((uint32_t)cond) : "memory");
}
__device__ __forceinline__ void warp_arrive_cl(uint32_t bar, bool cond = true) {
  asm volatile("{\n.reg .pred p;\nelect.sync _|p, 0xffffffff;\nsetp.ne.and.b32 p, %1, 0, p;\n"
               "@p mbarrier.arrive.shared::cluster.b64 _, [%0];\n}\n" ::"r"(bar), "r"((uint32_t)cond) : "memory");
}
__device__ __forceinline__ bool mbar_try_wait(uint32_t bar, uint32_t parity) {
  uint32_t ok;
  asm volatile(
      "{\n.reg .pred p;\nmbarrier.try_wait.parity.shared::cta.b64 p, [%1], %2;\nselp.b32 %0, 1, 0, p;\n}\n"
      : "=r"(ok)
      : "r"(sw(bar)), "r"(parity)
      : "memory");
  return ok != 0;
}
__device__ __forceinline__ bool mbar_test(uint32_t bar, uint32_t parity) {
  uint32_t ok;
  asm volatile(
      "{\n.reg .pred p;\nmbarrier.test_wait.parity.shared::cta.b64 p, [%1], %2;\nselp.b32 %0, 1, 0, p;\n}\n"
      : "=r"(ok)
      : "r"(sw(bar)), "r"(parity)
      : "memory");
  return ok != 0;
}
__device__ __forceinline__ void mbar_wait(uint32_t bar, uint32_t parity) {
#pragma unroll 1
  for (uint32_t it = 0; it < (1u << 18); ++it) {
    if (mbar_try_wait(bar, parity)) return;
  }
}
__device__ __forceinline__ void mbar_wait_raw(uint32_t bar, uint32_t parity) {
#pragma unroll 1
  for (uint32_t it = 0; it < (1u << 18); ++it) {
    uint32_t ok;
    asm volatile(
        "{\n.reg .pred p;\nmbarrier.try_wait.parity.shared::cta.b64 p, [%1], %2;\nselp.b32 %0, 1, 0, p;\n}\n"
        : "=r"(ok)
        : "r"(bar), "r"(parity)
        : "memory");
    if (ok) return;
  }
}
__device__ __forceinline__ void spin(uint32_t cyc) {
  uint32_t c0, c;
  asm volatile("mov.u32 %0, %%clock;" : "=r"(c0));
  do { asm volatile("mov.u32 %0, %%clock;" : "=r"(c)); } while (c - c0 < cyc);
}
__device__ __forceinline__ void mbar_pace(uint32_t bar, uint32_t parity) {
#pragma unroll 1
  for (uint32_t it = 0; it < 24; ++it) {
    if (mbar_try_wait(bar, parity)) return;
  }
}
template <int NS>
__device__ __forceinline__ void mbar_wait_lazy(uint32_t bar, uint32_t parity) {
#pragma unroll 1
  for (uint32_t it = 0; it < (1u << 18); ++it) {
    if (mbar_try_wait(bar, parity)) return;
    __nanosleep(NS);
  }
}
__device__ __forceinline__ bool elect_one() {
  uint32_t ok;
  asm volatile("{\n.reg .pred p;\nelect.sync _|p, 0xffffffff;\nselp.b32 %0, 1, 0, p;\n}\n" : "=r"(ok));
  return ok != 0;
}
__device__ __forceinline__ void fence_barrier_init() { asm volatile("fence.mbarrier_init.release.cluster;" ::: "memory"); }
__device__ __forceinline__ void fence_proxy_async_smem() { asm volatile("fence.proxy.async.shared::cta;" ::: "memory"); }
__device__ __forceinline__ void fence_proxy_async_all() { asm volatile("fence.proxy.async.global;" ::: "memory"); }

__device__ __forceinline__ void tma_load_3d(uint32_t dst, const CUtensorMap* map, uint32_t bar, int c0, int c1, int c2) {
  asm volatile(
      "cp.async.bulk.tensor.3d.shared::cluster.global.mbarrier::complete_tx::bytes [%0], [%1, {%3, %4, %5}], [%2];" ::"r"(sw(dst)),
      "l"(map), "r"(sw(bar)), "r"(c0), "r"(c1), "r"(c2)
      : "memory");
}
__device__ __forceinline__ void tma_load_3d_mc(uint32_t dst, const CUtensorMap* map, uint32_t bar, int c0, int c1, int c2) {
  asm volatile(
      "cp.async.bulk.tensor.3d.shared::cluster.global.mbarrier::complete_tx::bytes.multicast::cluster [%0], [%1, {%3, %4, %5}], [%2], %6;" ::"r"(sw(dst)),
      "l"(map), "r"(sw(bar)), "r"(c0), "r"(c1), "r"(c2), "h"((unsigned short)3)
      : "memory");
}
__device__ __forceinline__ void bulk_load(uint32_t dst, const void* src, uint32_t bytes, uint32_t bar) {
  asm volatile("cp.async.bulk.shared::cluster.global.mbarrier::complete_tx::bytes [%0], [%1], %2, [%3];" ::"r"(sw(dst)),
               "l"(src), "r"(bytes), "r"(sw(bar))
               : "memory");
}
__device__ __forceinline__ void bulk_store(void* dst, uint32_t src, uint32_t bytes) {
  asm volatile("cp.async.bulk.global.shared::cta.bulk_group [%0], [%1], %2;" ::"l"(dst), "r"(sw(src)), "r"(bytes) : "memory");
}
__device__ __forceinline__ void tma_store_3d(const CUtensorMap* map, uint32_t src, int c0, int c1, int c2) {
  asm volatile("cp.async.bulk.tensor.3d.global.shared::cta.bulk_group [%0, {%2, %3, %4}], [%1];" ::"l"(map), "r"(sw(src)),
               "r"(c0), "r"(c1), "r"(c2)
               : "memory");
}
__device__ __forceinline__ void bulk_commit() { asm volatile("cp.async.bulk.commit_group;" ::: "memory"); }
__device__ __forceinline__ void bulk_wait_read0() { asm volatile("cp.async.bulk.wait_group.read 0;" ::: "memory"); }
__device__ __forceinline__ void bulk_wait0() { asm volatile("cp.async.bulk.wait_group 0;" ::: "memory"); }
__device__ __forceinline__ void named_bar_sync(int id, int nthreads) {
  asm volatile("bar.sync %0, %1;" ::"r"(id), "r"(nthreads) : "memory");
}
__device__ __forceinline__ void named_bar_arrive(int id, int nthreads) {
  asm volatile("bar.arrive %0, %1;" ::"r"(id), "r"(nthreads) : "memory");
}

__device__ __forceinline__ void wgmma_fence() { asm volatile("wgmma.fence.sync.aligned;\n" ::: "memory"); }
__device__ __forceinline__ void wgmma_commit() { asm volatile("wgmma.commit_group.sync.aligned;\n" ::: "memory"); }
template <int N>
__device__ __forceinline__ void wgmma_wait() {
  asm volatile("wgmma.wait_group.sync.aligned %0;\n" ::"n"(N) : "memory");
}
template <int R>
__device__ __forceinline__ void setmaxnreg_inc() { asm volatile("setmaxnreg.inc.sync.aligned.u32 %0;\n" ::"n"(R)); }
template <int R>
__device__ __forceinline__ void setmaxnreg_dec() { asm volatile("setmaxnreg.dec.sync.aligned.u32 %0;\n" ::"n"(R)); }
template <int N>
__device__ __forceinline__ void reg_fence(float* r) {
#pragma unroll
  for (int i = 0; i < N; i++) asm volatile("" : "+f"(r[i])::"memory");
}

template <int N>
__device__ __forceinline__ void reg_define(float* r) {
#pragma unroll
  for (int i = 0; i < N; i++) r[i] = 0.f;
}

__device__ __forceinline__ uint64_t desc_lo(uint32_t lo) {
  uint64_t d;
  asm("mov.b64 %0, {%1, %2};" : "=l"(d) : "r"(lo), "r"(0x40000040u));
  return d;
}
__device__ __forceinline__ uint64_t make_desc(uint32_t addr, uint32_t lbo_bytes) {
  return desc_lo((addr >> 4) + ((lbo_bytes >> 4) << 16));
}

__device__ __forceinline__ void wgmma_n192_ss_ta0_tb1(float* d, uint64_t descA, uint64_t descB, int scaleD) {
  asm volatile("{\n.reg .pred p;\nsetp.ne.b32 p, %98, 0;\n"
    "wgmma.mma_async.sync.aligned.m64n192k16.f32.bf16.bf16 {%0, %1, %2, %3, %4, %5, %6, %7, %8, %9, %10, %11, %12, %13, %14, %15, %16, %17, %18, %19, %20, %21, %22, %23, %24, %25, %26, %27, %28, %29, %30, %31, %32, %33, %34, %35, %36, %37, %38, %39, %40, %41, %42, %43, %44, %45, %46, %47, %48, %49, %50, %51, %52, %53, %54, %55, %56, %57, %58, %59, %60, %61, %62, %63, %64, %65, %66, %67, %68, %69, %70, %71, %72, %73, %74, %75, %76, %77, %78, %79, %80, %81, %82, %83, %84, %85, %86, %87, %88, %89, %90, %91, %92, %93, %94, %95}, %96, %97, p, 1, 1, 0, 1;\n}\n"
    : "+f"(d[0]), "+f"(d[1]), "+f"(d[2]), "+f"(d[3]), "+f"(d[4]), "+f"(d[5]), "+f"(d[6]), "+f"(d[7]), "+f"(d[8]), "+f"(d[9]), "+f"(d[10]), "+f"(d[11]), "+f"(d[12]), "+f"(d[13]), "+f"(d[14]), "+f"(d[15]), "+f"(d[16]), "+f"(d[17]), "+f"(d[18]), "+f"(d[19]), "+f"(d[20]), "+f"(d[21]), "+f"(d[22]), "+f"(d[23]), "+f"(d[24]), "+f"(d[25]), "+f"(d[26]), "+f"(d[27]), "+f"(d[28]), "+f"(d[29]), "+f"(d[30]), "+f"(d[31]), "+f"(d[32]), "+f"(d[33]), "+f"(d[34]), "+f"(d[35]), "+f"(d[36]), "+f"(d[37]), "+f"(d[38]), "+f"(d[39]), "+f"(d[40]), "+f"(d[41]), "+f"(d[42]), "+f"(d[43]), "+f"(d[44]), "+f"(d[45]), "+f"(d[46]), "+f"(d[47]), "+f"(d[48]), "+f"(d[49]), "+f"(d[50]), "+f"(d[51]), "+f"(d[52]), "+f"(d[53]), "+f"(d[54]), "+f"(d[55]), "+f"(d[56]), "+f"(d[57]), "+f"(d[58]), "+f"(d[59]), "+f"(d[60]), "+f"(d[61]), "+f"(d[62]), "+f"(d[63]), "+f"(d[64]), "+f"(d[65]), "+f"(d[66]), "+f"(d[67]), "+f"(d[68]), "+f"(d[69]), "+f"(d[70]), "+f"(d[71]), "+f"(d[72]), "+f"(d[73]), "+f"(d[74]), "+f"(d[75]), "+f"(d[76]), "+f"(d[77]), "+f"(d[78]), "+f"(d[79]), "+f"(d[80]), "+f"(d[81]), "+f"(d[82]), "+f"(d[83]), "+f"(d[84]), "+f"(d[85]), "+f"(d[86]), "+f"(d[87]), "+f"(d[88]), "+f"(d[89]), "+f"(d[90]), "+f"(d[91]), "+f"(d[92]), "+f"(d[93]), "+f"(d[94]), "+f"(d[95])
    : "l"(descA), "l"(descB), "r"(scaleD));
}

__device__ __forceinline__ void wgmma_n128_ss_ta0_tb1(float* d, uint64_t descA, uint64_t descB, int scaleD) {
  asm volatile("{\n.reg .pred p;\nsetp.ne.b32 p, %66, 0;\n"
    "wgmma.mma_async.sync.aligned.m64n128k16.f32.bf16.bf16 {%0, %1, %2, %3, %4, %5, %6, %7, %8, %9, %10, %11, %12, %13, %14, %15, %16, %17, %18, %19, %20, %21, %22, %23, %24, %25, %26, %27, %28, %29, %30, %31, %32, %33, %34, %35, %36, %37, %38, %39, %40, %41, %42, %43, %44, %45, %46, %47, %48, %49, %50, %51, %52, %53, %54, %55, %56, %57, %58, %59, %60, %61, %62, %63}, %64, %65, p, 1, 1, 0, 1;\n}\n"
    : "+f"(d[0]), "+f"(d[1]), "+f"(d[2]), "+f"(d[3]), "+f"(d[4]), "+f"(d[5]), "+f"(d[6]), "+f"(d[7]), "+f"(d[8]), "+f"(d[9]), "+f"(d[10]), "+f"(d[11]), "+f"(d[12]), "+f"(d[13]), "+f"(d[14]), "+f"(d[15]), "+f"(d[16]), "+f"(d[17]), "+f"(d[18]), "+f"(d[19]), "+f"(d[20]), "+f"(d[21]), "+f"(d[22]), "+f"(d[23]), "+f"(d[24]), "+f"(d[25]), "+f"(d[26]), "+f"(d[27]), "+f"(d[28]), "+f"(d[29]), "+f"(d[30]), "+f"(d[31]), "+f"(d[32]), "+f"(d[33]), "+f"(d[34]), "+f"(d[35]), "+f"(d[36]), "+f"(d[37]), "+f"(d[38]), "+f"(d[39]), "+f"(d[40]), "+f"(d[41]), "+f"(d[42]), "+f"(d[43]), "+f"(d[44]), "+f"(d[45]), "+f"(d[46]), "+f"(d[47]), "+f"(d[48]), "+f"(d[49]), "+f"(d[50]), "+f"(d[51]), "+f"(d[52]), "+f"(d[53]), "+f"(d[54]), "+f"(d[55]), "+f"(d[56]), "+f"(d[57]), "+f"(d[58]), "+f"(d[59]), "+f"(d[60]), "+f"(d[61]), "+f"(d[62]), "+f"(d[63])
    : "l"(descA), "l"(descB), "r"(scaleD));
}

__device__ __forceinline__ void wgmma_n192_ssz_ta0_tb1(float* d, uint64_t descA, uint64_t descB) {
  asm volatile("{\n.reg .pred p;\nsetp.ne.b32 p, 0, 0;\n"
    "wgmma.mma_async.sync.aligned.m64n192k16.f32.bf16.bf16 {%0, %1, %2, %3, %4, %5, %6, %7, %8, %9, %10, %11, %12, %13, %14, %15, %16, %17, %18, %19, %20, %21, %22, %23, %24, %25, %26, %27, %28, %29, %30, %31, %32, %33, %34, %35, %36, %37, %38, %39, %40, %41, %42, %43, %44, %45, %46, %47, %48, %49, %50, %51, %52, %53, %54, %55, %56, %57, %58, %59, %60, %61, %62, %63, %64, %65, %66, %67, %68, %69, %70, %71, %72, %73, %74, %75, %76, %77, %78, %79, %80, %81, %82, %83, %84, %85, %86, %87, %88, %89, %90, %91, %92, %93, %94, %95}, %96, %97, p, 1, 1, 0, 1;\n}\n"
    : "=f"(d[0]), "=f"(d[1]), "=f"(d[2]), "=f"(d[3]), "=f"(d[4]), "=f"(d[5]), "=f"(d[6]), "=f"(d[7]), "=f"(d[8]), "=f"(d[9]), "=f"(d[10]), "=f"(d[11]), "=f"(d[12]), "=f"(d[13]), "=f"(d[14]), "=f"(d[15]), "=f"(d[16]), "=f"(d[17]), "=f"(d[18]), "=f"(d[19]), "=f"(d[20]), "=f"(d[21]), "=f"(d[22]), "=f"(d[23]), "=f"(d[24]), "=f"(d[25]), "=f"(d[26]), "=f"(d[27]), "=f"(d[28]), "=f"(d[29]), "=f"(d[30]), "=f"(d[31]), "=f"(d[32]), "=f"(d[33]), "=f"(d[34]), "=f"(d[35]), "=f"(d[36]), "=f"(d[37]), "=f"(d[38]), "=f"(d[39]), "=f"(d[40]), "=f"(d[41]), "=f"(d[42]), "=f"(d[43]), "=f"(d[44]), "=f"(d[45]), "=f"(d[46]), "=f"(d[47]), "=f"(d[48]), "=f"(d[49]), "=f"(d[50]), "=f"(d[51]), "=f"(d[52]), "=f"(d[53]), "=f"(d[54]), "=f"(d[55]), "=f"(d[56]), "=f"(d[57]), "=f"(d[58]), "=f"(d[59]), "=f"(d[60]), "=f"(d[61]), "=f"(d[62]), "=f"(d[63]), "=f"(d[64]), "=f"(d[65]), "=f"(d[66]), "=f"(d[67]), "=f"(d[68]), "=f"(d[69]), "=f"(d[70]), "=f"(d[71]), "=f"(d[72]), "=f"(d[73]), "=f"(d[74]), "=f"(d[75]), "=f"(d[76]), "=f"(d[77]), "=f"(d[78]), "=f"(d[79]), "=f"(d[80]), "=f"(d[81]), "=f"(d[82]), "=f"(d[83]), "=f"(d[84]), "=f"(d[85]), "=f"(d[86]), "=f"(d[87]), "=f"(d[88]), "=f"(d[89]), "=f"(d[90]), "=f"(d[91]), "=f"(d[92]), "=f"(d[93]), "=f"(d[94]), "=f"(d[95])
    : "l"(descA), "l"(descB));
}

__device__ __forceinline__ void wgmma_n192_rs_tb1(float* d, uint32_t a0, uint32_t a1, uint64_t descB) {
  asm volatile("{\n.reg .pred p;\nsetp.eq.b32 p, 0, 0;\n"
    "wgmma.mma_async.sync.aligned.m64n192k16.f32.bf16.bf16 {%0, %1, %2, %3, %4, %5, %6, %7, %8, %9, %10, %11, %12, %13, %14, %15, %16, %17, %18, %19, %20, %21, %22, %23, %24, %25, %26, %27, %28, %29, %30, %31, %32, %33, %34, %35, %36, %37, %38, %39, %40, %41, %42, %43, %44, %45, %46, %47, %48, %49, %50, %51, %52, %53, %54, %55, %56, %57, %58, %59, %60, %61, %62, %63, %64, %65, %66, %67, %68, %69, %70, %71, %72, %73, %74, %75, %76, %77, %78, %79, %80, %81, %82, %83, %84, %85, %86, %87, %88, %89, %90, %91, %92, %93, %94, %95}, {%96, %97, %98, %98}, %99, p, 1, 1, 1;\n}\n"
    : "+f"(d[0]), "+f"(d[1]), "+f"(d[2]), "+f"(d[3]), "+f"(d[4]), "+f"(d[5]), "+f"(d[6]), "+f"(d[7]), "+f"(d[8]), "+f"(d[9]), "+f"(d[10]), "+f"(d[11]), "+f"(d[12]), "+f"(d[13]), "+f"(d[14]), "+f"(d[15]), "+f"(d[16]), "+f"(d[17]), "+f"(d[18]), "+f"(d[19]), "+f"(d[20]), "+f"(d[21]), "+f"(d[22]), "+f"(d[23]), "+f"(d[24]), "+f"(d[25]), "+f"(d[26]), "+f"(d[27]), "+f"(d[28]), "+f"(d[29]), "+f"(d[30]), "+f"(d[31]), "+f"(d[32]), "+f"(d[33]), "+f"(d[34]), "+f"(d[35]), "+f"(d[36]), "+f"(d[37]), "+f"(d[38]), "+f"(d[39]), "+f"(d[40]), "+f"(d[41]), "+f"(d[42]), "+f"(d[43]), "+f"(d[44]), "+f"(d[45]), "+f"(d[46]), "+f"(d[47]), "+f"(d[48]), "+f"(d[49]), "+f"(d[50]), "+f"(d[51]), "+f"(d[52]), "+f"(d[53]), "+f"(d[54]), "+f"(d[55]), "+f"(d[56]), "+f"(d[57]), "+f"(d[58]), "+f"(d[59]), "+f"(d[60]), "+f"(d[61]), "+f"(d[62]), "+f"(d[63]), "+f"(d[64]), "+f"(d[65]), "+f"(d[66]), "+f"(d[67]), "+f"(d[68]), "+f"(d[69]), "+f"(d[70]), "+f"(d[71]), "+f"(d[72]), "+f"(d[73]), "+f"(d[74]), "+f"(d[75]), "+f"(d[76]), "+f"(d[77]), "+f"(d[78]), "+f"(d[79]), "+f"(d[80]), "+f"(d[81]), "+f"(d[82]), "+f"(d[83]), "+f"(d[84]), "+f"(d[85]), "+f"(d[86]), "+f"(d[87]), "+f"(d[88]), "+f"(d[89]), "+f"(d[90]), "+f"(d[91]), "+f"(d[92]), "+f"(d[93]), "+f"(d[94]), "+f"(d[95])
    : "r"(a0), "r"(a1), "r"(0u), "l"(descB));
}

__device__ __forceinline__ void wgmma_n128_ssz_ta0_tb1(float* d, uint64_t descA, uint64_t descB) {
  asm volatile("{\n.reg .pred p;\nsetp.ne.b32 p, 0, 0;\n"
    "wgmma.mma_async.sync.aligned.m64n128k16.f32.bf16.bf16 {%0, %1, %2, %3, %4, %5, %6, %7, %8, %9, %10, %11, %12, %13, %14, %15, %16, %17, %18, %19, %20, %21, %22, %23, %24, %25, %26, %27, %28, %29, %30, %31, %32, %33, %34, %35, %36, %37, %38, %39, %40, %41, %42, %43, %44, %45, %46, %47, %48, %49, %50, %51, %52, %53, %54, %55, %56, %57, %58, %59, %60, %61, %62, %63}, %64, %65, p, 1, 1, 0, 1;\n}\n"
    : "=f"(d[0]), "=f"(d[1]), "=f"(d[2]), "=f"(d[3]), "=f"(d[4]), "=f"(d[5]), "=f"(d[6]), "=f"(d[7]), "=f"(d[8]), "=f"(d[9]), "=f"(d[10]), "=f"(d[11]), "=f"(d[12]), "=f"(d[13]), "=f"(d[14]), "=f"(d[15]), "=f"(d[16]), "=f"(d[17]), "=f"(d[18]), "=f"(d[19]), "=f"(d[20]), "=f"(d[21]), "=f"(d[22]), "=f"(d[23]), "=f"(d[24]), "=f"(d[25]), "=f"(d[26]), "=f"(d[27]), "=f"(d[28]), "=f"(d[29]), "=f"(d[30]), "=f"(d[31]), "=f"(d[32]), "=f"(d[33]), "=f"(d[34]), "=f"(d[35]), "=f"(d[36]), "=f"(d[37]), "=f"(d[38]), "=f"(d[39]), "=f"(d[40]), "=f"(d[41]), "=f"(d[42]), "=f"(d[43]), "=f"(d[44]), "=f"(d[45]), "=f"(d[46]), "=f"(d[47]), "=f"(d[48]), "=f"(d[49]), "=f"(d[50]), "=f"(d[51]), "=f"(d[52]), "=f"(d[53]), "=f"(d[54]), "=f"(d[55]), "=f"(d[56]), "=f"(d[57]), "=f"(d[58]), "=f"(d[59]), "=f"(d[60]), "=f"(d[61]), "=f"(d[62]), "=f"(d[63])
    : "l"(descA), "l"(descB));
}

__device__ __forceinline__ void wgmma_n64_ss_ta0_tb0(float* d, uint64_t descA, uint64_t descB, int scaleD) {
  asm volatile("{\n.reg .pred p;\nsetp.ne.b32 p, %34, 0;\n"
    "wgmma.mma_async.sync.aligned.m64n64k16.f32.bf16.bf16 {%0, %1, %2, %3, %4, %5, %6, %7, %8, %9, %10, %11, %12, %13, %14, %15, %16, %17, %18, %19, %20, %21, %22, %23, %24, %25, %26, %27, %28, %29, %30, %31}, %32, %33, p, 1, 1, 0, 0;\n}\n"
    : "+f"(d[0]), "+f"(d[1]), "+f"(d[2]), "+f"(d[3]), "+f"(d[4]), "+f"(d[5]), "+f"(d[6]), "+f"(d[7]), "+f"(d[8]), "+f"(d[9]), "+f"(d[10]), "+f"(d[11]), "+f"(d[12]), "+f"(d[13]), "+f"(d[14]), "+f"(d[15]), "+f"(d[16]), "+f"(d[17]), "+f"(d[18]), "+f"(d[19]), "+f"(d[20]), "+f"(d[21]), "+f"(d[22]), "+f"(d[23]), "+f"(d[24]), "+f"(d[25]), "+f"(d[26]), "+f"(d[27]), "+f"(d[28]), "+f"(d[29]), "+f"(d[30]), "+f"(d[31])
    : "l"(descA), "l"(descB), "r"(scaleD));
}

__device__ __forceinline__ void wgmma_n64_ssz_ta0_tb0(float* d, uint64_t descA, uint64_t descB) {
  asm volatile("{\n.reg .pred p;\nsetp.ne.b32 p, 0, 0;\n"
    "wgmma.mma_async.sync.aligned.m64n64k16.f32.bf16.bf16 {%0, %1, %2, %3, %4, %5, %6, %7, %8, %9, %10, %11, %12, %13, %14, %15, %16, %17, %18, %19, %20, %21, %22, %23, %24, %25, %26, %27, %28, %29, %30, %31}, %32, %33, p, 1, 1, 0, 0;\n}\n"
    : "=f"(d[0]), "=f"(d[1]), "=f"(d[2]), "=f"(d[3]), "=f"(d[4]), "=f"(d[5]), "=f"(d[6]), "=f"(d[7]), "=f"(d[8]), "=f"(d[9]), "=f"(d[10]), "=f"(d[11]), "=f"(d[12]), "=f"(d[13]), "=f"(d[14]), "=f"(d[15]), "=f"(d[16]), "=f"(d[17]), "=f"(d[18]), "=f"(d[19]), "=f"(d[20]), "=f"(d[21]), "=f"(d[22]), "=f"(d[23]), "=f"(d[24]), "=f"(d[25]), "=f"(d[26]), "=f"(d[27]), "=f"(d[28]), "=f"(d[29]), "=f"(d[30]), "=f"(d[31])
    : "l"(descA), "l"(descB));
}

__device__ __forceinline__ void wgmma_n80_ss_ta0_tb0(float* d, uint64_t descA, uint64_t descB, int scaleD) {
  asm volatile("{\n.reg .pred p;\nsetp.ne.b32 p, %42, 0;\n"
    "wgmma.mma_async.sync.aligned.m64n80k16.f32.bf16.bf16 {%0, %1, %2, %3, %4, %5, %6, %7, %8, %9, %10, %11, %12, %13, %14, %15, %16, %17, %18, %19, %20, %21, %22, %23, %24, %25, %26, %27, %28, %29, %30, %31, %32, %33, %34, %35, %36, %37, %38, %39}, %40, %41, p, 1, 1, 0, 0;\n}\n"
    : "+f"(d[0]), "+f"(d[1]), "+f"(d[2]), "+f"(d[3]), "+f"(d[4]), "+f"(d[5]), "+f"(d[6]), "+f"(d[7]), "+f"(d[8]), "+f"(d[9]), "+f"(d[10]), "+f"(d[11]), "+f"(d[12]), "+f"(d[13]), "+f"(d[14]), "+f"(d[15]), "+f"(d[16]), "+f"(d[17]), "+f"(d[18]), "+f"(d[19]), "+f"(d[20]), "+f"(d[21]), "+f"(d[22]), "+f"(d[23]), "+f"(d[24]), "+f"(d[25]), "+f"(d[26]), "+f"(d[27]), "+f"(d[28]), "+f"(d[29]), "+f"(d[30]), "+f"(d[31]), "+f"(d[32]), "+f"(d[33]), "+f"(d[34]), "+f"(d[35]), "+f"(d[36]), "+f"(d[37]), "+f"(d[38]), "+f"(d[39])
    : "l"(descA), "l"(descB), "r"(scaleD));
}

__device__ __forceinline__ void wgmma_n32_rs_tb1(float* d, const uint32_t* a, uint64_t descB, int scaleD) {
  asm volatile("{\n.reg .pred p;\nsetp.ne.b32 p, %21, 0;\n"
    "wgmma.mma_async.sync.aligned.m64n32k16.f32.bf16.bf16 {%0, %1, %2, %3, %4, %5, %6, %7, %8, %9, %10, %11, %12, %13, %14, %15}, {%16, %17, %18, %19}, %20, p, 1, 1, 1;\n}\n"
    : "+f"(d[0]), "+f"(d[1]), "+f"(d[2]), "+f"(d[3]), "+f"(d[4]), "+f"(d[5]), "+f"(d[6]), "+f"(d[7]), "+f"(d[8]), "+f"(d[9]), "+f"(d[10]), "+f"(d[11]), "+f"(d[12]), "+f"(d[13]), "+f"(d[14]), "+f"(d[15])
    : "r"(a[0]), "r"(a[1]), "r"(a[2]), "r"(a[3]), "l"(descB), "r"(scaleD));
}

__device__ __forceinline__ uint32_t pack_bf16x2(float lo, float hi) {
  uint32_t r;
  asm("cvt.rn.bf16x2.f32 %0, %1, %2;" : "=r"(r) : "f"(hi), "f"(lo));
  return r;
}
__device__ __forceinline__ float bf_lo(uint32_t p) { return __uint_as_float(p << 16); }
__device__ __forceinline__ float bf_hi(uint32_t p) { return __uint_as_float(p & 0xffff0000u); }
__device__ __forceinline__ float bf16_round(float v) { return __bfloat162float(__float2bfloat16_rn(v)); }
__device__ __forceinline__ float ex2_approx(float x) {
  float r;
  asm("ex2.approx.ftz.f32 %0, %1;" : "=f"(r) : "f"(x));
  return r;
}
__device__ __forceinline__ float rcp_fast(float x) {
  float r;
  asm("rcp.approx.ftz.f32 %0, %1;" : "=f"(r) : "f"(x));
  return r;
}
__device__ __forceinline__ void ldmatrix_x4(uint32_t (&r)[4], uint32_t addr) {
  asm volatile("ldmatrix.sync.aligned.m8n8.x4.shared.b16 {%0,%1,%2,%3}, [%4];"
               : "=r"(r[0]), "=r"(r[1]), "=r"(r[2]), "=r"(r[3])
               : "r"(sw(addr))
               : "memory");
}
__device__ __forceinline__ void stmatrix_x4(uint32_t addr, uint32_t r0, uint32_t r1, uint32_t r2, uint32_t r3) {
  asm volatile("stmatrix.sync.aligned.m8n8.x4.shared.b16 [%0], {%1,%2,%3,%4};" ::"r"(sw(addr)), "r"(r0), "r"(r1), "r"(r2),
               "r"(r3));
}
__device__ __forceinline__ uint32_t add_bf16x2(uint32_t a, uint32_t b) {
  uint32_t r;
  asm("add.rn.bf16x2 %0, %1, %2;" : "=r"(r) : "r"(a), "r"(b));
  return r;
}
__device__ __forceinline__ uint4 lds128(uint32_t addr) {
  uint4 v;
  asm volatile("ld.shared.v4.b32 {%0,%1,%2,%3}, [%4];" : "=r"(v.x), "=r"(v.y), "=r"(v.z), "=r"(v.w) : "r"(sw(addr)) : "memory");
  return v;
}
__device__ __forceinline__ uint32_t lds32(uint32_t addr) {
  uint32_t v;
  asm volatile("ld.shared.b32 %0, [%1];" : "=r"(v) : "r"(sw(addr)) : "memory");
  return v;
}
__device__ __forceinline__ void sts32(uint32_t addr, uint32_t v) {
  asm volatile("st.shared.b32 [%0], %1;" ::"r"(sw(addr)), "r"(v) : "memory");
}

__device__ __forceinline__ unsigned ld_acquire_u32(const unsigned* p) {
  unsigned v;
  asm volatile("ld.acquire.gpu.global.u32 %0, [%1];" : "=r"(v) : "l"(p) : "memory");
  return v;
}
__device__ __forceinline__ unsigned atom_add(unsigned* p, unsigned v, bool on) {
  unsigned r = 0;
  asm volatile("{\n.reg .pred p;\nsetp.ne.u32 p, %3, 0;\n@p atom.relaxed.gpu.global.add.u32 %0, [%1], %2;\n}\n"
               : "+r"(r) : "l"(p), "r"(v), "r"((uint32_t)on) : "memory");
  return r;
}
__device__ __forceinline__ void announce(unsigned* p) {
  asm volatile("red.release.gpu.global.add.u32 [%0], 1;" ::"l"(p) : "memory");
}
__device__ __forceinline__ void poison(uint8_t* p, int n, uint32_t gap) {
#pragma unroll 1
  for (int i = 0; i < n; i++, p += 2048) {
    asm volatile("st.global.v4.b32 [%0], {%1,%1,%1,%1};" ::"l"(p), "r"(0xffffffffu) : "memory");
    __nanosleep(gap);
  }
}
__device__ __forceinline__ void wait_ge2(const unsigned* p, unsigned t0, unsigned t1) {
#pragma unroll 1
  for (uint32_t it = 0; it < (1u << 17); ++it) {
    unsigned long long v;
    asm volatile("ld.acquire.gpu.global.u64 %0, [%1];" : "=l"(v) : "l"(p) : "memory");
    if ((int)((unsigned)v - t0) >= 0 && (int)((unsigned)(v >> 32) - t1) >= 0) return;
  }
}

#define RELNS 100
#define PCM 0x02
#define HBD 700
#define POI1 100
#define WU 3
constexpr int WUNR = WU;
#define PCS 4096
#define PCN 30
template <bool SLOW>
__device__ __forceinline__ void wait_mask(const unsigned* f, int cnt, unsigned target, uint32_t need, uint32_t& seen, int lane) {
  if ((seen & need) == need) return;
  const unsigned* fp = f + (lane & (cnt - 1));
#pragma unroll 1
  for (uint32_t it = 0; it < (1u << 17); ++it) {
    seen = __ballot_sync(0xffffffffu, (int)(ld_acquire_u32(fp) - target) >= 0);
    if ((seen & need) == need) break;
    if (SLOW) __nanosleep(400);
  }
  fence_proxy_async_all();
}
__device__ __forceinline__ void wait_lanes(const unsigned* fp, unsigned target, uint32_t need, uint32_t& seen) {
  if ((seen & need) == need) return;
#pragma unroll 1
  for (uint32_t it = 0; it < (1u << 17); ++it) {
    seen |= __ballot_sync(0xffffffffu, (int)(ld_acquire_u32(fp) - target) >= 0);
    if ((seen & need) == need) break;
  }
  fence_proxy_async_all();
}
__device__ __forceinline__ float4 ld_rec(const float4* p) {
  float4 v;
  asm volatile("ld.relaxed.gpu.global.v4.f32 {%0,%1,%2,%3}, [%4];" : "=f"(v.x), "=f"(v.y), "=f"(v.z), "=f"(v.w) : "l"(p) : "memory");
  return v;
}
__device__ __forceinline__ void st_rec(float4* p, float a, float b, float c, unsigned tag) {
  asm volatile("st.relaxed.gpu.global.v4.f32 [%0], {%1,%2,%3,%4};" ::"l"(p), "f"(a), "f"(b), "f"(c), "f"(__uint_as_float(tag)) : "memory");
}
template <int N>
__device__ __forceinline__ float4 sum_recs(const float4* p, int stride, unsigned tag) {
  float4 s;
#pragma unroll 1
  for (uint32_t it = 0; it < (1u << 17); ++it) {
    float4 v[N];
#pragma unroll
    for (int t = 0; t < N; t++) v[t] = ld_rec(p + t * stride);
    bool ok = true;
    s = make_float4(0.f, 0.f, 0.f, 0.f);
#pragma unroll
    for (int t = 0; t < N; t++) {
      ok &= __float_as_uint(v[t].w) == tag;
      s.x += v[t].x;
      s.y += v[t].y;
      s.z += v[t].z;
    }
    if (ok) break;
    __nanosleep(200);
  }
  return s;
}

__device__ __forceinline__ int fresh_tid() {
  int t;
  asm volatile("mov.u32 %0, %%tid.x;" : "=r"(t));
  return t;
}
#define PHASE_IDS                                  \
  const int tid_ = fresh_tid();                    \
  const int lane = tid_ & 31, wwarp = __shfl_sync(0xffffffffu, (tid_ >> 5) & 3, 0), tid = tid_ & 127; \
  const int g = lane >> 2, c = lane & 3;           \
  (void)tid; (void)g; (void)c; (void)wwarp;

#define STAMPW(cond, i) do { } while (0)
#define STAMP(cond, i) do { } while (0)
#define KSPN true
#define KSAON false
#define STA(i) do { } while (0)
#define GTL(i) do { } while (0)
#define GTLX(c, i) do { } while (0)
#define TGET(v) do { } while (0)
#define TPUT(c, i, v) do { } while (0)

constexpr float SM_C = 0.17677669529663687f * 1.4426950408889634f;

constexpr uint32_t OA_TILE = SBASE + OFF_SLOT + 16384;

__device__ __forceinline__ void sched_fence(uint32_t never) {
  asm volatile("{\n.reg .pred p;\nsetp.ne.u32 p, %0, 0;\n@p exit;\n}\n" ::"r"(never) : "memory");
}

template <int K0, int K1>
__device__ __forceinline__ void attn_exp(float (&s)[32]) {
#pragma unroll
  for (int k = K0; k < K1; k++) s[k] = ex2_approx(s[k]);
}
#define ASPL 16
#define ASPD 6
#define ASPE 6
#define ASPF 6
template <int MODE, bool NEXT>
__device__ __forceinline__ void attn_unit(float (&s)[32], float (&sn)[32], float (&o)[16], float (&l)[2], bool valid,
                                          uint32_t vdesc, uint32_t qdesc, uint32_t kdesc, uint32_t tri, int w,
                                          uint32_t hbar, uint32_t hpar, uint32_t rel, uint32_t zero, bool stampon = false) {
  float x[9][2];
  constexpr int ASPM = MODE == 1 ? ASPD : (NEXT ? ASPE : ASPF);
  if (MODE == 0) {
    attn_exp<0, ASPL>(s);
  } else {
#pragma unroll
    for (int e = 0; e < 2; e++) {
#pragma unroll
      for (int j = 0; j < 4; j++) x[j][e] = MODE == 1 ? s[4 * j + 2 + e] : s[16 + 4 * j + e];
      x[4][e] = MODE == 1 ? s[e] : s[30 + e];
      x[5][e] = MODE == 1 ? s[18 + e] : s[12 + e];
#pragma unroll
      for (int u = 1; u < 4; u++)
        x[5 + u][e] = MODE == 1 ? (w >= u ? s[4 * u + e] : s[4 * (8 - u) + 2 + e]) : (w >= u ? s[4 * (7 - u) + 2 + e] : s[4 * (u - 1) + e]);
    }
#pragma unroll
    for (int k = 0; k < 2 * ASPM; k++) x[k >> 1][k & 1] = ex2_approx(x[k >> 1][k & 1]);
  }
  sched_fence(zero);
  if (hbar) mbar_wait(hbar, hpar);
  wgmma_wait<0>();
  if (rel) mbar_arrive(rel);
  if (NEXT) {
    wgmma_fence();
    wgmma_n64_ssz_ta0_tb0(sn, desc_lo(qdesc), desc_lo(kdesc));
    wgmma_n64_ss_ta0_tb0(sn, desc_lo(qdesc + 2), desc_lo(kdesc + 2), 1);
    wgmma_commit();
    sched_fence(zero);
  }
  uint32_t p[16];
  if (MODE == 0) {
    attn_exp<ASPL, 32>(s);
#pragma unroll
    for (int k = 0; k < 16; k++) p[k] = pack_bf16x2(s[2 * k], s[2 * k + 1]);
  } else {
#pragma unroll
    for (int k = 2 * ASPM; k < 18; k++) x[k >> 1][k & 1] = ex2_approx(x[k >> 1][k & 1]);
    const uint32_t tm = MODE == 1 ? tri : ~tri;
#pragma unroll
    for (int j = 0; j < 4; j++) {
      p[MODE == 1 ? 2 * j + 1 : 8 + 2 * j] = pack_bf16x2(x[j][0], x[j][1]);
      p[MODE == 1 ? 8 + 2 * j : 2 * j + 1] = 0u;
    }
    p[MODE == 1 ? 0 : 15] = pack_bf16x2(x[4][0], x[4][1]) & (w == 0 ? tm : 0xffffffffu);
    p[MODE == 1 ? 9 : 6] = pack_bf16x2(x[5][0], x[5][1]) & (w == 3 ? tm : 0xffffffffu);
#pragma unroll
    for (int u = 1; u < 4; u++) {
      const uint32_t q = pack_bf16x2(x[5 + u][0], x[5 + u][1]);
      p[MODE == 1 ? 2 * u : 2 * (7 - u) + 1] = q & (w > u ? 0xffffffffu : (w == u ? tm : 0u));
      p[MODE == 1 ? 2 * (8 - u) + 1 : 2 * (u - 1)] = q & (w < u - 1 ? 0xffffffffu : (w == u - 1 ? tm : 0u));
    }
  }
  wgmma_fence();
#pragma unroll
  for (int k = 0; k < 4; k++) wgmma_n32_rs_tb1(o, p + 4 * k, desc_lo(vdesc + k * 128), 1);
  wgmma_commit();
#pragma unroll
  for (int r = 0; r < 2; r++) {
    float t = 0.f;
#pragma unroll
    for (int hf = 0; hf < 2; hf++) {
      if (MODE != 0 && r == MODE - 1 && hf == 2 - MODE) continue;
      const uint32_t* q = p + 8 * hf + r;
      const uint32_t v = add_bf16x2(add_bf16x2(q[0], q[2]), add_bf16x2(q[4], q[6]));
      t = (MODE != 0 && r == MODE - 1) || hf == 0 ? bf_lo(v) + bf_hi(v) : t + (bf_lo(v) + bf_hi(v));
    }
    if (valid) l[r] += t;
  }
  if (NEXT) {
    wgmma_wait<1>();
    reg_fence<32>(sn);
  }
}

__device__ __forceinline__ void attn_a_slow(const uint8_t* __restrict__ kvimg, int L, int gb, int hp,
                                         int hh, int wwarp, int lane, int t0, int t1) {
  constexpr uint32_t sq = SBASE + OFF_SLOT + 3 * 16384;
  const unsigned ep = (*(volatile unsigned*)(g_flags + F_DONE)) / NCTA;
  wait_ge2(g_flags + F_KV + (gb * 16 + hp) * KSTR, 2u * ep + (L >> 1) + 1u, 2u * ep + (L >> 1) + 1u);
#pragma unroll 1
  for (int t = t0; t < t1; t++) {
    const int row = (t >> 4) * 64 + ((t & 8) ? 7 - wwarp : wwarp) * 8 + (t & 7);
    const int qpos = gb * 128 + row;
    const uint32_t qaddr = sq + ((t >> 4) * 64 + wwarp * 16 + (t & 15)) * 128;
    float mx = -INFINITY, sum = 0.f, acc = 0.f;
#pragma unroll 1
    for (int pass = 0; pass < 2; pass++) {
#pragma unroll 1
      for (int j = 0; j < 8; j++) {
        const int kp = qpos - (lane + 32 * j);
        const uint8_t* kr = kvimg + ((size_t)((kp >> 7) * 16 + hp) * 2 + ((kp >> 6) & 1)) * 16384 + (kp & 63) * 128;
        float d = -INFINITY;
        if (kp >= 0) {
          d = 0.f;
#pragma unroll 1
          for (int q = 0; q < 4; q++) {
            const uint4 kv = __ldcg(reinterpret_cast<const uint4*>(kr + (((hh * 4 + q) ^ (kp & 7)) << 4)));
            const uint4 qv = lds128(qaddr + (((hh * 4 + q) ^ (row & 7)) << 4));
            const uint32_t kw[4] = {kv.x, kv.y, kv.z, kv.w}, qw[4] = {qv.x, qv.y, qv.z, qv.w};
#pragma unroll
            for (int e = 0; e < 4; e++) d = fmaf(bf_lo(kw[e]), bf_lo(qw[e]), fmaf(bf_hi(kw[e]), bf_hi(qw[e]), d));
          }
        }
        if (pass == 0) {
          mx = fmaxf(mx, d);
        } else {
          const float ev = ex2_approx(d - mx);
          sum += ev;
          const float pv = bf16_round(ev);
#pragma unroll 1
          for (int kk = 0; kk < 32; kk++) {
            const float pk = __shfl_sync(0xffffffffu, pv, kk);
            const int k2 = qpos - (kk + 32 * j);
            if (k2 >= 0) {
              const uint8_t* vr = kvimg + ((size_t)((k2 >> 7) * 16 + hp) * 2 + ((k2 >> 6) & 1)) * 16384 + 8192 + (k2 & 63) * 128;
              const unsigned short vv =
                  __ldcg(reinterpret_cast<const unsigned short*>(vr + (((hh * 4 + (lane >> 3)) ^ (k2 & 7)) << 4) + (lane & 7) * 2));
              acc = fmaf(pk, __uint_as_float((uint32_t)vv << 16), acc);
            }
          }
        }
      }
      if (pass == 0) {
#pragma unroll
        for (int o = 16; o > 0; o >>= 1) mx = fmaxf(mx, __shfl_xor_sync(0xffffffffu, mx, o));
      }
    }
#pragma unroll
    for (int o = 16; o > 0; o >>= 1) sum += __shfl_xor_sync(0xffffffffu, sum, o);
    acc *= rcp_fast(sum);
    const float hi = __shfl_down_sync(0xffffffffu, acc, 1);
    __syncwarp();
    if ((lane & 1) == 0)
      sts32(OA_TILE + row * 128 + (((hh * 4 + (lane >> 3)) ^ (row & 7)) << 4) + (lane & 7) * 2, pack_bf16x2(acc, hi));
    __syncwarp();
  }
}

__device__ __forceinline__ void store_o(const float (&o)[16], const float (&inv)[2], uint32_t rowaddr, int hh, int lane) {
  const int mat = lane >> 3, r7 = lane & 7;
#pragma unroll
  for (int jp = 0; jp < 2; jp++)
    stmatrix_x4(rowaddr + (((hh * 4 + 2 * jp + (mat >> 1)) ^ r7) << 4),
                pack_bf16x2(o[8 * jp] * inv[0], o[8 * jp + 1] * inv[0]),
                pack_bf16x2(o[8 * jp + 2] * inv[1], o[8 * jp + 3] * inv[1]),
                pack_bf16x2(o[8 * jp + 4] * inv[0], o[8 * jp + 5] * inv[0]),
                pack_bf16x2(o[8 * jp + 6] * inv[1], o[8 * jp + 7] * inv[1]));
}

__device__ __forceinline__ void attention_a(int HH, int L, int gb, int hp, uint32_t par0, uint32_t parA, int wwarp, int lane,
                                            uint32_t zero) {
  constexpr uint32_t bars = SBASE + OFF_BAR;
  const uint32_t dslot = ((SBASE + OFF_SLOT) >> 4) + 0x10000u + HH * 4;
  const uint32_t dq = dslot + 3 * 1024;
  float sa[32], sb[32], o[2][16], l[2][2];
  auto dch = [&](int n) { return dslot + 1024u * (n % 3 == 0 ? 1 : (n % 3 == 1 ? 0 : 2)); };
  wgmma_fence();
  wgmma_n64_ssz_ta0_tb0(sa, desc_lo(dq + 512), desc_lo(dch(0)));
  wgmma_n64_ss_ta0_tb0(sa, desc_lo(dq + 512 + 2), desc_lo(dch(0) + 2), 1);
  wgmma_commit();
#pragma unroll
  for (int h = 0; h < 2; h++) {
#pragma unroll
    for (int i = 0; i < 16; i++) o[h][i] = 0.f;
    l[h][0] = l[h][1] = 0.f;
  }
  const int dg = (lane >> 2) - 2 * (lane & 3);
  const uint32_t tri = (dg >= 0 ? 0xffffu : 0u) | (dg >= 1 ? 0xffff0000u : 0u);
  const int nmax = 2 * gb + 1;
  wgmma_wait<0>();
  reg_fence<32>(sa);
#define STON false
#define ATT_STEP(i, MODE)                                                                                            \
  attn_unit<MODE, true>(sa, sb, o[1], l[1], i <= nmax, dch(i) + 512, dq, dch(i + 1), tri, wwarp,                     \
                        i >= 1 ? bars + 8u * (B_HALO + i - 1) : 0u, i == 1 ? par0 : parA, 0u, zero, STON); \
  attn_unit<MODE, (i < 4)>(sb, sa, o[0], l[0], i + 1 <= nmax, dch(i + 1) + 512, dq + 512, dch(i + 1), tri, wwarp, 0u, \
                           0u, i < 3 && lane == 0 ? bars + 8u * (B_REL + i) : 0u, zero);
  ATT_STEP(0, 1)
  ATT_STEP(1, 0)
  ATT_STEP(2, 0)
  ATT_STEP(3, 0)
  ATT_STEP(4, 2)
#undef ATT_STEP
  const uint32_t ra = OA_TILE + (((lane & 8) ? 7 - wwarp : wwarp) * 8 + (lane & 7)) * 128;
  bool redo[2];
#pragma unroll
  for (int h = 1; h >= 0; h--) {
    float inv[2];
    bool bad = false;
#pragma unroll
    for (int r = 0; r < 2; r++) {
      float v = l[h][r];
      v += __shfl_xor_sync(0xffffffffu, v, 1);
      v += __shfl_xor_sync(0xffffffffu, v, 2);
      bad |= !(v <= 1.152921504606846976e18f && v >= 8.673617379884035e-19f);
      inv[r] = rcp_fast(v);
    }
    if (h == 0) wgmma_wait<0>();
    reg_fence<16>(o[h]);
    store_o(o[h], inv, ra + h * 8192, HH, lane);
    redo[h] = __any_sync(0xffffffffu, bad);
    if (h == 1 && !redo[1]) {
      fence_proxy_async_smem();
      named_bar_arrive(9, 288);
    }
  }
  if (HH == 0) GTL(45);
  if (redo[0] || redo[1]) {
    attn_a_slow(g_kvA[L >> 1][0][0][0], L, gb, hp, HH, wwarp, lane, redo[0] ? 0 : 16, redo[1] ? 32 : 16);
    fence_proxy_async_smem();
    if (redo[1]) named_bar_arrive(9, 288);
  }
}

constexpr uint32_t KB_ROW0 = SBASE + OFF_SLOT + 2048, VB_ROW0 = SBASE + OFF_SLOT + 24576 + 2048;

__device__ __forceinline__ void attnB_soft(const float (&s)[40], int wwarp, int D, bool edge, bool odd,
                                           uint32_t (&p)[5][4], float (&sum)[2]) {
  float z[2][3];
#define GATHER_(W)                                                                                  \
  _Pragma("unroll") for (int r = 0; r < 2; r++) _Pragma("unroll") for (int t = 0; t < 3; t++)       \
      z[r][t] = odd ? s[4 * (2 * W + r + t) + 2 * r + 1] : s[4 * (2 * W + r + t) + 2 * r];
  if (wwarp < 2) {
    if (wwarp == 0) { GATHER_(0) } else { GATHER_(1) }
  } else {
    if (wwarp == 2) { GATHER_(2) } else { GATHER_(3) }
  }
#undef GATHER_
  float y[2];
  y[0] = D >= 2 ? z[0][0] : z[0][2];
  y[1] = D >= 2 ? z[1][0] : z[1][2];
  if (edge) {
    z[0][1] = -INFINITY;
    if (D >= 2) y[0] = y[1] = -INFINITY;
  }
  float m0 = fmaxf(z[0][1], y[0]), m1 = fmaxf(z[1][1], y[1]);
  m0 = fmaxf(m0, __shfl_xor_sync(0xffffffffu, m0, 1));
  m1 = fmaxf(m1, __shfl_xor_sync(0xffffffffu, m1, 1));
  m0 = fmaxf(m0, __shfl_xor_sync(0xffffffffu, m0, 2));
  m1 = fmaxf(m1, __shfl_xor_sync(0xffffffffu, m1, 2));
  const float e00 = ex2_approx(z[0][1] - m0), e01 = ex2_approx(y[0] - m0);
  const float e10 = ex2_approx(z[1][1] - m1), e11 = ex2_approx(y[1] - m1);
  sum[0] = e00 + e01;
  sum[1] = e10 + e11;
  const int sh = odd ? 16 : 0;
  const uint32_t a0 = pack_bf16x2(e00, 0.f) << sh, a1 = pack_bf16x2(e10, 0.f) << sh;
  const uint32_t b0 = pack_bf16x2(e01, 0.f) << sh, b1 = pack_bf16x2(e11, 0.f) << sh;
  const int kb = wwarp + (D >= 2 ? 0 : 1);
#pragma unroll
  for (int k = 0; k < 5; k++) {
    p[k][0] = k == kb ? b0 : 0u;
    p[k][1] = k == wwarp + 1 ? a1 : 0u;
    p[k][2] = k == wwarp ? a0 : 0u;
    p[k][3] = k == kb ? b1 : 0u;
#pragma unroll
    for (int q = 0; q < 4; q++) asm volatile("" : "+r"(p[k][q]));
  }
}

__device__ __forceinline__ void attnB_s(float (&s)[40], int HH, int h) {
  constexpr uint32_t sq = SBASE + OFF_SLOT + 3 * 16384;
#pragma unroll
  for (int ks = 0; ks < 2; ks++)
    wgmma_n80_ss_ta0_tb0(s, make_desc(sq + h * 8192 + HH * 64 + ks * 32, 16),
                         make_desc(KB_ROW0 + h * 8192 - 2048 + HH * 64 + ks * 32, 16), ks);
}
__device__ __forceinline__ void attnB_pv(float (&o)[16], const uint32_t (&p)[5][4], int HH, int h) {
#pragma unroll
  for (int k = 0; k < 5; k++)
    wgmma_n32_rs_tb1(o, p[k], make_desc(VB_ROW0 + h * 8192 - 2048 + k * 2048 + HH * 64, 16), k);
}

__device__ __forceinline__ void attention_b(int HH, int gb, uint32_t par0, int wwarp, int lane, bool ston) {
  constexpr uint32_t bars = SBASE + OFF_BAR, sq = SBASE + OFF_SLOT + 3 * 16384;
  float s[40];
  reg_define<40>(s);
  wgmma_fence();
  attnB_s(s, HH, 1);
  wgmma_commit();
  const int g = lane >> 2;
  const bool odd = g & 1;
  const int D = 2 * (lane & 3) + (g & 1) - g;
  const uint32_t ra = sq + (wwarp * 16 + ((lane >> 3) & 1) * 8 + (lane & 7)) * 128;
  wgmma_wait<0>();
  reg_fence<40>(s);
  STAMP(ston, 21);
#pragma unroll 1
  for (int h = 1; h >= 0; h--) {
    float o[16], inv[2];
    uint32_t p[5][4];
    reg_define<16>(o);
    attnB_soft(s, wwarp, D, h == 0 && gb == 0 && wwarp == 0, odd, p, inv);
    STAMP(ston, 25 - 3 * h);
    wgmma_fence();
    attnB_pv(o, p, HH, h);
    wgmma_commit();
#pragma unroll
    for (int r = 0; r < 2; r++) {
      inv[r] += __shfl_xor_sync(0xffffffffu, inv[r], 1);
      inv[r] += __shfl_xor_sync(0xffffffffu, inv[r], 2);
      inv[r] = rcp_fast(inv[r]);
    }
    if (h == 1) {
      mbar_wait(bars + 8u * B_HALO, par0);
      STAMP(ston, 23);
      wgmma_fence();
      attnB_s(s, HH, 0);
      wgmma_commit();
      wgmma_wait<1>();
    } else {
      wgmma_wait<0>();
    }
    reg_fence<16>(o);
    store_o(o, inv, ra + h * 8192, HH, lane);
    if (h == 1) {
      fence_proxy_async_smem();
      named_bar_arrive(9, 288);
    }
    wgmma_wait<0>();
    reg_fence<40>(s);
    STAMP(ston, 26 - 2 * h);
  }
}

#define TRICKLE 300
#define CSI 1
#define PCA 1
#define PCB 3
#define PXB 4
#define EPW1 4
#define EPW0 12
#define PRENS 800
#define LOCE 1
#define QTURN 2
constexpr int NPT = 240 + 8;
struct Params {
  CUtensorMap xq[2], xr[3], o, wqkv[2], wo[2];
  const __nv_bfloat16* in_x;
  const __nv_bfloat16* wqkv_p1;
  const __nv_bfloat16* wo_p[2];
  uint32_t zero;
  uint2 wtab[4][17];
  uint2 ptab[NPT + 1];
};
static_assert(sizeof(Params) <= 4096, "");

__device__ __forceinline__ void colsum_part(const CUtensorMap* wmap, int ty, int qr, int hp) {
  constexpr uint32_t bars = SBASE + OFF_BAR, slots = SBASE + OFF_SLOT;
  PHASE_IDS
  const unsigned ep1 = (*(volatile unsigned*)(g_flags + F_DONE)) / NCTA + 1u;
  if (ty) {
#pragma unroll 1
    for (int j = 0; j < 4; j++) poison(g_kvB[j >> 1][(j & 1) * 8 + qr][hp] + tid * 16, 2, POI1);
    asm volatile("fence.acq_rel.gpu;" ::: "memory");
    fence_proxy_async_all();
  }
  if (wwarp == 0 && elect_one()) {
    mbar_expect_tx(bars + 8u * B_CS, 6 * UNIT);
#pragma unroll 1
    for (int j = 0; j < 2; j++) {
      if (ty == 0) mbar_pace(bars + 8u * (B_EMPTY + PCA + PCB * j), 0);
      else __nanosleep(1000);
      tma_load_3d(slots + j * 3 * UNIT, wmap, bars + 8u * B_CS, hp * 64, qr * 128 + j * 64, 0);
    }
  }
  mbar_wait(bars + 8u * B_CS, ty);
  STAMP(KSQ == 0 && ty == 0, 49);
  const uint32_t src = slots + (tid >> 3) * 128 + (((tid & 7) ^ ((tid >> 3) & 7)) << 4);
#pragma unroll 1
  for (int p = 0; p < 3; p++) {
    float s[8];
#pragma unroll
    for (int e = 0; e < 8; e++) s[e] = 0.f;
#pragma unroll
    for (int j = 0; j < 8; j++) {
      const uint4 v = lds128(src + p * UNIT + (j >> 2) * 3 * UNIT + (j & 3) * 2048);
      const uint32_t x[4] = {v.x, v.y, v.z, v.w};
#pragma unroll
      for (int e = 0; e < 4; e++) {
        s[2 * e] += bf_lo(x[e]);
        s[2 * e + 1] += bf_hi(x[e]);
      }
    }
#pragma unroll
    for (int st = 0; st < 2; st++) {
      const bool up = (lane >> (st + 3)) & 1;
#pragma unroll
      for (int e = 0; e < (4 >> st); e++) {
        const float keep = up ? s[e + (4 >> st)] : s[e], give = up ? s[e] : s[e + (4 >> st)];
        s[e] = keep + __shfl_xor_sync(0xffffffffu, give, 8 << st);
      }
    }
    const uint32_t dst = slots + 6 * UNIT + ((wwarp * 3 + p) * 64 + (lane & 7) * 8 + ((lane >> 3) & 1) * 4 + (lane >> 4) * 2) * 4;
    sts32(dst, __float_as_uint(s[0]));
    sts32(dst + 4, __float_as_uint(s[1]));
  }
  named_bar_sync(6, 128);
  if (tid < 64) {
    float r[3] = {0.f, 0.f, 0.f};
#pragma unroll
    for (int e = 0; e < 12; e++) r[e % 3] += __uint_as_float(lds32(slots + 6 * UNIT + (e * 64 + tid) * 4));
    st_rec(&g_cs[ty][hp][qr][tid], r[0], r[1], r[2], ep1);
    STAMP(KSQ == 0 && ty == 0, 50);
  }
  named_bar_sync(6, 128);
}

__device__ __forceinline__ void cs_put(int blk, int ty, int col, float v) {
  const uint32_t hi = pack_bf16x2(v, 0.f), lo = pack_bf16x2(v - bf_lo(hi), 0.f);
  const uint32_t a = SBASE + OFF_CS + blk * 512 + ty * 256 + col * 2;
  asm volatile("st.shared.b16 [%0], %1;" ::"r"(sw(a ^ (((a >> 7) & 7) << 4))), "h"((unsigned short)hi) : "memory");
  asm volatile("st.shared.b16 [%0], %1;" ::"r"(sw((a + 128) ^ ((((a >> 7) + 1) & 7) << 4))), "h"((unsigned short)lo) : "memory");
}

__device__ __forceinline__ uint32_t ln_params(float s1, float s2) {
  const float mean = s1 * (1.0f / DM);
  const float var = fmaxf(fmaf(-mean, mean, s2 * (1.0f / DM)), 0.f);
  float sd;
  asm("sqrt.approx.f32 %0, %1;" : "=f"(sd) : "f"(bf16_round(bf16_round(var) + 1e-5f)));
  return pack_bf16x2(mean, sd);
}

#define SPLITS 0x085866688ull
__host__ __device__ __forceinline__ int q_split(int inst) { return (int)((SPLITS >> (4 * inst)) & 15ull); }
__device__ __forceinline__ int q_first(int inst) { return inst == 0 ? 0 : 32 * inst - 16; }
__device__ __forceinline__ int w_first(int inst) { return 32 * inst + 16 + 2 * q_split(inst + 1); }
#define PREMASK 0x2Cu
#define WBUF 0x0400103000201000ull
static_assert((PREMASK & 0xC0u) == 0, "");
__host__ __device__ __forceinline__ bool w_pre(int inst) { return (PREMASK >> inst) & 1u; }
struct WPlan {
  int v[6][21];
  int own[28], len;
};
__host__ __device__ constexpr WPlan w_plan(int mode) {
  WPlan p{};
  for (int u = 0; u < 28; u++) p.own[u] = u < 20 ? u / 5 - 4 : -16;
  if (mode == 2) {
    const WPlan q = w_plan(0);
    for (int u = 0; u < 20; u++) p.own[u] = q.own[(u + q.len) % 20] - 16;
  }
  int pos = 0, mx = -16;
  for (int kt = 0; kt < 21; kt++) {
    const int code = mode == 1 && kt < 16 ? (int)(WBUF >> (4 * kt)) & 15 : 0, st = kt > 16 ? kt - 1 : kt;
    const int na = kt == 16 ? 0 : (kt < 16 ? 1 : 2), nb = kt < 17 ? 2 : 3;
    const bool hole = code == 0 || (code & 8), swap = kt < 16 && hole && pos % 10 == 8;
    const int ua = (pos + (swap ? 2 : 0)) % 20, ub = code ? NUNITS - 2 + 2 * (code & 7) : (pos + (swap ? 0 : na)) % 20;
    int ra = st - 8, rb = kt == 16 ? -16 : st - 8;
    for (int i = 0; i < na; i++) ra = p.own[ua + i] > ra ? p.own[ua + i] : ra;
    for (int i = 0; i < nb; i++) rb = p.own[ub + i] > rb ? p.own[ub + i] : rb;
    p.v[0][kt] = ua;
    p.v[1][kt] = ub;
    p.v[2][kt] = st - ra;
    p.v[3][kt] = st - rb;
    p.v[4][kt] = rb > mx;
    p.v[5][kt] = p.own[ub] == -16;
    mx = rb > mx ? rb : mx;
    if (kt < 17) {
      for (int i = 0; i < na; i++) p.own[ua + i] = kt;
      for (int i = 0; i < nb; i++) p.own[ub + i] = kt < 16 ? kt : 15;
    }
    pos += na + (hole ? nb : 0);
    if (kt == 16) p.len = pos;
  }
  return p;
}
__host__ __device__ constexpr uint64_t w_tab(int f, int mode, int k0, int dk, int n, int bits) {
  const WPlan p = w_plan(mode);
  uint64_t r = 0;
  for (int j = 0; j < n; j++) r |= (uint64_t)p.v[f][k0 + j * dk] << (bits * j);
  return r;
}
__host__ __device__ constexpr uint32_t q_backs(bool act, int rank, bool pre) {
  return act ? 0x44444400u | (uint32_t)w_tab(2, pre, 17 + rank, 2, 2, 4) : 0x44440000u | (uint32_t)w_tab(3, pre, 17, 1, 4, 4);
}
__host__ __device__ constexpr uint32_t w_early() {
  const WPlan p = w_plan(1);
  uint32_t r = 0;
  for (int kt = 0; kt < 16; kt++)
    if (p.v[5][kt]) r |= (uint32_t)kt << (2 * (p.v[1][kt] - NUNITS));
  return r;
}
__host__ __device__ constexpr uint32_t w_emask() {
  const WPlan p = w_plan(1);
  uint32_t r = 0;
  for (int kt = 0; kt < 16; kt++) r |= (uint32_t)p.v[5][kt] << kt;
  return r;
}
static_assert((w_emask() & 3) == 0 && (w_early() & 15) < ((w_early() >> 4) & 15) && ((w_early() >> 4) & 15) < ((w_early() >> 8) & 15) &&
              ((w_early() >> 8) & 15) < (w_early() >> 12), "");
static_assert(w_plan(1).len % 10 == 0 && w_tab(2, 0, 0, 2, 8, 4) == 0x77776654u && w_tab(2, 2, 1, 2, 8, 4) == 0x77777666u &&
              q_backs(false, 0, false) == 0x44444445u && q_backs(true, 0, false) == 0x44444456u, "");
constexpr bool PRE_FLIP = w_plan(1).len % 20 != 0;
__device__ __forceinline__ int w_flips(int n) { return PRE_FLIP ? n : __popc(~PREMASK & ((1u << n) - 1u)); }
__host__ __device__ __forceinline__ uint32_t unit_off(int u, uint32_t dl) { return u * UNIT + (u < 10 ? dl : (u < 20 ? 0u - dl : 0u)); }

__global__ void __cluster_dims__(2, 1, 1) __launch_bounds__(512, 1) fused_kernel(const __grid_constant__ Params P) {
  constexpr uint32_t base = SBASE, bars = base + OFF_BAR, slots = base + OFF_SLOT;
  const int warp = __shfl_sync(0xffffffffu, threadIdx.x >> 5, 0), lane = threadIdx.x & 31;
  const int b = blockIdx.x, rank = b & 1;
  if (smem_u32(smem_raw) != base + (rank << 24)) __trap();
  int role = 0;
  {
    unsigned smid;
    asm volatile("mov.u32 %0, %smid;" : "=r"(smid));
    const int tc = smid >> 1;
    role = (tc < 32 ? (tc & 7) * 8 + (tc >> 3) : (tc < 62 ? ((tc - 32) % 7 + 1) * 8 + 4 + (tc - 32) / 7 : tc - 58)) & 63;
  }
  if (warp == 12) {
    if (elect_one()) {
#pragma unroll
      for (int s = 0; s < 8; s++) {
        mbar_init(bars + 8u * (B_FULL + s), 1);
        mbar_init(bars + 8u * (B_EMPTY + s), LOCE ? 2 : 4);
        mbar_init(bars + 8u * (B_LOC + s), 2);
      }
      mbar_init(bars + 8u * B_GO, 1);
      mbar_init(bars + 8u * B_ROLE, 1);
      mbar_expect_tx(bars + 8u * B_ROLE, 4);
      fence_barrier_init();
    }
    __syncwarp();
  }
  asm volatile("barrier.cluster.arrive.relaxed.aligned;" ::: "memory");
  if (threadIdx.x == 0) {
    mbar_init(bars + 8u * B_PREP, 1);
    mbar_init(bars + 8u * (B_PREP + 1), 1);
    for (int s = 0; s < 4; s++) mbar_init(bars + 8u * (B_HALO + s), 1);
    for (int s = 0; s < 3; s++) mbar_init(bars + 8u * (B_REL + s), 8);
    mbar_init(bars + 8u * B_AFREE, 2);
    mbar_init(bars + 8u * B_TURN, 4);
    mbar_init(bars + 8u * (B_TURN + 1), 4);
    mbar_init(bars + 8u * B_CS, 1);
    mbar_init(bars + 8u * B_HB, 1);
    mbar_init(bars + 8u * B_KVS, 1);
    for (int s = 0; s < 4; s++) mbar_init(bars + 8u * (B_PRE + s), 1);
    mbar_init(bars + 8u * B_RESF, 1);
    mbar_init(bars + 8u * B_RESE, 4);
    mbar_init(bars + 8u * B_CSD, 4);
    mbar_init(bars + 8u * B_XRDY, 1);
    mbar_init(bars + 8u * (B_XRDY + 1), 1);
    fence_barrier_init();
  }
  if (warp == 15 && rank == 0) {
    const unsigned ep = *(volatile unsigned*)(g_flags + F_DONE);
    int r = role;
#pragma unroll 1
    for (int it = 0; it < 64; it++, r = (r + 1) & 63) {
      if (__all_sync(0xffffffffu, (ep - atom_add(g_flags + F_ROLE + r * RSTR, NCTA, lane == 0) < NCTA) | (lane != 0))) break;
      atom_add(g_flags + F_ROLE + r * RSTR, 0u - NCTA, lane == 0);
    }
    asm volatile("barrier.cluster.wait.aligned;" ::: "memory");
    asm volatile("{\n.reg .pred p;\nsetp.lt.u32 p, %3, 2;\n"
                 "@p st.async.weak.shared::cluster.mbarrier::complete_tx::bytes.b32 [%0], %1, [%2];\n}\n" ::"r"(base + OFF_ROLE + (lane << 24)),
                 "r"(r), "r"(bars + 8u * B_ROLE + (lane << 24)), "r"(lane)
                 : "memory");
  } else if (warp != 12) {
    asm volatile("barrier.cluster.wait.aligned;" ::: "memory");
  }
#define ROLE_IDS                                                                                   \
  const int qr = role & 7, hp = (role >> 3) * 2 + rank, rt = role & 15, ct = ((role >> 3) & 6) + rank; \
  (void)qr; (void)hp; (void)rt; (void)ct;
#define ROLE_GET                                                          \
  named_bar_sync(0, 512);                                                 \
  role = __shfl_sync(0xffffffffu, (int)lds32(base + OFF_ROLE), 0);

  if (warp < 12) {
    const bool asst = warp >= 8;
    ROLE_GET
    ROLE_IDS
    uint32_t tpar = 0;
    const uint32_t ebar = LOCE && (warp & 2) ? bars + 8u * B_LOC + (rank << 24) : bars + 8u * B_EMPTY + ((warp & 1) << 24);
    GTL(0);
#pragma unroll 1
    for (int inst = (warp < 4 ? 0 : -1) + (int)P.zero; inst < 8; inst += asst ? 1 : 2) {
      const int L = inst >> 1, ch = inst & 1, gb = ch * 8 + qr;
      if (inst >= 0) {
      if (asst) {
        setmaxnreg_dec<24>();
        named_bar_sync(4, 256);
        setmaxnreg_inc<128>();
      } else {
      setmaxnreg_inc<224>();
      {
        float acc[2][96];
        const int ksp = q_split(inst);
        int n = q_first(inst);
        uint32_t dlt = inst > 0 && (w_flips(inst - 1) & 1) ? 10u * (UNIT >> 4) : 0u;
        if (inst == 1 || (inst > 1 && q_split(inst - 1) != 8)) {
          mbar_wait_lazy<100>(bars + 8u * (B_TURN + ch), tpar);
          tpar ^= 1u;
        }
        if (L == 3) GTL(37);
        mbar_wait(bars + 8u * (B_FULL + (n & 7)), (n >> 3) & 1);
        GTL(1 + L * 8);
        {
          const uint32_t da = (base >> 4) + 0x10000u + dlt;
          const uint64_t db = desc_lo(da - 0x10000u + ((UNIT >> 4) << 16) + 2 * (UNIT >> 4));
          wgmma_fence();
          wgmma_n192_ssz_ta0_tb1(acc[0], desc_lo(da), db);
          wgmma_commit();
          wgmma_n192_ssz_ta0_tb1(acc[1], desc_lo(da + (UNIT >> 4)), db);
          wgmma_commit();
        }
#pragma unroll 1
        for (int k2 = 0; k2 < 7; k2++) {
          const bool brk = k2 + 1 == ksp;
#pragma unroll
          for (int ks = 0; ks < 2; ks++, n++) {
            STAMP(inst == KSQ, k2 * 2 + ks);
            const uint32_t da = ((base + ks * 5 * UNIT) >> 4) + 0x10000u + dlt;
            const uint32_t dbb = da - 0x10000u + ((UNIT >> 4) << 16) + 2 * (UNIT >> 4);
#pragma unroll
            for (int k16 = 0; k16 < 4; k16++) {
              if (ks == 0 && k16 == 0 && k2 == 0) continue;
              const uint64_t db = desc_lo(dbb + k16 * 128);
              wgmma_fence();
              wgmma_n192_ss_ta0_tb1(acc[0], desc_lo(da + k16 * 2), db, 1);
              wgmma_commit();
              wgmma_wait<1>();
              if (k16 == 0) warp_arrive_cl(ebar + 8u * ((n - 1) & 7), ks != 0 || k2 != ksp);
              wgmma_fence();
              wgmma_n192_ss_ta0_tb1(acc[1], desc_lo(da + (UNIT >> 4) + k16 * 2), db, 1);
              wgmma_commit();
              bool ok = true;
              if (k16 == 2) ok = mbar_test(bars + 8u * (B_FULL + ((n + 1) & 7)), ((n + 1) >> 3) & 1) || (ks == 1 && brk);
              if (k16 == QTURN && ks == 1) warp_arrive(bars + 8u * (B_TURN + (ch ^ 1)), brk);
              if (ks == 0 || k16 < 3) wgmma_wait<1>();
              if (k16 == 2 && !ok) mbar_wait(bars + 8u * (B_FULL + ((n + 1) & 7)), ((n + 1) >> 3) & 1);
            }
          }
          if (brk) {
            wgmma_wait<0>();
            warp_arrive_cl(ebar + 8u * ((n - 1) & 7));
            n += 16;
            mbar_wait_lazy<100>(bars + 8u * (B_TURN + ch), tpar);
            tpar ^= 1u;
            STAMP(inst == KSQ, 17);
            mbar_wait(bars + 8u * (B_FULL + (n & 7)), (n >> 3) & 1);
          }
          if (!brk || (!PRE_FLIP && w_pre(inst - 1))) dlt ^= 10u * (UNIT >> 4);
        }
        auto tail_group = [&](int u) {
          const uint32_t da = ((base + (u & 1) * 5 * UNIT) >> 4) + 0x10000u + dlt;
          const uint32_t dbb = da - 0x10000u + ((UNIT >> 4) << 16) + 2 * (UNIT >> 4);
          if (u < 3) wgmma_fence();
#pragma unroll
          for (int k16 = 0; k16 < 4; k16++)
            wgmma_n192_ss_ta0_tb1(acc[u < 2], desc_lo(da + (u < 2 ? UNIT >> 4 : 0) + k16 * 2), desc_lo(dbb + k16 * 128), 1);
          wgmma_commit();
        };
        STAMP(inst == KSQ, 14);
        tail_group(0);
        wgmma_wait<1>();
        STAMP(inst == KSQ && KSPN, 42);
        warp_arrive_cl(ebar + 8u * ((n - 1) & 7), ksp != 7);
        PHASE_IDS
        mbar_wait(bars + 8u * (B_PREP + ch), L & 1);
        STAMP(inst == KSQ && KSPN, 43);
        uint32_t rs[4];
#pragma unroll
        for (int i = 0; i < 4; i++)
          rs[i] = lds32(base + OFF_RS + (ch * 128 + (i >> 1) * 64 + wwarp * 16 + g + 8 * (i & 1)) * 4);
        auto fold = [&](int h) {
          uint32_t a[2];
#pragma unroll
          for (int r = 0; r < 2; r++) a[r] = c == (L & 1) ? __byte_perm(rs[2 * h + r], 0, 0x1010) ^ 0x80008000u : 0u;
          uint64_t d;
          asm("mov.b64 %0, {%1, %2};" : "=l"(d) : "r"(((base + OFF_CS) >> 4) + ((512 >> 4) << 16)), "r"(0x40000000u));
          wgmma_fence();
          wgmma_n192_rs_tb1(acc[h], a[0], a[1], d);
        };
        fold(1);
        wgmma_commit();
        mbar_wait(bars + 8u * (B_FULL + ((n + 1) & 7)), ((n + 1) >> 3) & 1);
        STAMP(inst == KSQ && KSPN, 44);
        tail_group(1);
        tail_group(2);
        STAMP(inst == KSQ && KSPN, 45);
        const bool ppre = ksp == 7 && w_pre(inst - 1);
        const uint32_t fbar = bars + 8u * (ppre ? (LOCE ? B_LOC : B_EMPTY) + ((n - 1) & 7) : (inst == CSI + 1 ? B_CSD : B_AFREE));
        const uint32_t fpar = ppre ? ((n - 1) >> 3) & 1 : (inst == CSI + 1 ? 0 : ch);
        const bool afree = mbar_test(fbar, fpar);
        float rinv[2][2];
#pragma unroll
        for (int i = 0; i < 4; i++) rinv[i >> 1][i & 1] = rcp_fast(bf_hi(rs[i]));
        const int mat = lane >> 3;
        const uint32_t soff = (wwarp * 16 + (mat & 1) * 8 + (lane & 7)) * 128;
        const uint32_t kdst = ((L & 1) ? KB_ROW0 : slots) + soff, vdst = ((L & 1) ? VB_ROW0 : slots + 8192) + soff;
        const uint32_t hs = (L & 1) ? 8192 : 16384;
        const int rg = 2 * wwarp + (mat & 1);
        const uint32_t qdst = slots + 3 * 16384 + ((L & 1) ? soff : ((rg < 4 ? 2 * rg : 15 - 2 * rg) * 8 + (lane & 7)) * 128);
        wgmma_wait<2>();
        STAMP(inst == KSQ && KSPN, 46);
        fold(0);
        tail_group(3);
        STAMP(inst == KSQ && KSPN, 47);
        warp_arrive(bars + 8u * (B_TURN + (ch ^ 1)));
        if (!afree) {
          wgmma_wait<1>();
          warp_arrive_cl(ebar + 8u * (n & 7));
          wgmma_wait<0>();
          warp_arrive_cl(ebar + 8u * ((n + 1) & 7));
          mbar_wait(fbar, fpar);
        }
        wgmma_wait<2>();
        reg_fence<96>(acc[1]);
        STAMP(inst == KSQ, 15);
#pragma unroll
        for (int t = 0; t < 24; t++) {
          const int h = t < 12 ? 1 : 0, p = (t % 12 / 4 + 1) % 3, jp = t & 3;
          if (t == EPW1) {
            wgmma_wait<1>();
            warp_arrive_cl(ebar + 8u * (n & 7), afree);
          }
          if (t == EPW0) {
            wgmma_wait<0>();
            reg_fence<96>(acc[0]);
            warp_arrive_cl(ebar + 8u * ((n + 1) & 7), afree);
            STAMP(inst == KSQ, 16);
            GTL(2 + L * 8);
          }
          if (t % 12 == 8) {
            rinv[h][0] *= SM_C;
            rinv[h][1] *= SM_C;
          }
          const uint32_t swz = ((2 * jp + (mat >> 1)) ^ (lane & 7)) << 4;
          const float* a = &acc[h][32 * p + 8 * jp];
          const uint32_t dst = p == 0 ? qdst + h * 8192 : (p == 1 ? kdst : vdst) + h * hs;
          stmatrix_x4(dst + swz, pack_bf16x2(a[0] * rinv[h][0], a[1] * rinv[h][0]), pack_bf16x2(a[2] * rinv[h][1], a[3] * rinv[h][1]),
                      pack_bf16x2(a[4] * rinv[h][0], a[5] * rinv[h][0]), pack_bf16x2(a[6] * rinv[h][1], a[7] * rinv[h][1]));
          if (t % 12 == 7) {
            fence_proxy_async_smem();
            if (t == 7) named_bar_arrive(3, (L & 1) ? 192 : 160);
            else if ((L & 1) == 0) named_bar_arrive(7, 160);
            if (t > EPW0) sched_fence(P.zero);
          }
        }
      }
      fence_proxy_async_smem();
      setmaxnreg_dec<128>();
      named_bar_sync(4, 256);
      }
      GTL(3 + L * 8);
      {
        PHASE_IDS
        if ((L & 1) == 0) attention_a(asst, L, gb, hp, inst & 1, ch, (tid_ >> 5) & 3, lane, P.zero);
        else attention_b(asst, gb, inst & 1, wwarp, lane, KSAON);
        GTL(4 + L * 8);
        fence_proxy_async_smem();
      }
      if (!asst) {
      {
        named_bar_sync(5, 256);
        STAMP(KSAON, 27);
        if ((warp & 3) == 0 && elect_one()) {
          tma_store_3d(&P.o, (L & 1) ? slots + 3 * 16384 : OA_TILE, 0, gb * 128, hp);
          bulk_commit();
          bulk_wait0();
          STAMP(KSAON, 31);
          mbar_arrive(bars + 8u * B_AFREE);
          announce(g_flags + F_O + gb * 2 * OSTR + hp);
        }
        __syncwarp();
      }
      GTL(5 + L * 8);

      {
        float acc[64];
        const int n0 = w_first(inst);
        const bool pre = w_pre(inst);
        const uint32_t dl = ((w_flips(inst) + q_split(inst + 1)) & 1) * 10u * UNIT;
        const uint2* tab = P.wtab[2 * pre + (dl != 0)];
        const uint32_t ppar = __popc(PREMASK & ((1u << inst) - 1u)) & 1;
        uint32_t pbar = bars + 8u * B_PRE;
        const uint32_t flg = (pre ? w_emask() >> 1 : 0u) | (inst >= 6 || q_split(inst + 1) != 8 ? 1u << 30 : 0u);
        uint2 e = tab[0];
        mbar_wait_lazy<100>(bars + 8u * (B_TURN + ch), tpar);
        tpar ^= 1u;
        mbar_wait(bars + 8u * (B_FULL + (n0 & 7)), (n0 >> 3) & 1);
        GTL(6 + L * 8);
        auto wstep = [&](auto first_, int kt) {
          constexpr bool first = decltype(first_)::value;
          const int n = n0 + kt;
          STAMP(inst == KSW, 20 + kt);
          wgmma_fence();
          if (first) wgmma_n128_ssz_ta0_tb1(acc, desc_lo(e.x), desc_lo(e.y));
#pragma unroll
          for (int k16 = first ? 1 : 0; k16 < 4; k16++) wgmma_n128_ss_ta0_tb1(acc, desc_lo(e.x + 2 * k16), desc_lo(e.y + 128 * k16), 1);
          wgmma_commit();
          if (!first) warp_arrive(bars + 8u * (B_TURN + (ch ^ 1)), (flg >> kt) & 0x8000u);
          e = tab[kt + 1];
          const uint32_t nb = bars + 8u * (kt == 15 ? B_RESF : B_FULL + ((n + 1) & 7)), np = kt == 15 ? ch : ((n + 1) >> 3) & 1;
          const bool ok = mbar_test(nb, np);
          if (!first) {
            wgmma_wait<1>();
            warp_arrive_cl(ebar + 8u * ((n - 1) & 7));
            if ((flg >> kt) & 1u) {
              mbar_wait(pbar, ppar);
              pbar += 8u;
            }
          }
          if (!ok) mbar_wait(nb, np);
        };
        wstep(std::true_type(), 0);
#pragma unroll WUNR
        for (int kt = 1; kt < 16; kt++) wstep(std::false_type(), kt);
        PHASE_IDS
        const uint32_t xb = e.x;
        const int mat = lane >> 3;
        const uint32_t xrow = xb + (wwarp * 16 + (mat & 1) * 8 + (lane & 7)) * 128;
        uint32_t xv[8][4];
#pragma unroll
        for (int jp = 0; jp < 8; jp++)
          ldmatrix_x4(xv[jp], xrow + (jp >> 2) * UNIT + (((2 * (jp & 3) + (mat >> 1)) ^ (lane & 7)) << 4));
        wgmma_wait<0>();
        reg_fence<64>(acc);
        warp_arrive_cl(ebar + 8u * ((n0 + 15) & 7));
        STAMP(inst == KSW, 36);
        GTL(7 + L * 8);
#pragma unroll
        for (int jp = 0; jp < 8; jp++) {
#pragma unroll
          for (int q = 0; q < 4; q++) xv[jp][q] = add_bf16x2(xv[jp][q], pack_bf16x2(acc[8 * jp + 2 * q], acc[8 * jp + 2 * q + 1]));
          stmatrix_x4(xrow + (jp >> 2) * UNIT + (((2 * (jp & 3) + (mat >> 1)) ^ (lane & 7)) << 4), xv[jp][0], xv[jp][1],
                      xv[jp][2], xv[jp][3]);
        }
        const int grow = ch * 1024 + rt * 64;
        fence_proxy_async_smem();
        named_bar_sync(1 + ch, 128);
        if (wwarp == 0) {
          if (elect_one()) {
            STAMP(inst == KSW, 37);
            tma_store_3d(&P.xr[L == 3 ? 2 : 1], xb, ct * 128, grow, 0);
            bulk_commit();
            bulk_wait0();
            STAMP(inst == KSW, 38);
            mbar_arrive(bars + 8u * B_RESE);
            if (L < 3) announce(g_flags + F_X + (ch * 8 + (rt >> 1)) * XSTR + ct);
            STAMP(inst == KSW, 39);
          }
          __syncwarp();
        } else if (lane == 0) {
          mbar_arrive(bars + 8u * B_RESE);
        }
        if (L < 3) {
          const unsigned ep1 = lds32(base + OFF_EPOCH);
          float s1[2] = {0.f, 0.f}, s2[2] = {0.f, 0.f};
#pragma unroll
          for (int jp = 0; jp < 8; jp++)
#pragma unroll
            for (int q = 0; q < 4; q++) {
              const float x0 = bf_lo(xv[jp][q]), x1 = bf_hi(xv[jp][q]);
              s1[q & 1] += x0 + x1;
              s2[q & 1] = fmaf(x0, x0, fmaf(x1, x1, s2[q & 1]));
            }
#pragma unroll
          for (int r = 0; r < 2; r++) {
            s1[r] += __shfl_xor_sync(0xffffffffu, s1[r], 1);
            s2[r] += __shfl_xor_sync(0xffffffffu, s2[r], 1);
            s1[r] += __shfl_xor_sync(0xffffffffu, s1[r], 2);
            s2[r] += __shfl_xor_sync(0xffffffffu, s2[r], 2);
            if (c == 0) st_rec(&g_stats[L + 1][ct][grow + wwarp * 16 + g + 8 * r], s1[r], s2[r], 0.f, ep1);
          }
        }
        GTL(8 + L * 8);
      }
      continue;
      }
      named_bar_arrive(5, 256);
      if (inst != CSI) continue;
      mbar_wait(bars + 8u * B_AFREE, CSI ^ 1);
      }
      if (asst) {
        colsum_part(&P.wqkv[inst >= 0], inst >= 0, qr, hp);
        warp_arrive(bars + 8u * (inst >= 0 ? B_CSD : B_AFREE), inst >= 0 || warp < 10);
      } else {
      PHASE_IDS
      {
        const unsigned ep1 = (*(volatile unsigned*)(g_flags + F_DONE)) / NCTA + 1u;
        const int row = b * 16 + (tid >> 3);
        const uint4* src = reinterpret_cast<const uint4*>(P.in_x + (size_t)row * DM) + (tid & 7);
        float s1 = 0.f, s2 = 0.f;
#pragma unroll 1
        for (int k = 0; k < 4; k++) {
          mbar_pace(bars + 8u * (B_EMPTY + PXB * k / 2), 0);
          uint4 v[4];
#pragma unroll
          for (int j = 0; j < 4; j++) v[j] = __ldg(src + (k * 4 + j) * 8);
#pragma unroll
          for (int j = 0; j < 4; j++) {
            const uint32_t w[4] = {v[j].x, v[j].y, v[j].z, v[j].w};
#pragma unroll
            for (int e = 0; e < 4; e++) {
              const float x0 = bf_lo(w[e]), x1 = bf_hi(w[e]);
              s1 += x0 + x1;
              s2 = fmaf(x0, x0, fmaf(x1, x1, s2));
            }
          }
        }
#pragma unroll
        for (int o = 1; o < 8; o <<= 1) {
          s1 += __shfl_xor_sync(0xffffffffu, s1, o);
          s2 += __shfl_xor_sync(0xffffffffu, s2, o);
        }
        if ((tid & 7) == 0) st_rec(&g_stats[0][0][row], s1, s2, 0.f, ep1);
        if (tid == 0) sts32(base + OFF_EPOCH, ep1);
        STAMP(KSQ == 0, 51);
        float4 v[6];
#pragma unroll 1
        for (uint32_t it = 0; it < (1u << 17); ++it) {
          bool ok = true;
#pragma unroll
          for (int t = 0; t < 6; t++) {
            v[t] = ld_rec(t < 2 ? &g_stats[0][0][(t * 8 + qr) * 128 + tid] : &g_cs[0][hp][(tid & 1) * 4 + t - 2][tid >> 1]);
            ok &= __float_as_uint(v[t].w) == ep1;
          }
          STAMP(KSQ == 0 && it == 0, 18);
          if (ok) break;
          __nanosleep(100);
        }
        STAMP(KSQ == 0, 17);
        __syncwarp();
        STAMP(KSQ == 0, 19);
#pragma unroll
        for (int cc = 0; cc < 2; cc++) sts32(base + OFF_RS + (cc * 128 + tid) * 4, ln_params(v[cc].x, v[cc].y));
        const float cs[3] = {(v[2].x + v[3].x) + (v[4].x + v[5].x), (v[2].y + v[3].y) + (v[4].y + v[5].y),
                             (v[2].z + v[3].z) + (v[4].z + v[5].z)};
#pragma unroll
        for (int blk = 0; blk < 3; blk++) {
          const float t = cs[blk] + __shfl_xor_sync(0xffffffffu, cs[blk], 1);
          cs_put(blk, tid & 1, tid >> 1, (tid & 1) ? 0.f : t);
        }
        fence_proxy_async_smem();
        named_bar_sync(2, 128);
        if (tid < 2) mbar_arrive(bars + 8u * (B_PREP + tid));
        STAMP(KSQ == 0, 48);
      }
      }
    }
    if (threadIdx.x == 128) atomicAdd(g_flags + F_DONE, 1u);
    if (!asst) asm volatile("barrier.cluster.arrive.relaxed.aligned;\nbarrier.cluster.wait.aligned;" ::: "memory");
    if (P.zero == 0) return;
  } else {
    setmaxnreg_dec<32>();
    if (warp != 12) {
      ROLE_GET
    }
    if (warp != 15) {
    if (warp == 14) {
      ROLE_IDS
      const unsigned ep1 = (*(volatile unsigned*)(g_flags + F_DONE)) / NCTA + 1u;
      uint32_t hbp = 0;
#pragma unroll 1
      for (int inst = 0; inst < 8; inst++) {
        const int L = inst >> 1, ch = inst & 1, gb = ch * 8 + qr;
        if ((L & 1) == 0) {
          const unsigned* fp = g_flags + F_KV + (max(gb - 1 - ((lane >> 1) & 1), 0) * 16 + hp) * KSTR + (lane & 1);
          uint32_t seen = gb == 0 ? 15u : (gb == 1 ? 12u : 0u);
          named_bar_sync(3, 160);
          STA(34);
          if (elect_one()) {
#pragma unroll 1
            for (int o = 0, pc = (PCM >> inst) & 1 ? PCS : 16384; o < 16384; o += pc) {
              bulk_store(g_kvA[L >> 1][gb][hp][1] + o, slots + 16384 + o, pc);
              if ((PCM >> inst) & 1) spin(PCN);
            }
            bulk_commit();
            bulk_wait0();
            STA(35);
            announce(g_flags + F_KV + (gb * 16 + hp) * KSTR);
            STA(41);
          }
          __syncwarp();
#pragma unroll 1
          for (int i = 0; i < 4; i++) {
            wait_lanes(fp, 2u * ep1 - 1u + (L >> 1), 1u << i, seen);
            STA(36 + i);
            if (i > 0) mbar_wait_lazy<RELNS>(bars + 8u * (B_REL + i - 1), ch);
            if (i == 2) mbar_wait(bars + 8u * B_KVS, ch);
            if (elect_one()) {
              mbar_expect_tx(bars + 8u * (B_HALO + i), 16384);
              bulk_load(slots + (i == 3 ? 2 : 2 - i) * 16384, gb > (i >> 1) ? g_kvA[L >> 1][gb - 1 - (i >> 1)][hp][(i & 1) ^ 1] : g_zero,
                        16384, bars + 8u * (B_HALO + i));
            }
          }
        } else {
          const uint8_t* src = gb > 0 ? g_kvB[L >> 1][gb - 1][hp] : g_zero;
          const uint32_t o = slots + lane * 32 + (lane & 28);
          named_bar_sync(3, 192);
          STA(34);
          if (elect_one()) spin(HBD);
          __syncwarp();
#pragma unroll 1
          for (uint32_t it = 0; it < (1u << 16); ++it) {
            if (elect_one()) {
              mbar_expect_tx(bars + 8u * B_HB, 4096);
              bulk_load(KB_ROW0 - 2048, src, 2048, bars + 8u * B_HB);
              bulk_load(VB_ROW0 - 2048, src + 2048, 2048, bars + 8u * B_HB);
            }
            mbar_wait(bars + 8u * B_HB, hbp);
            hbp ^= 1u;
            const uint32_t m = max(max(lds32(o), lds32(o + 1024)), max(lds32(o + 24576), lds32(o + 24576 + 1024)));
            STA(36 + min(it, 3u));
            if (__reduce_max_sync(0xffffffffu, m) != 0xffffffffu) break;
            fence_proxy_async_smem();
            __syncwarp();
          }
          warp_arrive(bars + 8u * B_HALO);
        }
        named_bar_sync(9, 288);
        if (elect_one()) {
          tma_store_3d(&P.o, ((L & 1) ? slots + 3 * 16384 : OA_TILE) + 8192, 0, gb * 128 + 64, hp);
          bulk_commit();
          bulk_wait0();
          mbar_arrive(bars + 8u * B_AFREE);
          announce(g_flags + F_O + (gb * 2 + 1) * OSTR + hp);
        }
        __syncwarp();
        if (w_pre(inst)) {
          mbar_wait(bars + 8u * B_KVS, ch);
          mbar_wait(bars + 8u * B_AFREE, (inst & 1) ^ 1);
          if (inst == CSI) mbar_wait(bars + 8u * B_CSD, 0);
#pragma unroll 1
          for (int j = 0; j < 4; j++) {
            constexpr uint32_t early = w_early();
            if (elect_one()) {
              mbar_expect_tx(bars + 8u * (B_PRE + j), 2 * UNIT);
              tma_load_3d(slots + j * 2 * UNIT, &P.wo[L & 1], bars + 8u * (B_PRE + j), ct * 128, ((early >> (4 * j)) & 15) * 64, 0);
            }
            __nanosleep(PRENS);
          }
        }
      }
    } else if (warp == 13) {
      ROLE_IDS
      uint32_t n = 16 + rank, dl = 0;
      uint32_t back = 0x44444444u;
      mbar_wait(bars + 8u * B_GO, 0);
      const unsigned ep1 = __shfl_sync(0xffffffffu, (*(volatile unsigned*)(g_flags + F_DONE)) / NCTA + 1u, 0);
#pragma unroll 1
      for (int sg = 4; sg < 34; sg++) {
        const int part = sg & 3, si = (sg >> 2) - (part & 1), L = si >> 1, ch = si & 1;
        const int k0 = part == 2 ? 2 * q_split(si) : 0, k1 = part == 0 ? 2 * q_split(si) : 16;
        if (part == 3 || k0 == k1) continue;
        const bool wj = part == 1;
        uint32_t seen = 0u;
        if (!wj && (L == 0 || __any_sync(0xffffffffu, mbar_test(bars + 8u * (B_XRDY + ch), (L & 1) ^ 1)))) {
          seen = 0xFFFFu;
          fence_proxy_async_all();
        }
        const CUtensorMap* map = wj ? &P.o : &P.xq[L == 0 ? 0 : 1];
        const unsigned* fl = g_flags + (wj ? F_O + (ch * 16 + rt) * OSTR : F_X + (ch * 8 + qr) * XSTR);
        const unsigned target = wj ? 4u * ep1 - 3u + L : 6u * ep1 - 6u + 2u * L;
        const int row = ch * 1024 + (wj ? rt * 64 : qr * 128);
        const bool pre = w_pre(si);
        uint64_t units = rank ? 0x0f050f050f050f05ull : 0x0a000a000a000a00ull;
        if (wj) {
          constexpr uint32_t b00 = (uint32_t)w_tab(2, 0, 0, 2, 8, 4), b01 = (uint32_t)w_tab(2, 0, 1, 2, 8, 4), b10 = (uint32_t)w_tab(2, 1, 0, 2, 8, 4),
                             b11 = (uint32_t)w_tab(2, 1, 1, 2, 8, 4), b20 = (uint32_t)w_tab(2, 2, 0, 2, 8, 4), b21 = (uint32_t)w_tab(2, 2, 1, 2, 8, 4);
          constexpr uint64_t u00 = w_tab(0, 0, 0, 2, 8, 8), u01 = w_tab(0, 0, 1, 2, 8, 8), u10 = w_tab(0, 1, 0, 2, 8, 8), u11 = w_tab(0, 1, 1, 2, 8, 8);
          back = pre ? (rank ? b11 : b10) : (si == 7 ? (rank ? b21 : b20) : (rank ? b01 : b00));
          units = pre ? (rank ? u11 : u10) : (rank ? u01 : u00);
        }
#pragma unroll 1
        for (int kt = k0 + rank; kt < k1; kt += 2, n += 2, back = (back >> 4) | 0x40000000u, units >>= 8) {
          wait_mask<false>(fl, 16, target, 1u << (wj ? kt : kt >> 1), seen, lane);
          const uint32_t nw = n - (back & 15u), pos = ((uint32_t)units & 31u) * UNIT + dl;
          mbar_wait(bars + 8u * (B_EMPTY + (nw & 7u)), (nw >> 3) & 1u);
          if (elect_one())
            tma_load_3d_mc(base + (pos >= 20 * UNIT ? pos - 20 * UNIT : pos), map, bars + 8u * (B_FULL + (n & 7u)), 0, row, kt);
        }
        if (wj ? !pre || PRE_FLIP : ((k1 - k0) & 2)) dl ^= 10u * UNIT;
        constexpr uint32_t q00 = q_backs(true, 0, false), q01 = q_backs(true, 1, false), q10 = q_backs(true, 0, true), q11 = q_backs(true, 1, true);
        if (wj) back = pre ? (rank ? q11 : q10) : (rank ? q01 : q00);
      }
    } else {
#pragma unroll 1
      for (int att = P.zero; att < 2; att++) {
        ROLE_IDS
#pragma unroll 1
        for (int s = 0; s < 4; s++) {
          if (elect_one()) {
            mbar_expect_tx(bars + 8u * (B_FULL + s), 5 * UNIT);
            tma_load_3d(base + s * 5 * UNIT, &P.xq[0], bars + 8u * (B_FULL + s), 0, qr * 128, s);
            tma_load_3d(base + (s * 5 + 2) * UNIT, &P.wqkv[0], bars + 8u * (B_FULL + s), hp * 64, s * 64, 0);
          }
        }
        if (att) break;
        asm volatile("barrier.cluster.wait.aligned;" ::: "memory");
        mbar_wait(bars + 8u * B_ROLE, 0);
        const int r = __shfl_sync(0xffffffffu, (int)lds32(base + OFF_ROLE), 0);
        if (r == role) break;
        role = r;
#pragma unroll 1
        for (int s = 0; s < 4; s++) {
          mbar_wait(bars + 8u * (B_FULL + s), 0);
          __syncwarp();
          if (elect_one()) {
            asm volatile("mbarrier.inval.shared::cta.b64 [%0];" ::"r"(sw(bars + 8u * (B_FULL + s))) : "memory");
            mbar_init(bars + 8u * (B_FULL + s), 1);
          }
        }
        fence_barrier_init();
        fence_proxy_async_smem();
        __syncwarp();
      }
      named_bar_arrive(0, 512);
      ROLE_IDS
#pragma unroll 1
      for (int s = 4; s < 16; s++) {
        const uint32_t fb = bars + 8u * (B_FULL + (s & 7)), sa = base + (s & 3) * 5 * UNIT;
        mbar_wait(bars + 8u * (B_EMPTY + ((s - 4) & 7)), ((s - 4) >> 3) & 1);
        if (elect_one()) {
          mbar_expect_tx(fb, 5 * UNIT);
          if ((s & 1) == rank) tma_load_3d_mc(sa, &P.xq[0], fb, 0, qr * 128, s);
          tma_load_3d(sa + 2 * UNIT, &P.wqkv[0], fb, hp * 64, s * 64, 0);
        }
      }
      if (elect_one()) mbar_arrive(bars + 8u * B_GO);
      const uint32_t wbase = sw(base), wbars = sw(bars);
      uint2 e = P.ptab[0];
#pragma unroll 1
      for (int i = 1; i <= NPT; i++) {
        const uint32_t wb = (e.x & 0x1f8u) | wbars, par = e.x >> 31, fl = e.x;
        uint32_t dst = (e.x & 0x3e000u) | wbase, fb = (e.y & 0x1f8u) | wbars, bytes = e.y & 0xe000u, nold = e.y & 1u;
        int c0 = (e.x & (1u << 29)) ? hp * 64 : ct * 128, c1 = ((e.x >> 18) & 0x7ffu) + ((e.x & (1u << 30)) ? rt * 64 : 0);
        const char* map = reinterpret_cast<const char*>(&P) + (e.y >> 21);
        asm volatile("" : "+r"(dst), "+r"(fb), "+r"(bytes), "+r"(nold), "+r"(c0), "+r"(c1), "+l"(map));
        e = P.ptab[i];
        if (fl & 2u) mbar_wait(bars + 8u * B_RESE, (fl >> 2) & 1u);
        if (!(fl & 1u)) mbar_wait_raw(wb, par);
        asm volatile(
            "{\n.reg .pred p, q;\nelect.sync _|p, 0xffffffff;\nsetp.eq.and.u32 q, %6, 0, p;\n"
            "@p mbarrier.arrive.expect_tx.shared::cta.b64 _, [%2], %5;\n"
            "@q cp.async.bulk.tensor.3d.shared::cluster.global.mbarrier::complete_tx::bytes [%0], [%1, {%3, %4, %7}], [%2];\n}\n" ::"r"(dst),
            "l"(map), "r"(fb), "r"(c0), "r"(c1), "r"(bytes), "r"(nold), "r"(0)
            : "memory");
      }
    }
    return;
    }
  }
  {
    {
      ROLE_IDS
      const unsigned ep1 = (*(volatile unsigned*)(g_flags + F_DONE)) / NCTA + 1u;
#pragma unroll 1
      for (int inst = 0; inst < 8; inst++) {
        const int L = inst >> 1, ch = inst & 1, gb = ch * 8 + qr;
        if (inst == 1) {
#pragma unroll 1
          for (int i = 0; i < 20; i++) {
            const char* src = i < 4 ? reinterpret_cast<const char*>(P.wo_p[0]) + (size_t)b * 16384 + i * 4096
                                    : (i < 16 ? reinterpret_cast<const char*>(P.wqkv_p1) + (size_t)b * 49152 + (i - 4) * 4096
                                              : reinterpret_cast<const char*>(P.wo_p[1]) + (size_t)b * 16384 + (i - 16) * 4096);
            asm volatile("prefetch.global.L2 [%0];" ::"l"(src + lane * 128));
            __nanosleep(TRICKLE);
          }
        }
        if (inst >= 2) {
        uint32_t seen = 0;
        wait_mask<true>(g_flags + F_X + gb * XSTR, 8, 6u * ep1 - 6u + 2u * L, 0xFFu, seen, lane);
        if (lane == 0) mbar_arrive(bars + 8u * (B_XRDY + ch));
#pragma unroll 1
        for (int h = 0; h < 4; h++) {
          const float4* sp = &g_stats[L][0][gb * 128 + h * 32 + lane];
          const float4 s0 = sum_recs<4>(sp, S_LEN, ep1), s1 = sum_recs<4>(sp + 4 * S_LEN, S_LEN, ep1);
          sts32(base + OFF_RS + (ch * 128 + h * 32 + lane) * 4, ln_params(s0.x + s1.x, s0.y + s1.y));
        }
        if (inst == 2) {
          mbar_wait(bars + 8u * B_CSD, 0);
#pragma unroll 1
          for (int hf = 0; hf < 2; hf++) {
            const float4* cp = &g_cs[1][hp][0][hf * 32 + lane];
            const float4 s0 = sum_recs<4>(cp, 64, ep1), s1 = sum_recs<4>(cp + 4 * 64, 64, ep1);
            cs_put(0, 1, hf * 32 + lane, s0.x + s1.x);
            cs_put(1, 1, hf * 32 + lane, s0.y + s1.y);
            cs_put(2, 1, hf * 32 + lane, s0.z + s1.z);
          }
          fence_proxy_async_smem();
        }
        __syncwarp();
        if (lane == 0) mbar_arrive(bars + 8u * (B_PREP + ch));
        }
        named_bar_sync((L & 1) ? 3 : 7, (L & 1) ? 192 : 160);
        if (elect_one()) {
          if (L & 1) {
            bulk_store(g_kvB[L >> 1][gb][hp], KB_ROW0 + 112 * 128, 2048);
            bulk_store(g_kvB[L >> 1][gb][hp] + 2048, VB_ROW0 + 112 * 128, 2048);
          } else {
#pragma unroll 1
            for (int o = 0, pc = (PCM >> inst) & 1 ? PCS : 16384; o < 16384; o += pc) {
              bulk_store(g_kvA[L >> 1][gb][hp][0] + o, slots + o, pc);
              if ((PCM >> inst) & 1) spin(PCN);
            }
          }
          bulk_commit();
          bulk_wait0();
          mbar_arrive(bars + 8u * B_KVS);
          STA(32);
          if ((L & 1) == 0) {
            announce(g_flags + F_KV + (gb * 16 + hp) * KSTR + 1);
          }
          STA(33);
        }
        __syncwarp();
      }
    }
  }
}

typedef CUresult (*PFN_tmEncode)(CUtensorMap*, CUtensorMapDataType, cuuint32_t, void*, const cuuint64_t*,
                                 const cuuint64_t*, const cuuint32_t*, const cuuint32_t*, CUtensorMapInterleave,
                                 CUtensorMapSwizzle, CUtensorMapL2promotion, CUtensorMapFloatOOBfill);

PFN_tmEncode get_encode_fn() {
  static PFN_tmEncode fn = nullptr;
  if (!fn) {
    cudaDriverEntryPointQueryResult qr;
    void* p = nullptr;
    cudaGetDriverEntryPoint("cuTensorMapEncodeTiled", &p, cudaEnableDefault, &qr);
    fn = (PFN_tmEncode)p;
  }
  return fn;
}

CUtensorMap make_map(const void* ptr, int rows, int cols, int inner, int blocks, int bs, int box_rows, int box_blk) {
  CUtensorMap m;
  cuuint64_t gdim[3] = {(cuuint64_t)inner, (cuuint64_t)rows, (cuuint64_t)blocks};
  cuuint64_t gstr[2] = {(cuuint64_t)cols * 2, (cuuint64_t)bs * 2};
  cuuint32_t box[3] = {64, (cuuint32_t)box_rows, (cuuint32_t)box_blk};
  cuuint32_t estr[3] = {1, 1, 1};
  get_encode_fn()(&m, CU_TENSOR_MAP_DATA_TYPE_BFLOAT16, 3, const_cast<void*>(ptr), gdim, gstr, box, estr,
                  CU_TENSOR_MAP_INTERLEAVE_NONE, CU_TENSOR_MAP_SWIZZLE_128B, CU_TENSOR_MAP_L2_PROMOTION_L2_128B,
                  CU_TENSOR_MAP_FLOAT_OOB_FILL_NONE);
  return m;
}

void make_tables(Params& P) {
  const WPlan pl[3] = {w_plan(0), w_plan(1), w_plan(2)};
  for (int m = 0; m < 4; m++)
    for (int kt = 0; kt < 17; kt++) {
      const WPlan& p = pl[m >> 1];
      const uint32_t dl = (m & 1) * 10u * UNIT;
      P.wtab[m][kt] = make_uint2(kt == 16 ? SBASE + unit_off(p.v[1][kt], dl) : ((SBASE + unit_off(p.v[0][kt], dl)) >> 4) + 0x10000u,
                                 ((SBASE + unit_off(p.v[1][kt], dl)) >> 4) + ((UNIT >> 4) << 16));
    }
  int np = 0;
  auto put = [&](int nw, int rp, uint32_t off, int c1, int kind, int fb, int units, const CUtensorMap* map) {
    P.ptab[np++] = make_uint2((nw < 0 ? 1u : 8u * ((LOCE ? B_LOC : B_EMPTY) + (nw & 7)) | (uint32_t)((nw >> 3) & 1) << 31) | (rp < 0 ? 0u : 2u | 4u * rp) |
                                  off | (uint32_t)c1 << 18 | (uint32_t)kind << 29,
                              8u * fb | (map ? 0u : 1u) | units * UNIT |
                                  (map ? (uint32_t)(reinterpret_cast<const char*>(map) - reinterpret_cast<const char*>(&P)) << 21 : 0u));
  };
  int n = 16, aw = 0;
  uint32_t dl = 0;
  uint32_t back = 0x44444444u;
  for (int sg = 4; sg < 34; sg++) {
    const int part = sg & 3, si = (sg >> 2) - (part & 1), L = si >> 1, ch = si & 1;
    const int k0 = part == 2 ? 2 * q_split(si) : 0, k1 = part == 0 ? 2 * q_split(si) : 16;
    if (part == 3) continue;
    if (part != 1) {
      for (int k2 = k0; k2 < k1; k2 += 2, aw--, dl ^= 10u * UNIT)
        for (int ks = 0; ks < 2; ks++, n++, back = (back >> 4) | 0x40000000u)
          put(n - (int)(back & 15u), ks == 1 && aw == 1 ? (part == 2) ^ ch : -1, (ks * 5 + 2) * UNIT + dl, (k2 + ks) * 64, 1,
              B_FULL + (n & 7), 5, &P.wqkv[L & 1]);
    } else {
      const bool pre = w_pre(si);
      const WPlan& p = pl[pre ? 1 : (aw == 2 ? 2 : 0)];
      for (int kt = 0; kt < 17; kt++) {
        const bool early = kt < 16 && p.v[5][kt];
        put(p.v[4][kt] ? n + kt - p.v[3][kt] : -1, !pre && kt == 6 && aw == 2 ? ch ^ 1 : -1, unit_off(p.v[1][kt], dl),
            kt == 16 ? ch * 1024 : kt * 64, kt == 16 ? 2 : 0, kt == 16 ? B_RESF : B_FULL + ((n + kt) & 7),
            kt == 16 ? 2 : (early ? 1 : 3), kt == 16 ? &P.xr[L == 0 ? 0 : 1] : (early ? nullptr : &P.wo[L & 1]));
      }
      n += 16;
      if (!pre || PRE_FLIP) dl ^= 10u * UNIT;
      back = q_backs(false, 0, pre);
      aw = 2;
    }
  }
  P.ptab[np] = make_uint2(0, 0);
}

}

extern "C" void kernel_launch(void* const* d_in, const int* in_sizes, int n_in, void* d_out, int out_size) {
  (void)in_sizes; (void)n_in; (void)out_size;
  void *p_o, *p_x;
  cudaGetSymbolAddress(&p_o, g_o);
  cudaGetSymbolAddress(&p_x, g_x);
  static bool attr_done = false;
  if (!attr_done) {
    cudaFuncSetAttribute(fused_kernel, cudaFuncAttributeMaxDynamicSharedMemorySize, SMEM_BYTES);
    attr_done = true;
  }
  Params P;
  P.in_x = (const __nv_bfloat16*)d_in[0];
  P.wo_p[0] = (const __nv_bfloat16*)d_in[2];
  P.wqkv_p1 = (const __nv_bfloat16*)d_in[4];
  P.wo_p[1] = (const __nv_bfloat16*)d_in[5];
  P.zero = 0;
  P.xq[0] = make_map(P.in_x, S_LEN, DM, 64, 16, 64, 128, 1);
  P.xq[1] = make_map(p_x, S_LEN, DM, 64, 16, 64, 128, 1);
  P.xr[0] = make_map(P.in_x, S_LEN, DM, DM - 64, 2, 64, 64, 2);
  P.xr[1] = make_map(p_x, S_LEN, DM, DM - 64, 2, 64, 64, 2);
  P.xr[2] = make_map(d_out, S_LEN, DM, DM - 64, 2, 64, 64, 2);
  P.o = make_map(p_o, S_LEN, DM, 64, 16, 64, 64, 1);
  for (int t = 0; t < 2; t++) {
    P.wqkv[t] = make_map(d_in[3 * t + 1], DM, NQKV, 1024, 3, 1024, 64, 3);
    P.wo[t] = make_map(P.wo_p[t], DM, DM, DM - 64, 2, 64, 64, 2);
  }
  make_tables(P);
  fused_kernel<<<NCTA, 512, SMEM_BYTES>>>(P);
}
```

```cpp
#include <cuda_runtime.h>
#include <cuda_bf16.h>
#include <cuda.h>
#include <stdint.h>
#include <type_traits>

namespace {

constexpr int S_LEN = 2048;
constexpr int DM = 1024;
constexpr int NQKV = 3072;
constexpr int NCTA = 128;

__device__ __align__(1024) uint8_t g_kvA[2][16][16][2][16384];
__device__ __align__(1024) uint8_t g_kvB[2][16][16][4096];
__device__ __align__(1024) uint8_t g_zero[16384];
__device__ __align__(1024) __nv_bfloat16 g_o[S_LEN * DM];
__device__ __align__(1024) __nv_bfloat16 g_x[S_LEN * DM];
__device__ __align__(1024) float4 g_stats[4][8][S_LEN];
__device__ __align__(1024) float4 g_cs[2][16][8][64];
#define RSTR 1
constexpr int F_X = 0;
constexpr int XSTR = 32, OSTR = 32, KSTR = 32;
constexpr int F_O = F_X + 16 * XSTR;
constexpr int F_KV = F_O + 16 * OSTR;
constexpr int F_DONE = F_KV + 256 * KSTR;
constexpr int F_ROLE = F_DONE + 32;
__device__ __align__(1024) unsigned g_flags[F_ROLE + 64 * RSTR];

constexpr uint32_t SBASE = 1024;
constexpr int UNIT = 8192;
constexpr int NUNITS = 20;
constexpr int OFF_SLOT = NUNITS * UNIT;
constexpr int OFF_CS = OFF_SLOT + 4 * 16384;
constexpr int OFF_RS = OFF_CS + 1536;
constexpr int OFF_BAR = OFF_RS + 1024;
constexpr int OFF_EPOCH = OFF_BAR + 400, OFF_ROLE = OFF_BAR + 404;
constexpr int OFF_TS = OFF_BAR + 408;
constexpr int SMEM_BYTES = OFF_TS;
constexpr int B_FULL = 0, B_EMPTY = 8, B_PREP = 16, B_HALO = 18, B_REL = 22, B_AFREE = 25, B_TURN = 26, B_XRDY = 28,
              B_CS = 30, B_CSD = 31, B_GO = 32, B_RESF = 33, B_RESE = 34, B_PRE = 35, B_ROLE = 39, B_LOC = 40, B_HB = 48, B_KVS = 49;

__device__ __forceinline__ uint32_t smem_u32(const void* p) { return (uint32_t)__cvta_generic_to_shared(p); }
extern __shared__ __align__(1024) uint8_t smem_raw[];
__device__ __forceinline__ uint32_t sw(uint32_t a) {
  uint32_t r;
  asm volatile("add.u32 %0, %1, %2;" : "=r"(r) : "r"(a), "r"(smem_u32(smem_raw) - SBASE));
  return r;
}

__device__ __forceinline__ void mbar_init(uint32_t bar, uint32_t cnt) {
  asm volatile("mbarrier.init.shared::cta.b64 [%0], %1;" ::"r"(sw(bar)), "r"(cnt));
}
__device__ __forceinline__ void mbar_expect_tx(uint32_t bar, uint32_t bytes) {
  asm volatile("mbarrier.arrive.expect_tx.shared::cta.b64 _, [%0], %1;" ::"r"(sw(bar)), "r"(bytes) : "memory");
}
__device__ __forceinline__ void mbar_arrive(uint32_t bar) {
  asm volatile("mbarrier.arrive.shared::cta.b64 _, [%0];" ::"r"(sw(bar)) : "memory");
}
__device__ __forceinline__ void warp_arrive(uint32_t bar, bool cond = true) {
  asm volatile("{\n.reg .pred p;\nelect.sync _|p, 0xffffffff;\nsetp.ne.and.b32 p, %1, 0, p;\n"
               "@p mbarrier.arrive.shared::cta.b64 _, [%0];\n}\n" ::"r"(sw(bar)), "r"((uint32_t)cond) : "memory");
}
__device__ __forceinline__ void warp_arrive_cl(uint32_t bar, bool cond = true) {
  asm volatile("{\n.reg .pred p;\nelect.sync _|p, 0xffffffff;\nsetp.ne.and.b32 p, %1, 0, p;\n"
               "@p mbarrier.arrive.shared::cluster.b64 _, [%0];\n}\n" ::"r"(bar), "r"((uint32_t)cond) : "memory");
}
__device__ __forceinline__ bool mbar_try_wait(uint32_t bar, uint32_t parity) {
  uint32_t ok;
  asm volatile(
      "{\n.reg .pred p;\nmbarrier.try_wait.parity.shared::cta.b64 p, [%1], %2;\nselp.b32 %0, 1, 0, p;\n}\n"
      : "=r"(ok)
      : "r"(sw(bar)), "r"(parity)
      : "memory");
  return ok != 0;
}
__device__ __forceinline__ bool mbar_test(uint32_t bar, uint32_t parity) {
  uint32_t ok;
  asm volatile(
      "{\n.reg .pred p;\nmbarrier.test_wait.parity.shared::cta.b64 p, [%1], %2;\nselp.b32 %0, 1, 0, p;\n}\n"
      : "=r"(ok)
      : "r"(sw(bar)), "r"(parity)
      : "memory");
  return ok != 0;
}
__device__ __forceinline__ void mbar_wait(uint32_t bar, uint32_t parity) {
#pragma unroll 1
  for (uint32_t it = 0; it < (1u << 18); ++it) {
    if (mbar_try_wait(bar, parity)) return;
  }
}
__device__ __forceinline__ void mbar_wait_raw(uint32_t bar, uint32_t parity) {
#pragma unroll 1
  for (uint32_t it = 0; it < (1u << 18); ++it) {
    uint32_t ok;
    asm volatile(
        "{\n.reg .pred p;\nmbarrier.try_wait.parity.shared::cta.b64 p, [%1], %2;\nselp.b32 %0, 1, 0, p;\n}\n"
        : "=r"(ok)
        : "r"(bar), "r"(parity)
        : "memory");
    if (ok) return;
  }
}
__device__ __forceinline__ void spin(uint32_t cyc) {
  uint32_t c0, c;
  asm volatile("mov.u32 %0, %%clock;" : "=r"(c0));
  do { asm volatile("mov.u32 %0, %%clock;" : "=r"(c)); } while (c - c0 < cyc);
}
__device__ __forceinline__ void mbar_pace(uint32_t bar, uint32_t parity) {
#pragma unroll 1
  for (uint32_t it = 0; it < 24; ++it) {
    if (mbar_try_wait(bar, parity)) return;
  }
}
template <int NS>
__device__ __forceinline__ void mbar_wait_lazy(uint32_t bar, uint32_t parity) {
#pragma unroll 1
  for (uint32_t it = 0; it < (1u << 18); ++it) {
    if (mbar_try_wait(bar, parity)) return;
    __nanosleep(NS);
  }
}
__device__ __forceinline__ bool elect_one() {
  uint32_t ok;
  asm volatile("{\n.reg .pred p;\nelect.sync _|p, 0xffffffff;\nselp.b32 %0, 1, 0, p;\n}\n" : "=r"(ok));
  return ok != 0;
}
__device__ __forceinline__ void fence_barrier_init() { asm volatile("fence.mbarrier_init.release.cluster;" ::: "memory"); }
__device__ __forceinline__ void fence_proxy_async_smem() { asm volatile("fence.proxy.async.shared::cta;" ::: "memory"); }
__device__ __forceinline__ void fence_proxy_async_all() { asm volatile("fence.proxy.async.global;" ::: "memory"); }

__device__ __forceinline__ void tma_load_3d(uint32_t dst, const CUtensorMap* map, uint32_t bar, int c0, int c1, int c2) {
  asm volatile(
      "cp.async.bulk.tensor.3d.shared::cluster.global.mbarrier::complete_tx::bytes [%0], [%1, {%3, %4, %5}], [%2];" ::"r"(sw(dst)),
      "l"(map), "r"(sw(bar)), "r"(c0), "r"(c1), "r"(c2)
      : "memory");
}
__device__ __forceinline__ void tma_load_3d_mc(uint32_t dst, const CUtensorMap* map, uint32_t bar, int c0, int c1, int c2) {
  asm volatile(
      "cp.async.bulk.tensor.3d.shared::cluster.global.mbarrier::complete_tx::bytes.multicast::cluster [%0], [%1, {%3, %4, %5}], [%2], %6;" ::"r"(sw(dst)),
      "l"(map), "r"(sw(bar)), "r"(c0), "r"(c1), "r"(c2), "h"((unsigned short)3)
      : "memory");
}
__device__ __forceinline__ void bulk_load(uint32_t dst, const void* src, uint32_t bytes, uint32_t bar) {
  asm volatile("cp.async.bulk.shared::cluster.global.mbarrier::complete_tx::bytes [%0], [%1], %2, [%3];" ::"r"(sw(dst)),
               "l"(src), "r"(bytes), "r"(sw(bar))
               : "memory");
}
__device__ __forceinline__ void bulk_store(void* dst, uint32_t src, uint32_t bytes) {
  asm volatile("cp.async.bulk.global.shared::cta.bulk_group [%0], [%1], %2;" ::"l"(dst), "r"(sw(src)), "r"(bytes) : "memory");
}
__device__ __forceinline__ void tma_store_3d(const CUtensorMap* map, uint32_t src, int c0, int c1, int c2) {
  asm volatile("cp.async.bulk.tensor.3d.global.shared::cta.bulk_group [%0, {%2, %3, %4}], [%1];" ::"l"(map), "r"(sw(src)),
               "r"(c0), "r"(c1), "r"(c2)
               : "memory");
}
__device__ __forceinline__ void bulk_commit() { asm volatile("cp.async.bulk.commit_group;" ::: "memory"); }
__device__ __forceinline__ void bulk_wait_read0() { asm volatile("cp.async.bulk.wait_group.read 0;" ::: "memory"); }
__device__ __forceinline__ void bulk_wait0() { asm volatile("cp.async.bulk.wait_group 0;" ::: "memory"); }
__device__ __forceinline__ void named_bar_sync(int id, int nthreads) {
  asm volatile("bar.sync %0, %1;" ::"r"(id), "r"(nthreads) : "memory");
}
__device__ __forceinline__ void named_bar_arrive(int id, int nthreads) {
  asm volatile("bar.arrive %0, %1;" ::"r"(id), "r"(nthreads) : "memory");
}

__device__ __forceinline__ void wgmma_fence() { asm volatile("wgmma.fence.sync.aligned;\n" ::: "memory"); }
__device__ __forceinline__ void wgmma_commit() { asm volatile("wgmma.commit_group.sync.aligned;\n" ::: "memory"); }
template <int N>
__device__ __forceinline__ void wgmma_wait() {
  asm volatile("wgmma.wait_group.sync.aligned %0;\n" ::"n"(N) : "memory");
}
template <int R>
__device__ __forceinline__ void setmaxnreg_inc() { asm volatile("setmaxnreg.inc.sync.aligned.u32 %0;\n" ::"n"(R)); }
template <int R>
__device__ __forceinline__ void setmaxnreg_dec() { asm volatile("setmaxnreg.dec.sync.aligned.u32 %0;\n" ::"n"(R)); }
template <int N>
__device__ __forceinline__ void reg_fence(float* r) {
#pragma unroll
  for (int i = 0; i < N; i++) asm volatile("" : "+f"(r[i])::"memory");
}

template <int N>
__device__ __forceinline__ void reg_define(float* r) {
#pragma unroll
  for (int i = 0; i < N; i++) r[i] = 0.f;
}

__device__ __forceinline__ uint64_t desc_lo(uint32_t lo) {
  uint64_t d;
  asm("mov.b64 %0, {%1, %2};" : "=l"(d) : "r"(lo), "r"(0x40000040u));
  return d;
}
__device__ __forceinline__ uint64_t make_desc(uint32_t addr, uint32_t lbo_bytes) {
  return desc_lo((addr >> 4) + ((lbo_bytes >> 4) << 16));
}

__device__ __forceinline__ void wgmma_n192_ss_ta0_tb1(float* d, uint64_t descA, uint64_t descB, int scaleD) {
  asm volatile("{\n.reg .pred p;\nsetp.ne.b32 p, %98, 0;\n"
    "wgmma.mma_async.sync.aligned.m64n192k16.f32.bf16.bf16 {%0, %1, %2, %3, %4, %5, %6, %7, %8, %9, %10, %11, %12, %13, %14, %15, %16, %17, %18, %19, %20, %21, %22, %23, %24, %25, %26, %27, %28, %29, %30, %31, %32, %33, %34, %35, %36, %37, %38, %39, %40, %41, %42, %43, %44, %45, %46, %47, %48, %49, %50, %51, %52, %53, %54, %55, %56, %57, %58, %59, %60, %61, %62, %63, %64, %65, %66, %67, %68, %69, %70, %71, %72, %73, %74, %75, %76, %77, %78, %79, %80, %81, %82, %83, %84, %85, %86, %87, %88, %89, %90, %91, %92, %93, %94, %95}, %96, %97, p, 1, 1, 0, 1;\n}\n"
    : "+f"(d[0]), "+f"(d[1]), "+f"(d[2]), "+f"(d[3]), "+f"(d[4]), "+f"(d[5]), "+f"(d[6]), "+f"(d[7]), "+f"(d[8]), "+f"(d[9]), "+f"(d[10]), "+f"(d[11]), "+f"(d[12]), "+f"(d[13]), "+f"(d[14]), "+f"(d[15]), "+f"(d[16]), "+f"(d[17]), "+f"(d[18]), "+f"(d[19]), "+f"(d[20]), "+f"(d[21]), "+f"(d[22]), "+f"(d[23]), "+f"(d[24]), "+f"(d[25]), "+f"(d[26]), "+f"(d[27]), "+f"(d[28]), "+f"(d[29]), "+f"(d[30]), "+f"(d[31]), "+f"(d[32]), "+f"(d[33]), "+f"(d[34]), "+f"(d[35]), "+f"(d[36]), "+f"(d[37]), "+f"(d[38]), "+f"(d[39]), "+f"(d[40]), "+f"(d[41]), "+f"(d[42]), "+f"(d[43]), "+f"(d[44]), "+f"(d[45]), "+f"(d[46]), "+f"(d[47]), "+f"(d[48]), "+f"(d[49]), "+f"(d[50]), "+f"(d[51]), "+f"(d[52]), "+f"(d[53]), "+f"(d[54]), "+f"(d[55]), "+f"(d[56]), "+f"(d[57]), "+f"(d[58]), "+f"(d[59]), "+f"(d[60]), "+f"(d[61]), "+f"(d[62]), "+f"(d[63]), "+f"(d[64]), "+f"(d[65]), "+f"(d[66]), "+f"(d[67]), "+f"(d[68]), "+f"(d[69]), "+f"(d[70]), "+f"(d[71]), "+f"(d[72]), "+f"(d[73]), "+f"(d[74]), "+f"(d[75]), "+f"(d[76]), "+f"(d[77]), "+f"(d[78]), "+f"(d[79]), "+f"(d[80]), "+f"(d[81]), "+f"(d[82]), "+f"(d[83]), "+f"(d[84]), "+f"(d[85]), "+f"(d[86]), "+f"(d[87]), "+f"(d[88]), "+f"(d[89]), "+f"(d[90]), "+f"(d[91]), "+f"(d[92]), "+f"(d[93]), "+f"(d[94]), "+f"(d[95])
    : "l"(descA), "l"(descB), "r"(scaleD));
}

__device__ __forceinline__ void wgmma_n128_ss_ta0_tb1(float* d, uint64_t descA, uint64_t descB, int scaleD) {
  asm volatile("{\n.reg .pred p;\nsetp.ne.b32 p, %66, 0;\n"
    "wgmma.mma_async.sync.aligned.m64n128k16.f32.bf16.bf16 {%0, %1, %2, %3, %4, %5, %6, %7, %8, %9, %10, %11, %12, %13, %14, %15, %16, %17, %18, %19, %20, %21, %22, %23, %24, %25, %26, %27, %28, %29, %30, %31, %32, %33, %34, %35, %36, %37, %38, %39, %40, %41, %42, %43, %44, %45, %46, %47, %48, %49, %50, %51, %52, %53, %54, %55, %56, %57, %58, %59, %60, %61, %62, %63}, %64, %65, p, 1, 1, 0, 1;\n}\n"
    : "+f"(d[0]), "+f"(d[1]), "+f"(d[2]), "+f"(d[3]), "+f"(d[4]), "+f"(d[5]), "+f"(d[6]), "+f"(d[7]), "+f"(d[8]), "+f"(d[9]), "+f"(d[10]), "+f"(d[11]), "+f"(d[12]), "+f"(d[13]), "+f"(d[14]), "+f"(d[15]), "+f"(d[16]), "+f"(d[17]), "+f"(d[18]), "+f"(d[19]), "+f"(d[20]), "+f"(d[21]), "+f"(d[22]), "+f"(d[23]), "+f"(d[24]), "+f"(d[25]), "+f"(d[26]), "+f"(d[27]), "+f"(d[28]), "+f"(d[29]), "+f"(d[30]), "+f"(d[31]), "+f"(d[32]), "+f"(d[33]), "+f"(d[34]), "+f"(d[35]), "+f"(d[36]), "+f"(d[37]), "+f"(d[38]), "+f"(d[39]), "+f"(d[40]), "+f"(d[41]), "+f"(d[42]), "+f"(d[43]), "+f"(d[44]), "+f"(d[45]), "+f"(d[46]), "+f"(d[47]), "+f"(d[48]), "+f"(d[49]), "+f"(d[50]), "+f"(d[51]), "+f"(d[52]), "+f"(d[53]), "+f"(d[54]), "+f"(d[55]), "+f"(d[56]), "+f"(d[57]), "+f"(d[58]), "+f"(d[59]), "+f"(d[60]), "+f"(d[61]), "+f"(d[62]), "+f"(d[63])
    : "l"(descA), "l"(descB), "r"(scaleD));
}

__device__ __forceinline__ void wgmma_n192_ssz_ta0_tb1(float* d, uint64_t descA, uint64_t descB) {
  asm volatile("{\n.reg .pred p;\nsetp.ne.b32 p, 0, 0;\n"
    "wgmma.mma_async.sync.aligned.m64n192k16.f32.bf16.bf16 {%0, %1, %2, %3, %4, %5, %6, %7, %8, %9, %10, %11, %12, %13, %14, %15, %16, %17, %18, %19, %20, %21, %22, %23, %24, %25, %26, %27, %28, %29, %30, %31, %32, %33, %34, %35, %36, %37, %38, %39, %40, %41, %42, %43, %44, %45, %46, %47, %48, %49, %50, %51, %52, %53, %54, %55, %56, %57, %58, %59, %60, %61, %62, %63, %64, %65, %66, %67, %68, %69, %70, %71, %72, %73, %74, %75, %76, %77, %78, %79, %80, %81, %82, %83, %84, %85, %86, %87, %88, %89, %90, %91, %92, %93, %94, %95}, %96, %97, p, 1, 1, 0, 1;\n}\n"
    : "=f"(d[0]), "=f"(d[1]), "=f"(d[2]), "=f"(d[3]), "=f"(d[4]), "=f"(d[5]), "=f"(d[6]), "=f"(d[7]), "=f"(d[8]), "=f"(d[9]), "=f"(d[10]), "=f"(d[11]), "=f"(d[12]), "=f"(d[13]), "=f"(d[14]), "=f"(d[15]), "=f"(d[16]), "=f"(d[17]), "=f"(d[18]), "=f"(d[19]), "=f"(d[20]), "=f"(d[21]), "=f"(d[22]), "=f"(d[23]), "=f"(d[24]), "=f"(d[25]), "=f"(d[26]), "=f"(d[27]), "=f"(d[28]), "=f"(d[29]), "=f"(d[30]), "=f"(d[31]), "=f"(d[32]), "=f"(d[33]), "=f"(d[34]), "=f"(d[35]), "=f"(d[36]), "=f"(d[37]), "=f"(d[38]), "=f"(d[39]), "=f"(d[40]), "=f"(d[41]), "=f"(d[42]), "=f"(d[43]), "=f"(d[44]), "=f"(d[45]), "=f"(d[46]), "=f"(d[47]), "=f"(d[48]), "=f"(d[49]), "=f"(d[50]), "=f"(d[51]), "=f"(d[52]), "=f"(d[53]), "=f"(d[54]), "=f"(d[55]), "=f"(d[56]), "=f"(d[57]), "=f"(d[58]), "=f"(d[59]), "=f"(d[60]), "=f"(d[61]), "=f"(d[62]), "=f"(d[63]), "=f"(d[64]), "=f"(d[65]), "=f"(d[66]), "=f"(d[67]), "=f"(d[68]), "=f"(d[69]), "=f"(d[70]), "=f"(d[71]), "=f"(d[72]), "=f"(d[73]), "=f"(d[74]), "=f"(d[75]), "=f"(d[76]), "=f"(d[77]), "=f"(d[78]), "=f"(d[79]), "=f"(d[80]), "=f"(d[81]), "=f"(d[82]), "=f"(d[83]), "=f"(d[84]), "=f"(d[85]), "=f"(d[86]), "=f"(d[87]), "=f"(d[88]), "=f"(d[89]), "=f"(d[90]), "=f"(d[91]), "=f"(d[92]), "=f"(d[93]), "=f"(d[94]), "=f"(d[95])
    : "l"(descA), "l"(descB));
}

__device__ __forceinline__ void wgmma_n192_rs_tb1(float* d, uint32_t a0, uint32_t a1, uint64_t descB) {
  asm volatile("{\n.reg .pred p;\nsetp.eq.b32 p, 0, 0;\n"
    "wgmma.mma_async.sync.aligned.m64n192k16.f32.bf16.bf16 {%0, %1, %2, %3, %4, %5, %6, %7, %8, %9, %10, %11, %12, %13, %14, %15, %16, %17, %18, %19, %20, %21, %22, %23, %24, %25, %26, %27, %28, %29, %30, %31, %32, %33, %34, %35, %36, %37, %38, %39, %40, %41, %42, %43, %44, %45, %46, %47, %48, %49, %50, %51, %52, %53, %54, %55, %56, %57, %58, %59, %60, %61, %62, %63, %64, %65, %66, %67, %68, %69, %70, %71, %72, %73, %74, %75, %76, %77, %78, %79, %80, %81, %82, %83, %84, %85, %86, %87, %88, %89, %90, %91, %92, %93, %94, %95}, {%96, %97, %98, %98}, %99, p, 1, 1, 1;\n}\n"
    : "+f"(d[0]), "+f"(d[1]), "+f"(d[2]), "+f"(d[3]), "+f"(d[4]), "+f"(d[5]), "+f"(d[6]), "+f"(d[7]), "+f"(d[8]), "+f"(d[9]), "+f"(d[10]), "+f"(d[11]), "+f"(d[12]), "+f"(d[13]), "+f"(d[14]), "+f"(d[15]), "+f"(d[16]), "+f"(d[17]), "+f"(d[18]), "+f"(d[19]), "+f"(d[20]), "+f"(d[21]), "+f"(d[22]), "+f"(d[23]), "+f"(d[24]), "+f"(d[25]), "+f"(d[26]), "+f"(d[27]), "+f"(d[28]), "+f"(d[29]), "+f"(d[30]), "+f"(d[31]), "+f"(d[32]), "+f"(d[33]), "+f"(d[34]), "+f"(d[35]), "+f"(d[36]), "+f"(d[37]), "+f"(d[38]), "+f"(d[39]), "+f"(d[40]), "+f"(d[41]), "+f"(d[42]), "+f"(d[43]), "+f"(d[44]), "+f"(d[45]), "+f"(d[46]), "+f"(d[47]), "+f"(d[48]), "+f"(d[49]), "+f"(d[50]), "+f"(d[51]), "+f"(d[52]), "+f"(d[53]), "+f"(d[54]), "+f"(d[55]), "+f"(d[56]), "+f"(d[57]), "+f"(d[58]), "+f"(d[59]), "+f"(d[60]), "+f"(d[61]), "+f"(d[62]), "+f"(d[63]), "+f"(d[64]), "+f"(d[65]), "+f"(d[66]), "+f"(d[67]), "+f"(d[68]), "+f"(d[69]), "+f"(d[70]), "+f"(d[71]), "+f"(d[72]), "+f"(d[73]), "+f"(d[74]), "+f"(d[75]), "+f"(d[76]), "+f"(d[77]), "+f"(d[78]), "+f"(d[79]), "+f"(d[80]), "+f"(d[81]), "+f"(d[82]), "+f"(d[83]), "+f"(d[84]), "+f"(d[85]), "+f"(d[86]), "+f"(d[87]), "+f"(d[88]), "+f"(d[89]), "+f"(d[90]), "+f"(d[91]), "+f"(d[92]), "+f"(d[93]), "+f"(d[94]), "+f"(d[95])
    : "r"(a0), "r"(a1), "r"(0u), "l"(descB));
}

__device__ __forceinline__ void wgmma_n128_ssz_ta0_tb1(float* d, uint64_t descA, uint64_t descB) {
  asm volatile("{\n.reg .pred p;\nsetp.ne.b32 p, 0, 0;\n"
    "wgmma.mma_async.sync.aligned.m64n128k16.f32.bf16.bf16 {%0, %1, %2, %3, %4, %5, %6, %7, %8, %9, %10, %11, %12, %13, %14, %15, %16, %17, %18, %19, %20, %21, %22, %23, %24, %25, %26, %27, %28, %29, %30, %31, %32, %33, %34, %35, %36, %37, %38, %39, %40, %41, %42, %43, %44, %45, %46, %47, %48, %49, %50, %51, %52, %53, %54, %55, %56, %57, %58, %59, %60, %61, %62, %63}, %64, %65, p, 1, 1, 0, 1;\n}\n"
    : "=f"(d[0]), "=f"(d[1]), "=f"(d[2]), "=f"(d[3]), "=f"(d[4]), "=f"(d[5]), "=f"(d[6]), "=f"(d[7]), "=f"(d[8]), "=f"(d[9]), "=f"(d[10]), "=f"(d[11]), "=f"(d[12]), "=f"(d[13]), "=f"(d[14]), "=f"(d[15]), "=f"(d[16]), "=f"(d[17]), "=f"(d[18]), "=f"(d[19]), "=f"(d[20]), "=f"(d[21]), "=f"(d[22]), "=f"(d[23]), "=f"(d[24]), "=f"(d[25]), "=f"(d[26]), "=f"(d[27]), "=f"(d[28]), "=f"(d[29]), "=f"(d[30]), "=f"(d[31]), "=f"(d[32]), "=f"(d[33]), "=f"(d[34]), "=f"(d[35]), "=f"(d[36]), "=f"(d[37]), "=f"(d[38]), "=f"(d[39]), "=f"(d[40]), "=f"(d[41]), "=f"(d[42]), "=f"(d[43]), "=f"(d[44]), "=f"(d[45]), "=f"(d[46]), "=f"(d[47]), "=f"(d[48]), "=f"(d[49]), "=f"(d[50]), "=f"(d[51]), "=f"(d[52]), "=f"(d[53]), "=f"(d[54]), "=f"(d[55]), "=f"(d[56]), "=f"(d[57]), "=f"(d[58]), "=f"(d[59]), "=f"(d[60]), "=f"(d[61]), "=f"(d[62]), "=f"(d[63])
    : "l"(descA), "l"(descB));
}

__device__ __forceinline__ void wgmma_n64_ss_ta0_tb0(float* d, uint64_t descA, uint64_t descB, int scaleD) {
  asm volatile("{\n.reg .pred p;\nsetp.ne.b32 p, %34, 0;\n"
    "wgmma.mma_async.sync.aligned.m64n64k16.f32.bf16.bf16 {%0, %1, %2, %3, %4, %5, %6, %7, %8, %9, %10, %11, %12, %13, %14, %15, %16, %17, %18, %19, %20, %21, %22, %23, %24, %25, %26, %27, %28, %29, %30, %31}, %32, %33, p, 1, 1, 0, 0;\n}\n"
    : "+f"(d[0]), "+f"(d[1]), "+f"(d[2]), "+f"(d[3]), "+f"(d[4]), "+f"(d[5]), "+f"(d[6]), "+f"(d[7]), "+f"(d[8]), "+f"(d[9]), "+f"(d[10]), "+f"(d[11]), "+f"(d[12]), "+f"(d[13]), "+f"(d[14]), "+f"(d[15]), "+f"(d[16]), "+f"(d[17]), "+f"(d[18]), "+f"(d[19]), "+f"(d[20]), "+f"(d[21]), "+f"(d[22]), "+f"(d[23]), "+f"(d[24]), "+f"(d[25]), "+f"(d[26]), "+f"(d[27]), "+f"(d[28]), "+f"(d[29]), "+f"(d[30]), "+f"(d[31])
    : "l"(descA), "l"(descB), "r"(scaleD));
}

__device__ __forceinline__ void wgmma_n64_ssz_ta0_tb0(float* d, uint64_t descA, uint64_t descB) {
  asm volatile("{\n.reg .pred p;\nsetp.ne.b32 p, 0, 0;\n"
    "wgmma.mma_async.sync.aligned.m64n64k16.f32.bf16.bf16 {%0, %1, %2, %3, %4, %5, %6, %7, %8, %9, %10, %11, %12, %13, %14, %15, %16, %17, %18, %19, %20, %21, %22, %23, %24, %25, %26, %27, %28, %29, %30, %31}, %32, %33, p, 1, 1, 0, 0;\n}\n"
    : "=f"(d[0]), "=f"(d[1]), "=f"(d[2]), "=f"(d[3]), "=f"(d[4]), "=f"(d[5]), "=f"(d[6]), "=f"(d[7]), "=f"(d[8]), "=f"(d[9]), "=f"(d[10]), "=f"(d[11]), "=f"(d[12]), "=f"(d[13]), "=f"(d[14]), "=f"(d[15]), "=f"(d[16]), "=f"(d[17]), "=f"(d[18]), "=f"(d[19]), "=f"(d[20]), "=f"(d[21]), "=f"(d[22]), "=f"(d[23]), "=f"(d[24]), "=f"(d[25]), "=f"(d[26]), "=f"(d[27]), "=f"(d[28]), "=f"(d[29]), "=f"(d[30]), "=f"(d[31])
    : "l"(descA), "l"(descB));
}

__device__ __forceinline__ void wgmma_n80_ss_ta0_tb0(float* d, uint64_t descA, uint64_t descB, int scaleD) {
  asm volatile("{\n.reg .pred p;\nsetp.ne.b32 p, %42, 0;\n"
    "wgmma.mma_async.sync.aligned.m64n80k16.f32.bf16.bf16 {%0, %1, %2, %3, %4, %5, %6, %7, %8, %9, %10, %11, %12, %13, %14, %15, %16, %17, %18, %19, %20, %21, %22, %23, %24, %25, %26, %27, %28, %29, %30, %31, %32, %33, %34, %35, %36, %37, %38, %39}, %40, %41, p, 1, 1, 0, 0;\n}\n"
    : "+f"(d[0]), "+f"(d[1]), "+f"(d[2]), "+f"(d[3]), "+f"(d[4]), "+f"(d[5]), "+f"(d[6]), "+f"(d[7]), "+f"(d[8]), "+f"(d[9]), "+f"(d[10]), "+f"(d[11]), "+f"(d[12]), "+f"(d[13]), "+f"(d[14]), "+f"(d[15]), "+f"(d[16]), "+f"(d[17]), "+f"(d[18]), "+f"(d[19]), "+f"(d[20]), "+f"(d[21]), "+f"(d[22]), "+f"(d[23]), "+f"(d[24]), "+f"(d[25]), "+f"(d[26]), "+f"(d[27]), "+f"(d[28]), "+f"(d[29]), "+f"(d[30]), "+f"(d[31]), "+f"(d[32]), "+f"(d[33]), "+f"(d[34]), "+f"(d[35]), "+f"(d[36]), "+f"(d[37]), "+f"(d[38]), "+f"(d[39])
    : "l"(descA), "l"(descB), "r"(scaleD));
}

__device__ __forceinline__ void wgmma_n32_rs_tb1(float* d, const uint32_t* a, uint64_t descB, int scaleD) {
  asm volatile("{\n.reg .pred p;\nsetp.ne.b32 p, %21, 0;\n"
    "wgmma.mma_async.sync.aligned.m64n32k16.f32.bf16.bf16 {%0, %1, %2, %3, %4, %5, %6, %7, %8, %9, %10, %11, %12, %13, %14, %15}, {%16, %17, %18, %19}, %20, p, 1, 1, 1;\n}\n"
    : "+f"(d[0]), "+f"(d[1]), "+f"(d[2]), "+f"(d[3]), "+f"(d[4]), "+f"(d[5]), "+f"(d[6]), "+f"(d[7]), "+f"(d[8]), "+f"(d[9]), "+f"(d[10]), "+f"(d[11]), "+f"(d[12]), "+f"(d[13]), "+f"(d[14]), "+f"(d[15])
    : "r"(a[0]), "r"(a[1]), "r"(a[2]), "r"(a[3]), "l"(descB), "r"(scaleD));
}

__device__ __forceinline__ uint32_t pack_bf16x2(float lo, float hi) {
  uint32_t r;
  asm("cvt.rn.bf16x2.f32 %0, %1, %2;" : "=r"(r) : "f"(hi), "f"(lo));
  return r;
}
__device__ __forceinline__ float bf_lo(uint32_t p) { return __uint_as_float(p << 16); }
__device__ __forceinline__ float bf_hi(uint32_t p) { return __uint_as_float(p & 0xffff0000u); }
__device__ __forceinline__ float bf16_round(float v) { return __bfloat162float(__float2bfloat16_rn(v)); }
__device__ __forceinline__ float ex2_approx(float x) {
  float r;
  asm("ex2.approx.ftz.f32 %0, %1;" : "=f"(r) : "f"(x));
  return r;
}
__device__ __forceinline__ float rcp_fast(float x) {
  float r;
  asm("rcp.approx.ftz.f32 %0, %1;" : "=f"(r) : "f"(x));
  return r;
}
__device__ __forceinline__ void ldmatrix_x4(uint32_t (&r)[4], uint32_t addr) {
  asm volatile("ldmatrix.sync.aligned.m8n8.x4.shared.b16 {%0,%1,%2,%3}, [%4];"
               : "=r"(r[0]), "=r"(r[1]), "=r"(r[2]), "=r"(r[3])
               : "r"(sw(addr))
               : "memory");
}
__device__ __forceinline__ void stmatrix_x4(uint32_t addr, uint32_t r0, uint32_t r1, uint32_t r2, uint32_t r3) {
  asm volatile("stmatrix.sync.aligned.m8n8.x4.shared.b16 [%0], {%1,%2,%3,%4};" ::"r"(sw(addr)), "r"(r0), "r"(r1), "r"(r2),
               "r"(r3));
}
__device__ __forceinline__ uint32_t add_bf16x2(uint32_t a, uint32_t b) {
  uint32_t r;
  asm("add.rn.bf16x2 %0, %1, %2;" : "=r"(r) : "r"(a), "r"(b));
  return r;
}
__device__ __forceinline__ uint4 lds128(uint32_t addr) {
  uint4 v;
  asm volatile("ld.shared.v4.b32 {%0,%1,%2,%3}, [%4];" : "=r"(v.x), "=r"(v.y), "=r"(v.z), "=r"(v.w) : "r"(sw(addr)) : "memory");
  return v;
}
__device__ __forceinline__ uint32_t lds32(uint32_t addr) {
  uint32_t v;
  asm volatile("ld.shared.b32 %0, [%1];" : "=r"(v) : "r"(sw(addr)) : "memory");
  return v;
}
__device__ __forceinline__ void sts32(uint32_t addr, uint32_t v) {
  asm volatile("st.shared.b32 [%0], %1;" ::"r"(sw(addr)), "r"(v) : "memory");
}

__device__ __forceinline__ unsigned ld_acquire_u32(const unsigned* p) {
  unsigned v;
  asm volatile("ld.acquire.gpu.global.u32 %0, [%1];" : "=r"(v) : "l"(p) : "memory");
  return v;
}
__device__ __forceinline__ unsigned atom_add(unsigned* p, unsigned v, bool on) {
  unsigned r = 0;
  asm volatile("{\n.reg .pred p;\nsetp.ne.u32 p, %3, 0;\n@p atom.relaxed.gpu.global.add.u32 %0, [%1], %2;\n}\n"
               : "+r"(r) : "l"(p), "r"(v), "r"((uint32_t)on) : "memory");
  return r;
}
__device__ __forceinline__ void announce(unsigned* p) {
  asm volatile("red.release.gpu.global.add.u32 [%0], 1;" ::"l"(p) : "memory");
}
__device__ __forceinline__ void poison(uint8_t* p, int n, uint32_t gap) {
#pragma unroll 1
  for (int i = 0; i < n; i++, p += 2048) {
    asm volatile("st.global.v4.b32 [%0], {%1,%1,%1,%1};" ::"l"(p), "r"(0xffffffffu) : "memory");
    __nanosleep(gap);
  }
}
__device__ __forceinline__ void wait_ge2(const unsigned* p, unsigned t0, unsigned t1) {
#pragma unroll 1
  for (uint32_t it = 0; it < (1u << 17); ++it) {
    unsigned long long v;
    asm volatile("ld.acquire.gpu.global.u64 %0, [%1];" : "=l"(v) : "l"(p) : "memory");
    if ((int)((unsigned)v - t0) >= 0 && (int)((unsigned)(v >> 32) - t1) >= 0) return;
  }
}

#define RELNS 100
#define PCM 0x22
#define HBD 700
#define POI1 100
#define WU 3
constexpr int WUNR = WU;
#define PCS 4096
#define PCN 30
template <bool SLOW>
__device__ __forceinline__ void wait_mask(const unsigned* f, int cnt, unsigned target, uint32_t need, uint32_t& seen, int lane) {
  if ((seen & need) == need) return;
  const unsigned* fp = f + (lane & (cnt - 1));
#pragma unroll 1
  for (uint32_t it = 0; it < (1u << 17); ++it) {
    seen = __ballot_sync(0xffffffffu, (int)(ld_acquire_u32(fp) - target) >= 0);
    if ((seen & need) == need) break;
    if (SLOW) __nanosleep(400);
  }
  fence_proxy_async_all();
}
__device__ __forceinline__ void wait_lanes(const unsigned* fp, unsigned target, uint32_t need, uint32_t& seen) {
  if ((seen & need) == need) return;
#pragma unroll 1
  for (uint32_t it = 0; it < (1u << 17); ++it) {
    seen |= __ballot_sync(0xffffffffu, (int)(ld_acquire_u32(fp) - target) >= 0);
    if ((seen & need) == need) break;
  }
  fence_proxy_async_all();
}
__device__ __forceinline__ float4 ld_rec(const float4* p) {
  float4 v;
  asm volatile("ld.relaxed.gpu.global.v4.f32 {%0,%1,%2,%3}, [%4];" : "=f"(v.x), "=f"(v.y), "=f"(v.z), "=f"(v.w) : "l"(p) : "memory");
  return v;
}
__device__ __forceinline__ void st_rec(float4* p, float a, float b, float c, unsigned tag) {
  asm volatile("st.relaxed.gpu.global.v4.f32 [%0], {%1,%2,%3,%4};" ::"l"(p), "f"(a), "f"(b), "f"(c), "f"(__uint_as_float(tag)) : "memory");
}
template <int N>
__device__ __forceinline__ float4 sum_recs(const float4* p, int stride, unsigned tag) {
  float4 s;
#pragma unroll 1
  for (uint32_t it = 0; it < (1u << 17); ++it) {
    float4 v[N];
#pragma unroll
    for (int t = 0; t < N; t++) v[t] = ld_rec(p + t * stride);
    bool ok = true;
    s = make_float4(0.f, 0.f, 0.f, 0.f);
#pragma unroll
    for (int t = 0; t < N; t++) {
      ok &= __float_as_uint(v[t].w) == tag;
      s.x += v[t].x;
      s.y += v[t].y;
      s.z += v[t].z;
    }
    if (ok) break;
    __nanosleep(200);
  }
  return s;
}

__device__ __forceinline__ int fresh_tid() {
  int t;
  asm volatile("mov.u32 %0, %%tid.x;" : "=r"(t));
  return t;
}
#define PHASE_IDS                                  \
  const int tid_ = fresh_tid();                    \
  const int lane = tid_ & 31, wwarp = __shfl_sync(0xffffffffu, (tid_ >> 5) & 3, 0), tid = tid_ & 127; \
  const int g = lane >> 2, c = lane & 3;           \
  (void)tid; (void)g; (void)c; (void)wwarp;

#define STAMPW(cond, i) do { } while (0)
#define STAMP(cond, i) do { } while (0)
#define KSPN true
#define KSAON false
#define STA(i) do { } while (0)
#define GTL(i) do { } while (0)
#define GTLX(c, i) do { } while (0)
#define TGET(v) do { } while (0)
#define TPUT(c, i, v) do { } while (0)

constexpr float SM_C = 0.17677669529663687f * 1.4426950408889634f;

constexpr uint32_t OA_TILE = SBASE + OFF_SLOT + 16384;

__device__ __forceinline__ void sched_fence(uint32_t never) {
  asm volatile("{\n.reg .pred p;\nsetp.ne.u32 p, %0, 0;\n@p exit;\n}\n" ::"r"(never) : "memory");
}

template <int K0, int K1>
__device__ __forceinline__ void attn_exp(float (&s)[32]) {
#pragma unroll
  for (int k = K0; k < K1; k++) s[k] = ex2_approx(s[k]);
}
#define ASPL 16
#define ASPD 6
#define ASPE 6
#define ASPF 6
template <int MODE, bool NEXT>
__device__ __forceinline__ void attn_unit(float (&s)[32], float (&sn)[32], float (&o)[16], float (&l)[2], bool valid,
                                          uint32_t vdesc, uint32_t qdesc, uint32_t kdesc, uint32_t tri, int w,
                                          uint32_t hbar, uint32_t hpar, uint32_t rel, uint32_t zero, bool stampon = false) {
  float x[9][2];
  constexpr int ASPM = MODE == 1 ? ASPD : (NEXT ? ASPE : ASPF);
  if (MODE == 0) {
    attn_exp<0, ASPL>(s);
  } else {
#pragma unroll
    for (int e = 0; e < 2; e++) {
#pragma unroll
      for (int j = 0; j < 4; j++) x[j][e] = MODE == 1 ? s[4 * j + 2 + e] : s[16 + 4 * j + e];
      x[4][e] = MODE == 1 ? s[e] : s[30 + e];
      x[5][e] = MODE == 1 ? s[18 + e] : s[12 + e];
#pragma unroll
      for (int u = 1; u < 4; u++)
        x[5 + u][e] = MODE == 1 ? (w >= u ? s[4 * u + e] : s[4 * (8 - u) + 2 + e]) : (w >= u ? s[4 * (7 - u) + 2 + e] : s[4 * (u - 1) + e]);
    }
#pragma unroll
    for (int k = 0; k < 2 * ASPM; k++) x[k >> 1][k & 1] = ex2_approx(x[k >> 1][k & 1]);
  }
  sched_fence(zero);
  if (hbar) mbar_wait(hbar, hpar);
  wgmma_wait<0>();
  if (rel) mbar_arrive(rel);
  if (NEXT) {
    wgmma_fence();
    wgmma_n64_ssz_ta0_tb0(sn, desc_lo(qdesc), desc_lo(kdesc));
    wgmma_n64_ss_ta0_tb0(sn, desc_lo(qdesc + 2), desc_lo(kdesc + 2), 1);
    wgmma_commit();
    sched_fence(zero);
  }
  uint32_t p[16];
  if (MODE == 0) {
    attn_exp<ASPL, 32>(s);
#pragma unroll
    for (int k = 0; k < 16; k++) p[k] = pack_bf16x2(s[2 * k], s[2 * k + 1]);
  } else {
#pragma unroll
    for (int k = 2 * ASPM; k < 18; k++) x[k >> 1][k & 1] = ex2_approx(x[k >> 1][k & 1]);
    const uint32_t tm = MODE == 1 ? tri : ~tri;
#pragma unroll
    for (int j = 0; j < 4; j++) {
      p[MODE == 1 ? 2 * j + 1 : 8 + 2 * j] = pack_bf16x2(x[j][0], x[j][1]);
      p[MODE == 1 ? 8 + 2 * j : 2 * j + 1] = 0u;
    }
    p[MODE == 1 ? 0 : 15] = pack_bf16x2(x[4][0], x[4][1]) & (w == 0 ? tm : 0xffffffffu);
    p[MODE == 1 ? 9 : 6] = pack_bf16x2(x[5][0], x[5][1]) & (w == 3 ? tm : 0xffffffffu);
#pragma unroll
    for (int u = 1; u < 4; u++) {
      const uint32_t q = pack_bf16x2(x[5 + u][0], x[5 + u][1]);
      p[MODE == 1 ? 2 * u : 2 * (7 - u) + 1] = q & (w > u ? 0xffffffffu : (w == u ? tm : 0u));
      p[MODE == 1 ? 2 * (8 - u) + 1 : 2 * (u - 1)] = q & (w < u - 1 ? 0xffffffffu : (w == u - 1 ? tm : 0u));
    }
  }
  wgmma_fence();
#pragma unroll
  for (int k = 0; k < 4; k++) wgmma_n32_rs_tb1(o, p + 4 * k, desc_lo(vdesc + k * 128), 1);
  wgmma_commit();
#pragma unroll
  for (int r = 0; r < 2; r++) {
    float t = 0.f;
#pragma unroll
    for (int hf = 0; hf < 2; hf++) {
      if (MODE != 0 && r == MODE - 1 && hf == 2 - MODE) continue;
      const uint32_t* q = p + 8 * hf + r;
      const uint32_t v = add_bf16x2(add_bf16x2(q[0], q[2]), add_bf16x2(q[4], q[6]));
      t = (MODE != 0 && r == MODE - 1) || hf == 0 ? bf_lo(v) + bf_hi(v) : t + (bf_lo(v) + bf_hi(v));
    }
    if (valid) l[r] += t;
  }
  if (NEXT) {
    wgmma_wait<1>();
    reg_fence<32>(sn);
  }
}

__device__ __forceinline__ void attn_a_slow(const uint8_t* __restrict__ kvimg, int L, int gb, int hp,
                                         int hh, int wwarp, int lane, int t0, int t1) {
  constexpr uint32_t sq = SBASE + OFF_SLOT + 3 * 16384;
  const unsigned ep = (*(volatile unsigned*)(g_flags + F_DONE)) / NCTA;
  wait_ge2(g_flags + F_KV + (gb * 16 + hp) * KSTR, 2u * ep + (L >> 1) + 1u, 2u * ep + (L >> 1) + 1u);
#pragma unroll 1
  for (int t = t0; t < t1; t++) {
    const int row = (t >> 4) * 64 + ((t & 8) ? 7 - wwarp : wwarp) * 8 + (t & 7);
    const int qpos = gb * 128 + row;
    const uint32_t qaddr = sq + ((t >> 4) * 64 + wwarp * 16 + (t & 15)) * 128;
    float mx = -INFINITY, sum = 0.f, acc = 0.f;
#pragma unroll 1
    for (int pass = 0; pass < 2; pass++) {
#pragma unroll 1
      for (int j = 0; j < 8; j++) {
        const int kp = qpos - (lane + 32 * j);
        const uint8_t* kr = kvimg + ((size_t)((kp >> 7) * 16 + hp) * 2 + ((kp >> 6) & 1)) * 16384 + (kp & 63) * 128;
        float d = -INFINITY;
        if (kp >= 0) {
          d = 0.f;
#pragma unroll 1
          for (int q = 0; q < 4; q++) {
            const uint4 kv = __ldcg(reinterpret_cast<const uint4*>(kr + (((hh * 4 + q) ^ (kp & 7)) << 4)));
            const uint4 qv = lds128(qaddr + (((hh * 4 + q) ^ (row & 7)) << 4));
            const uint32_t kw[4] = {kv.x, kv.y, kv.z, kv.w}, qw[4] = {qv.x, qv.y, qv.z, qv.w};
#pragma unroll
            for (int e = 0; e < 4; e++) d = fmaf(bf_lo(kw[e]), bf_lo(qw[e]), fmaf(bf_hi(kw[e]), bf_hi(qw[e]), d));
          }
        }
        if (pass == 0) {
          mx = fmaxf(mx, d);
        } else {
          const float ev = ex2_approx(d - mx);
          sum += ev;
          const float pv = bf16_round(ev);
#pragma unroll 1
          for (int kk = 0; kk < 32; kk++) {
            const float pk = __shfl_sync(0xffffffffu, pv, kk);
            const int k2 = qpos - (kk + 32 * j);
            if (k2 >= 0) {
              const uint8_t* vr = kvimg + ((size_t)((k2 >> 7) * 16 + hp) * 2 + ((k2 >> 6) & 1)) * 16384 + 8192 + (k2 & 63) * 128;
              const unsigned short vv =
                  __ldcg(reinterpret_cast<const unsigned short*>(vr + (((hh * 4 + (lane >> 3)) ^ (k2 & 7)) << 4) + (lane & 7) * 2));
              acc = fmaf(pk, __uint_as_float((uint32_t)vv << 16), acc);
            }
          }
        }
      }
      if (pass == 0) {
#pragma unroll
        for (int o = 16; o > 0; o >>= 1) mx = fmaxf(mx, __shfl_xor_sync(0xffffffffu, mx, o));
      }
    }
#pragma unroll
    for (int o = 16; o > 0; o >>= 1) sum += __shfl_xor_sync(0xffffffffu, sum, o);
    acc *= rcp_fast(sum);
    const float hi = __shfl_down_sync(0xffffffffu, acc, 1);
    __syncwarp();
    if ((lane & 1) == 0)
      sts32(OA_TILE + row * 128 + (((hh * 4 + (lane >> 3)) ^ (row & 7)) << 4) + (lane & 7) * 2, pack_bf16x2(acc, hi));
    __syncwarp();
  }
}

__device__ __forceinline__ void store_o(const float (&o)[16], const float (&inv)[2], uint32_t rowaddr, int hh, int lane) {
  const int mat = lane >> 3, r7 = lane & 7;
#pragma unroll
  for (int jp = 0; jp < 2; jp++)
    stmatrix_x4(rowaddr + (((hh * 4 + 2 * jp + (mat >> 1)) ^ r7) << 4),
                pack_bf16x2(o[8 * jp] * inv[0], o[8 * jp + 1] * inv[0]),
                pack_bf16x2(o[8 * jp + 2] * inv[1], o[8 * jp + 3] * inv[1]),
                pack_bf16x2(o[8 * jp + 4] * inv[0], o[8 * jp + 5] * inv[0]),
                pack_bf16x2(o[8 * jp + 6] * inv[1], o[8 * jp + 7] * inv[1]));
}

__device__ __forceinline__ void attention_a(int HH, int L, int gb, int hp, uint32_t par0, uint32_t parA, int wwarp, int lane,
                                            uint32_t zero) {
  constexpr uint32_t bars = SBASE + OFF_BAR;
  const uint32_t dslot = ((SBASE + OFF_SLOT) >> 4) + 0x10000u + HH * 4;
  const uint32_t dq = dslot + 3 * 1024;
  float sa[32], sb[32], o[2][16], l[2][2];
  auto dch = [&](int n) { return dslot + 1024u * (n % 3 == 0 ? 1 : (n % 3 == 1 ? 0 : 2)); };
  wgmma_fence();
  wgmma_n64_ssz_ta0_tb0(sa, desc_lo(dq + 512), desc_lo(dch(0)));
  wgmma_n64_ss_ta0_tb0(sa, desc_lo(dq + 512 + 2), desc_lo(dch(0) + 2), 1);
  wgmma_commit();
#pragma unroll
  for (int h = 0; h < 2; h++) {
#pragma unroll
    for (int i = 0; i < 16; i++) o[h][i] = 0.f;
    l[h][0] = l[h][1] = 0.f;
  }
  const int dg = (lane >> 2) - 2 * (lane & 3);
  const uint32_t tri = (dg >= 0 ? 0xffffu : 0u) | (dg >= 1 ? 0xffff0000u : 0u);
  const int nmax = 2 * gb + 1;
  wgmma_wait<0>();
  reg_fence<32>(sa);
#define STON false
#define ATT_STEP(i, MODE)                                                                                            \
  attn_unit<MODE, true>(sa, sb, o[1], l[1], i <= nmax, dch(i) + 512, dq, dch(i + 1), tri, wwarp,                     \
                        i >= 1 ? bars + 8u * (B_HALO + i - 1) : 0u, i == 1 ? par0 : parA, 0u, zero, STON); \
  attn_unit<MODE, (i < 4)>(sb, sa, o[0], l[0], i + 1 <= nmax, dch(i + 1) + 512, dq + 512, dch(i + 1), tri, wwarp, 0u, \
                           0u, i < 3 && lane == 0 ? bars + 8u * (B_REL + i) : 0u, zero);
  ATT_STEP(0, 1)
  ATT_STEP(1, 0)
  ATT_STEP(2, 0)
  ATT_STEP(3, 0)
  ATT_STEP(4, 2)
#undef ATT_STEP
  const uint32_t ra = OA_TILE + (((lane & 8) ? 7 - wwarp : wwarp) * 8 + (lane & 7)) * 128;
  bool redo[2];
#pragma unroll
  for (int h = 1; h >= 0; h--) {
    float inv[2];
    bool bad = false;
#pragma unroll
    for (int r = 0; r < 2; r++) {
      float v = l[h][r];
      v += __shfl_xor_sync(0xffffffffu, v, 1);
      v += __shfl_xor_sync(0xffffffffu, v, 2);
      bad |= !(v <= 1.152921504606846976e18f && v >= 8.673617379884035e-19f);
      inv[r] = rcp_fast(v);
    }
    if (h == 0) wgmma_wait<0>();
    reg_fence<16>(o[h]);
    store_o(o[h], inv, ra + h * 8192, HH, lane);
    redo[h] = __any_sync(0xffffffffu, bad);
    if (h == 1 && !redo[1]) {
      fence_proxy_async_smem();
      named_bar_arrive(9, 288);
    }
  }
  if (HH == 0) GTL(45);
  if (redo[0] || redo[1]) {
    attn_a_slow(g_kvA[L >> 1][0][0][0], L, gb, hp, HH, wwarp, lane, redo[0] ? 0 : 16, redo[1] ? 32 : 16);
    fence_proxy_async_smem();
    if (redo[1]) named_bar_arrive(9, 288);
  }
}

constexpr uint32_t KB_ROW0 = SBASE + OFF_SLOT + 2048, VB_ROW0 = SBASE + OFF_SLOT + 24576 + 2048;

__device__ __forceinline__ void attnB_soft(const float (&s)[40], int wwarp, int D, bool edge, bool odd,
                                           uint32_t (&p)[5][4], float (&sum)[2]) {
  float z[2][3];
#define GATHER_(W)                                                                                  \
  _Pragma("unroll") for (int r = 0; r < 2; r++) _Pragma("unroll") for (int t = 0; t < 3; t++)       \
      z[r][t] = odd ? s[4 * (2 * W + r + t) + 2 * r + 1] : s[4 * (2 * W + r + t) + 2 * r];
  if (wwarp < 2) {
    if (wwarp == 0) { GATHER_(0) } else { GATHER_(1) }
  } else {
    if (wwarp == 2) { GATHER_(2) } else { GATHER_(3) }
  }
#undef GATHER_
  float y[2];
  y[0] = D >= 2 ? z[0][0] : z[0][2];
  y[1] = D >= 2 ? z[1][0] : z[1][2];
  if (edge) {
    z[0][1] = -INFINITY;
    if (D >= 2) y[0] = y[1] = -INFINITY;
  }
  float m0 = fmaxf(z[0][1], y[0]), m1 = fmaxf(z[1][1], y[1]);
  m0 = fmaxf(m0, __shfl_xor_sync(0xffffffffu, m0, 1));
  m1 = fmaxf(m1, __shfl_xor_sync(0xffffffffu, m1, 1));
  m0 = fmaxf(m0, __shfl_xor_sync(0xffffffffu, m0, 2));
  m1 = fmaxf(m1, __shfl_xor_sync(0xffffffffu, m1, 2));
  const float e00 = ex2_approx(z[0][1] - m0), e01 = ex2_approx(y[0] - m0);
  const float e10 = ex2_approx(z[1][1] - m1), e11 = ex2_approx(y[1] - m1);
  sum[0] = e00 + e01;
  sum[1] = e10 + e11;
  const int sh = odd ? 16 : 0;
  const uint32_t a0 = pack_bf16x2(e00, 0.f) << sh, a1 = pack_bf16x2(e10, 0.f) << sh;
  const uint32_t b0 = pack_bf16x2(e01, 0.f) << sh, b1 = pack_bf16x2(e11, 0.f) << sh;
  const int kb = wwarp + (D >= 2 ? 0 : 1);
#pragma unroll
  for (int k = 0; k < 5; k++) {
    p[k][0] = k == kb ? b0 : 0u;
    p[k][1] = k == wwarp + 1 ? a1 : 0u;
    p[k][2] = k == wwarp ? a0 : 0u;
    p[k][3] = k == kb ? b1 : 0u;
#pragma unroll
    for (int q = 0; q < 4; q++) asm volatile("" : "+r"(p[k][q]));
  }
}

__device__ __forceinline__ void attnB_s(float (&s)[40], int HH, int h) {
  constexpr uint32_t sq = SBASE + OFF_SLOT + 3 * 16384;
#pragma unroll
  for (int ks = 0; ks < 2; ks++)
    wgmma_n80_ss_ta0_tb0(s, make_desc(sq + h * 8192 + HH * 64 + ks * 32, 16),
                         make_desc(KB_ROW0 + h * 8192 - 2048 + HH * 64 + ks * 32, 16), ks);
}
__device__ __forceinline__ void attnB_pv(float (&o)[16], const uint32_t (&p)[5][4], int HH, int h) {
#pragma unroll
  for (int k = 0; k < 5; k++)
    wgmma_n32_rs_tb1(o, p[k], make_desc(VB_ROW0 + h * 8192 - 2048 + k * 2048 + HH * 64, 16), k);
}

__device__ __forceinline__ void attention_b(int HH, int gb, uint32_t par0, int wwarp, int lane, bool ston) {
  constexpr uint32_t bars = SBASE + OFF_BAR, sq = SBASE + OFF_SLOT + 3 * 16384;
  float s[40];
  reg_define<40>(s);
  wgmma_fence();
  attnB_s(s, HH, 1);
  wgmma_commit();
  const int g = lane >> 2;
  const bool odd = g & 1;
  const int D = 2 * (lane & 3) + (g & 1) - g;
  const uint32_t ra = sq + (wwarp * 16 + ((lane >> 3) & 1) * 8 + (lane & 7)) * 128;
  wgmma_wait<0>();
  reg_fence<40>(s);
  STAMP(ston, 21);
#pragma unroll 1
  for (int h = 1; h >= 0; h--) {
    float o[16], inv[2];
    uint32_t p[5][4];
    reg_define<16>(o);
    attnB_soft(s, wwarp, D, h == 0 && gb == 0 && wwarp == 0, odd, p, inv);
    STAMP(ston, 25 - 3 * h);
    wgmma_fence();
    attnB_pv(o, p, HH, h);
    wgmma_commit();
#pragma unroll
    for (int r = 0; r < 2; r++) {
      inv[r] += __shfl_xor_sync(0xffffffffu, inv[r], 1);
      inv[r] += __shfl_xor_sync(0xffffffffu, inv[r], 2);
      inv[r] = rcp_fast(inv[r]);
    }
    if (h == 1) {
      mbar_wait(bars + 8u * B_HALO, par0);
      STAMP(ston, 23);
      wgmma_fence();
      attnB_s(s, HH, 0);
      wgmma_commit();
      wgmma_wait<1>();
    } else {
      wgmma_wait<0>();
    }
    reg_fence<16>(o);
    store_o(o, inv, ra + h * 8192, HH, lane);
    if (h == 1) {
      fence_proxy_async_smem();
      named_bar_arrive(9, 288);
    }
    wgmma_wait<0>();
    reg_fence<40>(s);
    STAMP(ston, 26 - 2 * h);
  }
}

#define TRICKLE 300
#define TRSP 10
#define TRICK2 150
#define PDL 600
#define CSN 1000
#define CSI 1
#define PCA 1
#define PCB 3
#define PXB 4
#define EPW1 4
#define EPW0 12
#define PRENS 800
#define LOCE 1
#define QTURN 2
constexpr int NPT = 240 + 8;
struct Params {
  CUtensorMap xq[2], xr[3], o, wqkv[2], wo[2];
  const __nv_bfloat16* in_x;
  const __nv_bfloat16* wqkv_p1;
  const __nv_bfloat16* wo_p[2];
  uint32_t zero;
  uint2 wtab[4][17];
  uint2 ptab[NPT + 1];
};
static_assert(sizeof(Params) <= 4096, "");

__device__ __forceinline__ void colsum_part(const CUtensorMap* wmap, int ty, int qr, int hp) {
  constexpr uint32_t bars = SBASE + OFF_BAR, slots = SBASE + OFF_SLOT;
  PHASE_IDS
  const unsigned ep1 = (*(volatile unsigned*)(g_flags + F_DONE)) / NCTA + 1u;
  if (ty) {
#pragma unroll 1
    for (int j = 0; j < 4; j++) poison(g_kvB[j >> 1][(j & 1) * 8 + qr][hp] + tid * 16, 2, POI1);
    asm volatile("fence.acq_rel.gpu;" ::: "memory");
    fence_proxy_async_all();
  }
  if (wwarp == 0 && elect_one()) {
    mbar_expect_tx(bars + 8u * B_CS, 6 * UNIT);
#pragma unroll 1
    for (int j = 0; j < 2; j++) {
      if (ty == 0) mbar_pace(bars + 8u * (B_EMPTY + PCA + PCB * j), 0);
      else __nanosleep(CSN);
      tma_load_3d(slots + j * 3 * UNIT, wmap, bars + 8u * B_CS, hp * 64, qr * 128 + j * 64, 0);
    }
  }
  mbar_wait(bars + 8u * B_CS, ty);
  STAMP(KSQ == 0 && ty == 0, 49);
  const uint32_t src = slots + (tid >> 3) * 128 + (((tid & 7) ^ ((tid >> 3) & 7)) << 4);
#pragma unroll 1
  for (int p = 0; p < 3; p++) {
    float s[8];
#pragma unroll
    for (int e = 0; e < 8; e++) s[e] = 0.f;
#pragma unroll
    for (int j = 0; j < 8; j++) {
      const uint4 v = lds128(src + p * UNIT + (j >> 2) * 3 * UNIT + (j & 3) * 2048);
      const uint32_t x[4] = {v.x, v.y, v.z, v.w};
#pragma unroll
      for (int e = 0; e < 4; e++) {
        s[2 * e] += bf_lo(x[e]);
        s[2 * e + 1] += bf_hi(x[e]);
      }
    }
#pragma unroll
    for (int st = 0; st < 2; st++) {
      const bool up = (lane >> (st + 3)) & 1;
#pragma unroll
      for (int e = 0; e < (4 >> st); e++) {
        const float keep = up ? s[e + (4 >> st)] : s[e], give = up ? s[e] : s[e + (4 >> st)];
        s[e] = keep + __shfl_xor_sync(0xffffffffu, give, 8 << st);
      }
    }
    const uint32_t dst = slots + 6 * UNIT + ((wwarp * 3 + p) * 64 + (lane & 7) * 8 + ((lane >> 3) & 1) * 4 + (lane >> 4) * 2) * 4;
    sts32(dst, __float_as_uint(s[0]));
    sts32(dst + 4, __float_as_uint(s[1]));
  }
  named_bar_sync(6, 128);
  if (tid < 64) {
    float r[3] = {0.f, 0.f, 0.f};
#pragma unroll
    for (int e = 0; e < 12; e++) r[e % 3] += __uint_as_float(lds32(slots + 6 * UNIT + (e * 64 + tid) * 4));
    st_rec(&g_cs[ty][hp][qr][tid], r[0], r[1], r[2], ep1);
    STAMP(KSQ == 0 && ty == 0, 50);
  }
  named_bar_sync(6, 128);
}

__device__ __forceinline__ void cs_put(int blk, int ty, int col, float v) {
  const uint32_t hi = pack_bf16x2(v, 0.f), lo = pack_bf16x2(v - bf_lo(hi), 0.f);
  const uint32_t a = SBASE + OFF_CS + blk * 512 + ty * 256 + col * 2;
  asm volatile("st.shared.b16 [%0], %1;" ::"r"(sw(a ^ (((a >> 7) & 7) << 4))), "h"((unsigned short)hi) : "memory");
  asm volatile("st.shared.b16 [%0], %1;" ::"r"(sw((a + 128) ^ ((((a >> 7) + 1) & 7) << 4))), "h"((unsigned short)lo) : "memory");
}

__device__ __forceinline__ uint32_t ln_params(float s1, float s2) {
  const float mean = s1 * (1.0f / DM);
  const float var = fmaxf(fmaf(-mean, mean, s2 * (1.0f / DM)), 0.f);
  float sd;
  asm("sqrt.approx.f32 %0, %1;" : "=f"(sd) : "f"(bf16_round(bf16_round(var) + 1e-5f)));
  return pack_bf16x2(mean, sd);
}

#define SPLITS 0x085866688ull
__host__ __device__ __forceinline__ int q_split(int inst) { return (int)((SPLITS >> (4 * inst)) & 15ull); }
__device__ __forceinline__ int q_first(int inst) { return inst == 0 ? 0 : 32 * inst - 16; }
__device__ __forceinline__ int w_first(int inst) { return 32 * inst + 16 + 2 * q_split(inst + 1); }
#define PREMASK 0x2Cu
#define WBUF 0x0400103000201000ull
static_assert((PREMASK & 0xC0u) == 0, "");
__host__ __device__ __forceinline__ bool w_pre(int inst) { return (PREMASK >> inst) & 1u; }
struct WPlan {
  int v[6][21];
  int own[28], len;
};
__host__ __device__ constexpr WPlan w_plan(int mode) {
  WPlan p{};
  for (int u = 0; u < 28; u++) p.own[u] = u < 20 ? u / 5 - 4 : -16;
  if (mode == 2) {
    const WPlan q = w_plan(0);
    for (int u = 0; u < 20; u++) p.own[u] = q.own[(u + q.len) % 20] - 16;
  }
  int pos = 0, mx = -16;
  for (int kt = 0; kt < 21; kt++) {
    const int code = mode == 1 && kt < 16 ? (int)(WBUF >> (4 * kt)) & 15 : 0, st = kt > 16 ? kt - 1 : kt;
    const int na = kt == 16 ? 0 : (kt < 16 ? 1 : 2), nb = kt < 17 ? 2 : 3;
    const bool hole = code == 0 || (code & 8), swap = kt < 16 && hole && pos % 10 == 8;
    const int ua = (pos + (swap ? 2 : 0)) % 20, ub = code ? NUNITS - 2 + 2 * (code & 7) : (pos + (swap ? 0 : na)) % 20;
    int ra = st - 8, rb = kt == 16 ? -16 : st - 8;
    for (int i = 0; i < na; i++) ra = p.own[ua + i] > ra ? p.own[ua + i] : ra;
    for (int i = 0; i < nb; i++) rb = p.own[ub + i] > rb ? p.own[ub + i] : rb;
    p.v[0][kt] = ua;
    p.v[1][kt] = ub;
    p.v[2][kt] = st - ra;
    p.v[3][kt] = st - rb;
    p.v[4][kt] = rb > mx;
    p.v[5][kt] = p.own[ub] == -16;
    mx = rb > mx ? rb : mx;
    if (kt < 17) {
      for (int i = 0; i < na; i++) p.own[ua + i] = kt;
      for (int i = 0; i < nb; i++) p.own[ub + i] = kt < 16 ? kt : 15;
    }
    pos += na + (hole ? nb : 0);
    if (kt == 16) p.len = pos;
  }
  return p;
}
__host__ __device__ constexpr uint64_t w_tab(int f, int mode, int k0, int dk, int n, int bits) {
  const WPlan p = w_plan(mode);
  uint64_t r = 0;
  for (int j = 0; j < n; j++) r |= (uint64_t)p.v[f][k0 + j * dk] << (bits * j);
  return r;
}
__host__ __device__ constexpr uint32_t q_backs(bool act, int rank, bool pre) {
  return act ? 0x44444400u | (uint32_t)w_tab(2, pre, 17 + rank, 2, 2, 4) : 0x44440000u | (uint32_t)w_tab(3, pre, 17, 1, 4, 4);
}
__host__ __device__ constexpr uint32_t w_early() {
  const WPlan p = w_plan(1);
  uint32_t r = 0;
  for (int kt = 0; kt < 16; kt++)
    if (p.v[5][kt]) r |= (uint32_t)kt << (2 * (p.v[1][kt] - NUNITS));
  return r;
}
__host__ __device__ constexpr uint32_t w_emask() {
  const WPlan p = w_plan(1);
  uint32_t r = 0;
  for (int kt = 0; kt < 16; kt++) r |= (uint32_t)p.v[5][kt] << kt;
  return r;
}
static_assert((w_emask() & 3) == 0 && (w_early() & 15) < ((w_early() >> 4) & 15) && ((w_early() >> 4) & 15) < ((w_early() >> 8) & 15) &&
              ((w_early() >> 8) & 15) < (w_early() >> 12), "");
static_assert(w_plan(1).len % 10 == 0 && w_tab(2, 0, 0, 2, 8, 4) == 0x77776654u && w_tab(2, 2, 1, 2, 8, 4) == 0x77777666u &&
              q_backs(false, 0, false) == 0x44444445u && q_backs(true, 0, false) == 0x44444456u, "");
constexpr bool PRE_FLIP = w_plan(1).len % 20 != 0;
__device__ __forceinline__ int w_flips(int n) { return PRE_FLIP ? n : __popc(~PREMASK & ((1u << n) - 1u)); }
__host__ __device__ __forceinline__ uint32_t unit_off(int u, uint32_t dl) { return u * UNIT + (u < 10 ? dl : (u < 20 ? 0u - dl : 0u)); }

__global__ void __cluster_dims__(2, 1, 1) __launch_bounds__(512, 1) fused_kernel(const __grid_constant__ Params P) {
  constexpr uint32_t base = SBASE, bars = base + OFF_BAR, slots = base + OFF_SLOT;
  const int warp = __shfl_sync(0xffffffffu, threadIdx.x >> 5, 0), lane = threadIdx.x & 31;
  const int b = blockIdx.x, rank = b & 1;
  if (smem_u32(smem_raw) != base + (rank << 24)) __trap();
  int role = 0;
  {
    unsigned smid;
    asm volatile("mov.u32 %0, %smid;" : "=r"(smid));
    const int tc = smid >> 1;
    role = (tc < 32 ? (tc & 7) * 8 + (tc >> 3) : (tc < 62 ? ((tc - 32) % 7 + 1) * 8 + 4 + (tc - 32) / 7 : tc - 58)) & 63;
  }
  if (warp == 12) {
    if (elect_one()) {
#pragma unroll
      for (int s = 0; s < 8; s++) {
        mbar_init(bars + 8u * (B_FULL + s), 1);
        mbar_init(bars + 8u * (B_EMPTY + s), LOCE ? 2 : 4);
        mbar_init(bars + 8u * (B_LOC + s), 2);
      }
      mbar_init(bars + 8u * B_GO, 1);
      mbar_init(bars + 8u * B_ROLE, 1);
      mbar_expect_tx(bars + 8u * B_ROLE, 4);
      fence_barrier_init();
    }
    __syncwarp();
  }
  asm volatile("barrier.cluster.arrive.relaxed.aligned;" ::: "memory");
  if (threadIdx.x == 0) {
    mbar_init(bars + 8u * B_PREP, 1);
    mbar_init(bars + 8u * (B_PREP + 1), 1);
    for (int s = 0; s < 4; s++) mbar_init(bars + 8u * (B_HALO + s), 1);
    for (int s = 0; s < 3; s++) mbar_init(bars + 8u * (B_REL + s), 8);
    mbar_init(bars + 8u * B_AFREE, 2);
    mbar_init(bars + 8u * B_TURN, 4);
    mbar_init(bars + 8u * (B_TURN + 1), 4);
    mbar_init(bars + 8u * B_CS, 1);
    mbar_init(bars + 8u * B_HB, 1);
    mbar_init(bars + 8u * B_KVS, 1);
    for (int s = 0; s < 4; s++) mbar_init(bars + 8u * (B_PRE + s), 1);
    mbar_init(bars + 8u * B_RESF, 1);
    mbar_init(bars + 8u * B_RESE, 4);
    mbar_init(bars + 8u * B_CSD, 4);
    mbar_init(bars + 8u * B_XRDY, 1);
    mbar_init(bars + 8u * (B_XRDY + 1), 1);
    fence_barrier_init();
  }
  if (warp == 15 && rank == 0) {
    const unsigned ep = *(volatile unsigned*)(g_flags + F_DONE);
    int r = role;
#pragma unroll 1
    for (int it = 0; it < 64; it++, r = (r + 1) & 63) {
      if (__all_sync(0xffffffffu, (ep - atom_add(g_flags + F_ROLE + r * RSTR, NCTA, lane == 0) < NCTA) | (lane != 0))) break;
      atom_add(g_flags + F_ROLE + r * RSTR, 0u - NCTA, lane == 0);
    }
    asm volatile("barrier.cluster.wait.aligned;" ::: "memory");
    asm volatile("{\n.reg .pred p;\nsetp.lt.u32 p, %3, 2;\n"
                 "@p st.async.weak.shared::cluster.mbarrier::complete_tx::bytes.b32 [%0], %1, [%2];\n}\n" ::"r"(base + OFF_ROLE + (lane << 24)),
                 "r"(r), "r"(bars + 8u * B_ROLE + (lane << 24)), "r"(lane)
                 : "memory");
  } else if (warp != 12) {
    asm volatile("barrier.cluster.wait.aligned;" ::: "memory");
  }
#define ROLE_IDS                                                                                   \
  const int qr = role & 7, hp = (role >> 3) * 2 + rank, rt = role & 15, ct = ((role >> 3) & 6) + rank; \
  (void)qr; (void)hp; (void)rt; (void)ct;
#define ROLE_GET                                                          \
  named_bar_sync(0, 512);                                                 \
  role = __shfl_sync(0xffffffffu, (int)lds32(base + OFF_ROLE), 0);

  if (warp < 12) {
    const bool asst = warp >= 8;
    ROLE_GET
    ROLE_IDS
    uint32_t tpar = 0;
    const uint32_t ebar = LOCE && (warp & 2) ? bars + 8u * B_LOC + (rank << 24) : bars + 8u * B_EMPTY + ((warp & 1) << 24);
    GTL(0);
#pragma unroll 1
    for (int inst = (warp < 4 ? 0 : -1) + (int)P.zero; inst < 8; inst += asst ? 1 : 2) {
      const int L = inst >> 1, ch = inst & 1, gb = ch * 8 + qr;
      if (inst >= 0) {
      if (asst) {
        setmaxnreg_dec<24>();
        named_bar_sync(4, 256);
        setmaxnreg_inc<128>();
      } else {
      setmaxnreg_inc<224>();
      {
        float acc[2][96];
        const int ksp = q_split(inst);
        int n = q_first(inst);
        uint32_t dlt = inst > 0 && (w_flips(inst - 1) & 1) ? 10u * (UNIT >> 4) : 0u;
        if (inst == 1 || (inst > 1 && q_split(inst - 1) != 8)) {
          mbar_wait_lazy<100>(bars + 8u * (B_TURN + ch), tpar);
          tpar ^= 1u;
        }
        if (L == 3) GTL(37);
        mbar_wait(bars + 8u * (B_FULL + (n & 7)), (n >> 3) & 1);
        GTL(1 + L * 8);
        {
          const uint32_t da = (base >> 4) + 0x10000u + dlt;
          const uint64_t db = desc_lo(da - 0x10000u + ((UNIT >> 4) << 16) + 2 * (UNIT >> 4));
          wgmma_fence();
          wgmma_n192_ssz_ta0_tb1(acc[0], desc_lo(da), db);
          wgmma_commit();
          wgmma_n192_ssz_ta0_tb1(acc[1], desc_lo(da + (UNIT >> 4)), db);
          wgmma_commit();
        }
#pragma unroll 1
        for (int k2 = 0; k2 < 7; k2++) {
          const bool brk = k2 + 1 == ksp;
#pragma unroll
          for (int ks = 0; ks < 2; ks++, n++) {
            STAMP(inst == KSQ, k2 * 2 + ks);
            const uint32_t da = ((base + ks * 5 * UNIT) >> 4) + 0x10000u + dlt;
            const uint32_t dbb = da - 0x10000u + ((UNIT >> 4) << 16) + 2 * (UNIT >> 4);
#pragma unroll
            for (int k16 = 0; k16 < 4; k16++) {
              if (ks == 0 && k16 == 0 && k2 == 0) continue;
              const uint64_t db = desc_lo(dbb + k16 * 128);
              wgmma_fence();
              wgmma_n192_ss_ta0_tb1(acc[0], desc_lo(da + k16 * 2), db, 1);
              wgmma_commit();
              wgmma_wait<1>();
              if (k16 == 0) warp_arrive_cl(ebar + 8u * ((n - 1) & 7), ks != 0 || k2 != ksp);
              wgmma_fence();
              wgmma_n192_ss_ta0_tb1(acc[1], desc_lo(da + (UNIT >> 4) + k16 * 2), db, 1);
              wgmma_commit();
              bool ok = true;
              if (k16 == 2) ok = mbar_test(bars + 8u * (B_FULL + ((n + 1) & 7)), ((n + 1) >> 3) & 1) || (ks == 1 && brk);
              if (k16 == QTURN && ks == 1) warp_arrive(bars + 8u * (B_TURN + (ch ^ 1)), brk);
              if (ks == 0 || k16 < 3) wgmma_wait<1>();
              if (k16 == 2 && !ok) mbar_wait(bars + 8u * (B_FULL + ((n + 1) & 7)), ((n + 1) >> 3) & 1);
            }
          }
          if (brk) {
            wgmma_wait<0>();
            warp_arrive_cl(ebar + 8u * ((n - 1) & 7));
            n += 16;
            mbar_wait_lazy<100>(bars + 8u * (B_TURN + ch), tpar);
            tpar ^= 1u;
            STAMP(inst == KSQ, 17);
            mbar_wait(bars + 8u * (B_FULL + (n & 7)), (n >> 3) & 1);
          }
          if (!brk || (!PRE_FLIP && w_pre(inst - 1))) dlt ^= 10u * (UNIT >> 4);
        }
        auto tail_group = [&](int u) {
          const uint32_t da = ((base + (u & 1) * 5 * UNIT) >> 4) + 0x10000u + dlt;
          const uint32_t dbb = da - 0x10000u + ((UNIT >> 4) << 16) + 2 * (UNIT >> 4);
          if (u < 3) wgmma_fence();
#pragma unroll
          for (int k16 = 0; k16 < 4; k16++)
            wgmma_n192_ss_ta0_tb1(acc[u < 2], desc_lo(da + (u < 2 ? UNIT >> 4 : 0) + k16 * 2), desc_lo(dbb + k16 * 128), 1);
          wgmma_commit();
        };
        STAMP(inst == KSQ, 14);
        tail_group(0);
        wgmma_wait<1>();
        STAMP(inst == KSQ && KSPN, 42);
        warp_arrive_cl(ebar + 8u * ((n - 1) & 7), ksp != 7);
        PHASE_IDS
        mbar_wait(bars + 8u * (B_PREP + ch), L & 1);
        STAMP(inst == KSQ && KSPN, 43);
        uint32_t rs[4];
#pragma unroll
        for (int i = 0; i < 4; i++)
          rs[i] = lds32(base + OFF_RS + (ch * 128 + (i >> 1) * 64 + wwarp * 16 + g + 8 * (i & 1)) * 4);
        auto fold = [&](int h) {
          uint32_t a[2];
#pragma unroll
          for (int r = 0; r < 2; r++) a[r] = c == (L & 1) ? __byte_perm(rs[2 * h + r], 0, 0x1010) ^ 0x80008000u : 0u;
          uint64_t d;
          asm("mov.b64 %0, {%1, %2};" : "=l"(d) : "r"(((base + OFF_CS) >> 4) + ((512 >> 4) << 16)), "r"(0x40000000u));
          wgmma_fence();
          wgmma_n192_rs_tb1(acc[h], a[0], a[1], d);
        };
        fold(1);
        wgmma_commit();
        mbar_wait(bars + 8u * (B_FULL + ((n + 1) & 7)), ((n + 1) >> 3) & 1);
        STAMP(inst == KSQ && KSPN, 44);
        tail_group(1);
        tail_group(2);
        STAMP(inst == KSQ && KSPN, 45);
        const bool ppre = ksp == 7 && w_pre(inst - 1);
        const uint32_t fbar = bars + 8u * (ppre ? (LOCE ? B_LOC : B_EMPTY) + ((n - 1) & 7) : (inst == CSI + 1 ? B_CSD : B_AFREE));
        const uint32_t fpar = ppre ? ((n - 1) >> 3) & 1 : (inst == CSI + 1 ? 0 : ch);
        const bool afree = mbar_test(fbar, fpar);
        float rinv[2][2];
#pragma unroll
        for (int i = 0; i < 4; i++) rinv[i >> 1][i & 1] = rcp_fast(bf_hi(rs[i]));
        const int mat = lane >> 3;
        const uint32_t soff = (wwarp * 16 + (mat & 1) * 8 + (lane & 7)) * 128;
        const uint32_t kdst = ((L & 1) ? KB_ROW0 : slots) + soff, vdst = ((L & 1) ? VB_ROW0 : slots + 8192) + soff;
        const uint32_t hs = (L & 1) ? 8192 : 16384;
        const int rg = 2 * wwarp + (mat & 1);
        const uint32_t qdst = slots + 3 * 16384 + ((L & 1) ? soff : ((rg < 4 ? 2 * rg : 15 - 2 * rg) * 8 + (lane & 7)) * 128);
        wgmma_wait<2>();
        STAMP(inst == KSQ && KSPN, 46);
        fold(0);
        tail_group(3);
        STAMP(inst == KSQ && KSPN, 47);
        warp_arrive(bars + 8u * (B_TURN + (ch ^ 1)));
        if (!afree) {
          wgmma_wait<1>();
          warp_arrive_cl(ebar + 8u * (n & 7));
          wgmma_wait<0>();
          warp_arrive_cl(ebar + 8u * ((n + 1) & 7));
          mbar_wait(fbar, fpar);
        }
        wgmma_wait<2>();
        reg_fence<96>(acc[1]);
        STAMP(inst == KSQ, 15);
#pragma unroll
        for (int t = 0; t < 24; t++) {
          const int h = t < 12 ? 1 : 0, p = (t % 12 / 4 + 1) % 3, jp = t & 3;
          if (t == EPW1) {
            wgmma_wait<1>();
            warp_arrive_cl(ebar + 8u * (n & 7), afree);
          }
          if (t == EPW0) {
            wgmma_wait<0>();
            reg_fence<96>(acc[0]);
            warp_arrive_cl(ebar + 8u * ((n + 1) & 7), afree);
            STAMP(inst == KSQ, 16);
            GTL(2 + L * 8);
          }
          if (t % 12 == 8) {
            rinv[h][0] *= SM_C;
            rinv[h][1] *= SM_C;
          }
          const uint32_t swz = ((2 * jp + (mat >> 1)) ^ (lane & 7)) << 4;
          const float* a = &acc[h][32 * p + 8 * jp];
          const uint32_t dst = p == 0 ? qdst + h * 8192 : (p == 1 ? kdst : vdst) + h * hs;
          stmatrix_x4(dst + swz, pack_bf16x2(a[0] * rinv[h][0], a[1] * rinv[h][0]), pack_bf16x2(a[2] * rinv[h][1], a[3] * rinv[h][1]),
                      pack_bf16x2(a[4] * rinv[h][0], a[5] * rinv[h][0]), pack_bf16x2(a[6] * rinv[h][1], a[7] * rinv[h][1]));
          if (t % 12 == 7) {
            fence_proxy_async_smem();
            if (t == 7) named_bar_arrive(3, (L & 1) ? 192 : 160);
            else if ((L & 1) == 0) named_bar_arrive(7, 160);
            if (t > EPW0) sched_fence(P.zero);
          }
        }
      }
      fence_proxy_async_smem();
      setmaxnreg_dec<128>();
      named_bar_sync(4, 256);
      }
      GTL(3 + L * 8);
      {
        PHASE_IDS
        if ((L & 1) == 0) attention_a(asst, L, gb, hp, inst & 1, ch, (tid_ >> 5) & 3, lane, P.zero);
        else attention_b(asst, gb, inst & 1, wwarp, lane, KSAON);
        GTL(4 + L * 8);
        fence_proxy_async_smem();
      }
      if (!asst) {
      {
        named_bar_sync(5, 256);
        STAMP(KSAON, 27);
        if ((warp & 3) == 0 && elect_one()) {
          tma_store_3d(&P.o, (L & 1) ? slots + 3 * 16384 : OA_TILE, 0, gb * 128, hp);
          bulk_commit();
          bulk_wait0();
          STAMP(KSAON, 31);
          mbar_arrive(bars + 8u * B_AFREE);
          mbar_wait(bars + 8u * B_AFREE, ch ^ 1);
          announce(g_flags + F_O + gb * OSTR + hp);
        }
        __syncwarp();
      }
      GTL(5 + L * 8);

      {
        float acc[64];
        const int n0 = w_first(inst);
        const bool pre = w_pre(inst);
        const uint32_t dl = ((w_flips(inst) + q_split(inst + 1)) & 1) * 10u * UNIT;
        const uint2* tab = P.wtab[2 * pre + (dl != 0)];
        const uint32_t ppar = __popc(PREMASK & ((1u << inst) - 1u)) & 1;
        uint32_t pbar = bars + 8u * B_PRE;
        const uint32_t flg = (pre ? w_emask() >> 1 : 0u) | (inst >= 6 || q_split(inst + 1) != 8 ? 1u << 30 : 0u);
        uint2 e = tab[0];
        mbar_wait_lazy<100>(bars + 8u * (B_TURN + ch), tpar);
        tpar ^= 1u;
        mbar_wait(bars + 8u * (B_FULL + (n0 & 7)), (n0 >> 3) & 1);
        GTL(6 + L * 8);
        auto wstep = [&](auto first_, int kt) {
          constexpr bool first = decltype(first_)::value;
          const int n = n0 + kt;
          STAMP(inst == KSW, 20 + kt);
          wgmma_fence();
          if (first) wgmma_n128_ssz_ta0_tb1(acc, desc_lo(e.x), desc_lo(e.y));
#pragma unroll
          for (int k16 = first ? 1 : 0; k16 < 4; k16++) wgmma_n128_ss_ta0_tb1(acc, desc_lo(e.x + 2 * k16), desc_lo(e.y + 128 * k16), 1);
          wgmma_commit();
          if (!first) warp_arrive(bars + 8u * (B_TURN + (ch ^ 1)), (flg >> kt) & 0x8000u);
          e = tab[kt + 1];
          const uint32_t nb = bars + 8u * (kt == 15 ? B_RESF : B_FULL + ((n + 1) & 7)), np = kt == 15 ? ch : ((n + 1) >> 3) & 1;
          const bool ok = mbar_test(nb, np);
          if (!first) {
            wgmma_wait<1>();
            warp_arrive_cl(ebar + 8u * ((n - 1) & 7));
            if ((flg >> kt) & 1u) {
              mbar_wait(pbar, ppar);
              pbar += 8u;
            }
          }
          if (!ok) mbar_wait(nb, np);
        };
        wstep(std::true_type(), 0);
#pragma unroll WUNR
        for (int kt = 1; kt < 16; kt++) wstep(std::false_type(), kt);
        PHASE_IDS
        const uint32_t xb = e.x;
        const int mat = lane >> 3;
        const uint32_t xrow = xb + (wwarp * 16 + (mat & 1) * 8 + (lane & 7)) * 128;
        uint32_t xv[8][4];
#pragma unroll
        for (int jp = 0; jp < 8; jp++)
          ldmatrix_x4(xv[jp], xrow + (jp >> 2) * UNIT + (((2 * (jp & 3) + (mat >> 1)) ^ (lane & 7)) << 4));
        wgmma_wait<0>();
        reg_fence<64>(acc);
        warp_arrive_cl(ebar + 8u * ((n0 + 15) & 7));
        STAMP(inst == KSW, 36);
        GTL(7 + L * 8);
#pragma unroll
        for (int jp = 0; jp < 8; jp++) {
#pragma unroll
          for (int q = 0; q < 4; q++) xv[jp][q] = add_bf16x2(xv[jp][q], pack_bf16x2(acc[8 * jp + 2 * q], acc[8 * jp + 2 * q + 1]));
          stmatrix_x4(xrow + (jp >> 2) * UNIT + (((2 * (jp & 3) + (mat >> 1)) ^ (lane & 7)) << 4), xv[jp][0], xv[jp][1],
                      xv[jp][2], xv[jp][3]);
        }
        const int grow = ch * 1024 + rt * 64;
        fence_proxy_async_smem();
        named_bar_sync(1 + ch, 128);
        if (wwarp == 0) {
          if (elect_one()) {
            STAMP(inst == KSW, 37);
            tma_store_3d(&P.xr[L == 3 ? 2 : 1], xb, ct * 128, grow, 0);
            bulk_commit();
            bulk_wait0();
            STAMP(inst == KSW, 38);
            mbar_arrive(bars + 8u * B_RESE);
            if (L < 3) announce(g_flags + F_X + (ch * 8 + (rt >> 1)) * XSTR + ct);
            STAMP(inst == KSW, 39);
          }
          __syncwarp();
        } else if (lane == 0) {
          mbar_arrive(bars + 8u * B_RESE);
        }
        if (L < 3) {
          const unsigned ep1 = lds32(base + OFF_EPOCH);
          float s1[2] = {0.f, 0.f}, s2[2] = {0.f, 0.f};
#pragma unroll
          for (int jp = 0; jp < 8; jp++)
#pragma unroll
            for (int q = 0; q < 4; q++) {
              const float x0 = bf_lo(xv[jp][q]), x1 = bf_hi(xv[jp][q]);
              s1[q & 1] += x0 + x1;
              s2[q & 1] = fmaf(x0, x0, fmaf(x1, x1, s2[q & 1]));
            }
#pragma unroll
          for (int r = 0; r < 2; r++) {
            s1[r] += __shfl_xor_sync(0xffffffffu, s1[r], 1);
            s2[r] += __shfl_xor_sync(0xffffffffu, s2[r], 1);
            s1[r] += __shfl_xor_sync(0xffffffffu, s1[r], 2);
            s2[r] += __shfl_xor_sync(0xffffffffu, s2[r], 2);
            if (c == 0) st_rec(&g_stats[L + 1][ct][grow + wwarp * 16 + g + 8 * r], s1[r], s2[r], 0.f, ep1);
          }
        }
        GTL(8 + L * 8);
      }
      continue;
      }
      named_bar_arrive(5, 256);
      if (inst != CSI) continue;
      mbar_wait(bars + 8u * B_AFREE, CSI ^ 1);
      }
      if (asst) {
        colsum_part(&P.wqkv[inst >= 0], inst >= 0, qr, hp);
        warp_arrive(bars + 8u * (inst >= 0 ? B_CSD : B_AFREE), inst >= 0 || warp < 10);
      } else {
      PHASE_IDS
      {
        const unsigned ep1 = (*(volatile unsigned*)(g_flags + F_DONE)) / NCTA + 1u;
        const int row = b * 16 + (tid >> 3);
        const uint4* src = reinterpret_cast<const uint4*>(P.in_x + (size_t)row * DM) + (tid & 7);
        float s1 = 0.f, s2 = 0.f;
#pragma unroll 1
        for (int k = 0; k < 4; k++) {
          mbar_pace(bars + 8u * (B_EMPTY + PXB * k / 2), 0);
          uint4 v[4];
#pragma unroll
          for (int j = 0; j < 4; j++) v[j] = __ldg(src + (k * 4 + j) * 8);
#pragma unroll
          for (int j = 0; j < 4; j++) {
            const uint32_t w[4] = {v[j].x, v[j].y, v[j].z, v[j].w};
#pragma unroll
            for (int e = 0; e < 4; e++) {
              const float x0 = bf_lo(w[e]), x1 = bf_hi(w[e]);
              s1 += x0 + x1;
              s2 = fmaf(x0, x0, fmaf(x1, x1, s2));
            }
          }
        }
#pragma unroll
        for (int o = 1; o < 8; o <<= 1) {
          s1 += __shfl_xor_sync(0xffffffffu, s1, o);
          s2 += __shfl_xor_sync(0xffffffffu, s2, o);
        }
        if ((tid & 7) == 0) st_rec(&g_stats[0][0][row], s1, s2, 0.f, ep1);
        if (tid == 0) sts32(base + OFF_EPOCH, ep1);
        STAMP(KSQ == 0, 51);
        float4 v[6];
#pragma unroll 1
        for (uint32_t it = 0; it < (1u << 17); ++it) {
          bool ok = true;
#pragma unroll
          for (int t = 0; t < 6; t++) {
            v[t] = ld_rec(t < 2 ? &g_stats[0][0][(t * 8 + qr) * 128 + tid] : &g_cs[0][hp][(tid & 1) * 4 + t - 2][tid >> 1]);
            ok &= __float_as_uint(v[t].w) == ep1;
          }
          STAMP(KSQ == 0 && it == 0, 18);
          if (ok) break;
          __nanosleep(100);
        }
        STAMP(KSQ == 0, 17);
        __syncwarp();
        STAMP(KSQ == 0, 19);
#pragma unroll
        for (int cc = 0; cc < 2; cc++) sts32(base + OFF_RS + (cc * 128 + tid) * 4, ln_params(v[cc].x, v[cc].y));
        const float cs[3] = {(v[2].x + v[3].x) + (v[4].x + v[5].x), (v[2].y + v[3].y) + (v[4].y + v[5].y),
                             (v[2].z + v[3].z) + (v[4].z + v[5].z)};
#pragma unroll
        for (int blk = 0; blk < 3; blk++) {
          const float t = cs[blk] + __shfl_xor_sync(0xffffffffu, cs[blk], 1);
          cs_put(blk, tid & 1, tid >> 1, (tid & 1) ? 0.f : t);
        }
        fence_proxy_async_smem();
        named_bar_sync(2, 128);
        if (tid < 2) mbar_arrive(bars + 8u * (B_PREP + tid));
        STAMP(KSQ == 0, 48);
      }
      }
    }
    if (threadIdx.x == 128) atomicAdd(g_flags + F_DONE, 1u);
    if (!asst) asm volatile("barrier.cluster.arrive.relaxed.aligned;\nbarrier.cluster.wait.aligned;" ::: "memory");
    if (P.zero == 0) return;
  } else {
    setmaxnreg_dec<32>();
    if (warp != 12) {
      ROLE_GET
    }
    if (warp != 15) {
    if (warp == 14) {
      ROLE_IDS
      const unsigned ep1 = (*(volatile unsigned*)(g_flags + F_DONE)) / NCTA + 1u;
      uint32_t hbp = 0;
#pragma unroll 1
      for (int inst = 0; inst < 8; inst++) {
        const int L = inst >> 1, ch = inst & 1, gb = ch * 8 + qr;
        if ((L & 1) == 0) {
          const unsigned* fp = g_flags + F_KV + (max(gb - 1 - ((lane >> 1) & 1), 0) * 16 + hp) * KSTR + (lane & 1);
          uint32_t seen = gb == 0 ? 15u : (gb == 1 ? 12u : 0u);
          named_bar_sync(3, 160);
          STA(34);
          if (elect_one()) {
#pragma unroll 1
            for (int o = 0, pc = (PCM >> inst) & 1 ? PCS : 16384; o < 16384; o += pc) {
              bulk_store(g_kvA[L >> 1][gb][hp][1] + o, slots + 16384 + o, pc);
              if ((PCM >> inst) & 1) spin(PCN);
            }
            bulk_commit();
            bulk_wait0();
            STA(35);
            announce(g_flags + F_KV + (gb * 16 + hp) * KSTR);
            STA(41);
          }
          __syncwarp();
#pragma unroll 1
          for (int i = 0; i < 4; i++) {
            wait_lanes(fp, 2u * ep1 - 1u + (L >> 1), 1u << i, seen);
            STA(36 + i);
            if (i > 0) mbar_wait_lazy<RELNS>(bars + 8u * (B_REL + i - 1), ch);
            if (i == 2) mbar_wait(bars + 8u * B_KVS, ch);
            if (elect_one()) {
              mbar_expect_tx(bars + 8u * (B_HALO + i), 16384);
              bulk_load(slots + (i == 3 ? 2 : 2 - i) * 16384, gb > (i >> 1) ? g_kvA[L >> 1][gb - 1 - (i >> 1)][hp][(i & 1) ^ 1] : g_zero,
                        16384, bars + 8u * (B_HALO + i));
            }
          }
        } else {
          const uint8_t* src = gb > 0 ? g_kvB[L >> 1][gb - 1][hp] : g_zero;
          const uint32_t o = slots + lane * 32 + (lane & 28);
          named_bar_sync(3, 192);
          STA(34);
          if (elect_one()) spin(HBD);
          __syncwarp();
#pragma unroll 1
          for (uint32_t it = 0; it < (1u << 16); ++it) {
            if (elect_one()) {
              mbar_expect_tx(bars + 8u * B_HB, 4096);
              bulk_load(KB_ROW0 - 2048, src, 2048, bars + 8u * B_HB);
              bulk_load(VB_ROW0 - 2048, src + 2048, 2048, bars + 8u * B_HB);
            }
            mbar_wait(bars + 8u * B_HB, hbp);
            hbp ^= 1u;
            const uint32_t m = max(max(lds32(o), lds32(o + 1024)), max(lds32(o + 24576), lds32(o + 24576 + 1024)));
            STA(36 + min(it, 3u));
            if (__reduce_max_sync(0xffffffffu, m) != 0xffffffffu) break;
            fence_proxy_async_smem();
            __syncwarp();
          }
          warp_arrive(bars + 8u * B_HALO);
        }
        named_bar_sync(9, 288);
        if (elect_one()) {
          tma_store_3d(&P.o, ((L & 1) ? slots + 3 * 16384 : OA_TILE) + 8192, 0, gb * 128 + 64, hp);
          bulk_commit();
          bulk_wait0();
          mbar_arrive(bars + 8u * B_AFREE);
        }
        __syncwarp();
        if (w_pre(inst)) {
          mbar_wait(bars + 8u * B_KVS, ch);
          mbar_wait(bars + 8u * B_AFREE, (inst & 1) ^ 1);
          if (inst == CSI) mbar_wait(bars + 8u * B_CSD, 0);
#pragma unroll 1
          for (int j = 0; j < 4; j++) {
            constexpr uint32_t early = w_early();
            if (elect_one()) {
              mbar_expect_tx(bars + 8u * (B_PRE + j), 2 * UNIT);
              tma_load_3d(slots + j * 2 * UNIT, &P.wo[L & 1], bars + 8u * (B_PRE + j), ct * 128, ((early >> (4 * j)) & 15) * 64, 0);
            }
            __nanosleep(PRENS);
          }
        }
      }
    } else if (warp == 13) {
      ROLE_IDS
      uint32_t n = 16 + rank, dl = 0;
      uint32_t back = 0x44444444u;
      mbar_wait(bars + 8u * B_GO, 0);
      const unsigned ep1 = __shfl_sync(0xffffffffu, (*(volatile unsigned*)(g_flags + F_DONE)) / NCTA + 1u, 0);
#pragma unroll 1
      for (int sg = 4; sg < 34; sg++) {
        const int part = sg & 3, si = (sg >> 2) - (part & 1), L = si >> 1, ch = si & 1;
        const int k0 = part == 2 ? 2 * q_split(si) : 0, k1 = part == 0 ? 2 * q_split(si) : 16;
        if (part == 3 || k0 == k1) continue;
        const bool wj = part == 1;
        uint32_t seen = 0u;
        if (!wj && (L == 0 || __any_sync(0xffffffffu, mbar_test(bars + 8u * (B_XRDY + ch), (L & 1) ^ 1)))) {
          seen = 0xFFFFu;
          fence_proxy_async_all();
        }
        const CUtensorMap* map = wj ? &P.o : &P.xq[L == 0 ? 0 : 1];
        const unsigned* fl = g_flags + (wj ? F_O + (ch * 8 + (rt >> 1)) * OSTR : F_X + (ch * 8 + qr) * XSTR);
        const unsigned target = wj ? 4u * ep1 - 3u + L : 6u * ep1 - 6u + 2u * L;
        const int row = ch * 1024 + (wj ? rt * 64 : qr * 128);
        const bool pre = w_pre(si);
        uint64_t units = rank ? 0x0f050f050f050f05ull : 0x0a000a000a000a00ull;
        if (wj) {
          constexpr uint32_t b00 = (uint32_t)w_tab(2, 0, 0, 2, 8, 4), b01 = (uint32_t)w_tab(2, 0, 1, 2, 8, 4), b10 = (uint32_t)w_tab(2, 1, 0, 2, 8, 4),
                             b11 = (uint32_t)w_tab(2, 1, 1, 2, 8, 4), b20 = (uint32_t)w_tab(2, 2, 0, 2, 8, 4), b21 = (uint32_t)w_tab(2, 2, 1, 2, 8, 4);
          constexpr uint64_t u00 = w_tab(0, 0, 0, 2, 8, 8), u01 = w_tab(0, 0, 1, 2, 8, 8), u10 = w_tab(0, 1, 0, 2, 8, 8), u11 = w_tab(0, 1, 1, 2, 8, 8);
          back = pre ? (rank ? b11 : b10) : (si == 7 ? (rank ? b21 : b20) : (rank ? b01 : b00));
          units = pre ? (rank ? u11 : u10) : (rank ? u01 : u00);
        }
#pragma unroll 1
        for (int kt = k0 + rank; kt < k1; kt += 2, n += 2, back = (back >> 4) | 0x40000000u, units >>= 8) {
          wait_mask<false>(fl, 16, target, 1u << (wj ? kt : kt >> 1), seen, lane);
          const uint32_t nw = n - (back & 15u), pos = ((uint32_t)units & 31u) * UNIT + dl;
          mbar_wait(bars + 8u * (B_EMPTY + (nw & 7u)), (nw >> 3) & 1u);
          if (elect_one())
            tma_load_3d_mc(base + (pos >= 20 * UNIT ? pos - 20 * UNIT : pos), map, bars + 8u * (B_FULL + (n & 7u)), 0, row, kt);
        }
        if (wj ? !pre || PRE_FLIP : ((k1 - k0) & 2)) dl ^= 10u * UNIT;
        constexpr uint32_t q00 = q_backs(true, 0, false), q01 = q_backs(true, 1, false), q10 = q_backs(true, 0, true), q11 = q_backs(true, 1, true);
        if (wj) back = pre ? (rank ? q11 : q10) : (rank ? q01 : q00);
      }
    } else {
#pragma unroll 1
      for (int att = P.zero; att < 2; att++) {
        ROLE_IDS
#pragma unroll 1
        for (int s = 0; s < 4; s++) {
          if (elect_one()) {
            mbar_expect_tx(bars + 8u * (B_FULL + s), 5 * UNIT);
            tma_load_3d(base + s * 5 * UNIT, &P.xq[0], bars + 8u * (B_FULL + s), 0, qr * 128, s);
            tma_load_3d(base + (s * 5 + 2) * UNIT, &P.wqkv[0], bars + 8u * (B_FULL + s), hp * 64, s * 64, 0);
          }
        }
        if (att) break;
        asm volatile("barrier.cluster.wait.aligned;" ::: "memory");
        mbar_wait(bars + 8u * B_ROLE, 0);
        const int r = __shfl_sync(0xffffffffu, (int)lds32(base + OFF_ROLE), 0);
        if (r == role) break;
        role = r;
#pragma unroll 1
        for (int s = 0; s < 4; s++) {
          mbar_wait(bars + 8u * (B_FULL + s), 0);
          __syncwarp();
          if (elect_one()) {
            asm volatile("mbarrier.inval.shared::cta.b64 [%0];" ::"r"(sw(bars + 8u * (B_FULL + s))) : "memory");
            mbar_init(bars + 8u * (B_FULL + s), 1);
          }
        }
        fence_barrier_init();
        fence_proxy_async_smem();
        __syncwarp();
      }
      named_bar_arrive(0, 512);
      ROLE_IDS
#pragma unroll 1
      for (int s = 4; s < 16; s++) {
        const uint32_t fb = bars + 8u * (B_FULL + (s & 7)), sa = base + (s & 3) * 5 * UNIT;
        mbar_wait(bars + 8u * (B_EMPTY + ((s - 4) & 7)), ((s - 4) >> 3) & 1);
        if (elect_one()) {
          mbar_expect_tx(fb, 5 * UNIT);
          if ((s & 1) == rank) tma_load_3d_mc(sa, &P.xq[0], fb, 0, qr * 128, s);
          tma_load_3d(sa + 2 * UNIT, &P.wqkv[0], fb, hp * 64, s * 64, 0);
        }
      }
      if (elect_one()) mbar_arrive(bars + 8u * B_GO);
      const uint32_t wbase = sw(base), wbars = sw(bars);
      uint2 e = P.ptab[0];
#pragma unroll 1
      for (int i = 1; i <= NPT; i++) {
        const uint32_t wb = (e.x & 0x1f8u) | wbars, par = e.x >> 31, fl = e.x;
        uint32_t dst = (e.x & 0x3e000u) | wbase, fb = (e.y & 0x1f8u) | wbars, bytes = e.y & 0xe000u, nold = e.y & 1u;
        int c0 = (e.x & (1u << 29)) ? hp * 64 : ct * 128, c1 = ((e.x >> 18) & 0x7ffu) + ((e.x & (1u << 30)) ? rt * 64 : 0);
        const char* map = reinterpret_cast<const char*>(&P) + (e.y >> 21);
        asm volatile("" : "+r"(dst), "+r"(fb), "+r"(bytes), "+r"(nold), "+r"(c0), "+r"(c1), "+l"(map));
        e = P.ptab[i];
        if (fl & 2u) mbar_wait(bars + 8u * B_RESE, (fl >> 2) & 1u);
        if (!(fl & 1u)) mbar_wait_raw(wb, par);
        asm volatile(
            "{\n.reg .pred p, q;\nelect.sync _|p, 0xffffffff;\nsetp.eq.and.u32 q, %6, 0, p;\n"
            "@p mbarrier.arrive.expect_tx.shared::cta.b64 _, [%2], %5;\n"
            "@q cp.async.bulk.tensor.3d.shared::cluster.global.mbarrier::complete_tx::bytes [%0], [%1, {%3, %4, %7}], [%2];\n}\n" ::"r"(dst),
            "l"(map), "r"(fb), "r"(c0), "r"(c1), "r"(bytes), "r"(nold), "r"(0)
            : "memory");
      }
    }
    return;
    }
  }
  {
    {
      ROLE_IDS
      const unsigned ep1 = (*(volatile unsigned*)(g_flags + F_DONE)) / NCTA + 1u;
#pragma unroll 1
      for (int inst = 0; inst < 8; inst++) {
        const int L = inst >> 1, ch = inst & 1, gb = ch * 8 + qr;
        if (inst == 1 || inst == 2) {
#pragma unroll 1
          for (int i = inst == 1 ? 0 : TRSP; i < (inst == 1 ? TRSP : 20); i++) {
            const char* src = i < 4 ? reinterpret_cast<const char*>(P.wo_p[0]) + i * 524288
                                    : (i < 16 ? reinterpret_cast<const char*>(P.wqkv_p1) + (i - 4) * 524288
                                              : reinterpret_cast<const char*>(P.wo_p[1]) + (i - 16) * 524288);
            asm volatile("prefetch.global.L2 [%0];" ::"l"(src + b * 4096 + lane * 128));
            __nanosleep(inst == 1 ? TRICKLE : TRICK2);
          }
        }
        if (inst >= 2) {
        uint32_t seen = 0;
        wait_mask<true>(g_flags + F_X + gb * XSTR, 8, 6u * ep1 - 6u + 2u * L, 0xFFu, seen, lane);
        if (lane == 0) mbar_arrive(bars + 8u * (B_XRDY + ch));
#pragma unroll 1
        for (int h = 0; h < 4; h++) {
          const float4* sp = &g_stats[L][0][gb * 128 + h * 32 + lane];
          const float4 s0 = sum_recs<4>(sp, S_LEN, ep1), s1 = sum_recs<4>(sp + 4 * S_LEN, S_LEN, ep1);
          sts32(base + OFF_RS + (ch * 128 + h * 32 + lane) * 4, ln_params(s0.x + s1.x, s0.y + s1.y));
        }
        if (inst == 2) {
          mbar_wait(bars + 8u * B_CSD, 0);
#pragma unroll 1
          for (int hf = 0; hf < 2; hf++) {
            const float4* cp = &g_cs[1][hp][0][hf * 32 + lane];
            const float4 s0 = sum_recs<4>(cp, 64, ep1), s1 = sum_recs<4>(cp + 4 * 64, 64, ep1);
            cs_put(0, 1, hf * 32 + lane, s0.x + s1.x);
            cs_put(1, 1, hf * 32 + lane, s0.y + s1.y);
            cs_put(2, 1, hf * 32 + lane, s0.z + s1.z);
          }
          fence_proxy_async_smem();
        }
        __syncwarp();
        if (lane == 0) mbar_arrive(bars + 8u * (B_PREP + ch));
        }
        named_bar_sync((L & 1) ? 3 : 7, (L & 1) ? 192 : 160);
        if (elect_one()) {
          if (L & 1) {
            bulk_store(g_kvB[L >> 1][gb][hp], KB_ROW0 + 112 * 128, 2048);
            bulk_store(g_kvB[L >> 1][gb][hp] + 2048, VB_ROW0 + 112 * 128, 2048);
          } else {
            spin(PDL);
#pragma unroll 1
            for (int o = 0, pc = (PCM >> inst) & 1 ? PCS : 16384; o < 16384; o += pc) {
              bulk_store(g_kvA[L >> 1][gb][hp][0] + o, slots + o, pc);
              if ((PCM >> inst) & 1) spin(PCN);
            }
          }
          bulk_commit();
          bulk_wait0();
          mbar_arrive(bars + 8u * B_KVS);
          STA(32);
          if ((L & 1) == 0) {
            announce(g_flags + F_KV + (gb * 16 + hp) * KSTR + 1);
          }
          STA(33);
        }
        __syncwarp();
      }
    }
  }
}

typedef CUresult (*PFN_tmEncode)(CUtensorMap*, CUtensorMapDataType, cuuint32_t, void*, const cuuint64_t*,
                                 const cuuint64_t*, const cuuint32_t*, const cuuint32_t*, CUtensorMapInterleave,
                                 CUtensorMapSwizzle, CUtensorMapL2promotion, CUtensorMapFloatOOBfill);

PFN_tmEncode get_encode_fn() {
  static PFN_tmEncode fn = nullptr;
  if (!fn) {
    cudaDriverEntryPointQueryResult qr;
    void* p = nullptr;
    cudaGetDriverEntryPoint("cuTensorMapEncodeTiled", &p, cudaEnableDefault, &qr);
    fn = (PFN_tmEncode)p;
  }
  return fn;
}

CUtensorMap make_map(const void* ptr, int rows, int cols, int inner, int blocks, int bs, int box_rows, int box_blk) {
  CUtensorMap m;
  cuuint64_t gdim[3] = {(cuuint64_t)inner, (cuuint64_t)rows, (cuuint64_t)blocks};
  cuuint64_t gstr[2] = {(cuuint64_t)cols * 2, (cuuint64_t)bs * 2};
  cuuint32_t box[3] = {64, (cuuint32_t)box_rows, (cuuint32_t)box_blk};
  cuuint32_t estr[3] = {1, 1, 1};
  get_encode_fn()(&m, CU_TENSOR_MAP_DATA_TYPE_BFLOAT16, 3, const_cast<void*>(ptr), gdim, gstr, box, estr,
                  CU_TENSOR_MAP_INTERLEAVE_NONE, CU_TENSOR_MAP_SWIZZLE_128B, CU_TENSOR_MAP_L2_PROMOTION_L2_128B,
                  CU_TENSOR_MAP_FLOAT_OOB_FILL_NONE);
  return m;
}

void make_tables(Params& P) {
  const WPlan pl[3] = {w_plan(0), w_plan(1), w_plan(2)};
  for (int m = 0; m < 4; m++)
    for (int kt = 0; kt < 17; kt++) {
      const WPlan& p = pl[m >> 1];
      const uint32_t dl = (m & 1) * 10u * UNIT;
      P.wtab[m][kt] = make_uint2(kt == 16 ? SBASE + unit_off(p.v[1][kt], dl) : ((SBASE + unit_off(p.v[0][kt], dl)) >> 4) + 0x10000u,
                                 ((SBASE + unit_off(p.v[1][kt], dl)) >> 4) + ((UNIT >> 4) << 16));
    }
  int np = 0;
  auto put = [&](int nw, int rp, uint32_t off, int c1, int kind, int fb, int units, const CUtensorMap* map) {
    P.ptab[np++] = make_uint2((nw < 0 ? 1u : 8u * ((LOCE ? B_LOC : B_EMPTY) + (nw & 7)) | (uint32_t)((nw >> 3) & 1) << 31) | (rp < 0 ? 0u : 2u | 4u * rp) |
                                  off | (uint32_t)c1 << 18 | (uint32_t)kind << 29,
                              8u * fb | (map ? 0u : 1u) | units * UNIT |
                                  (map ? (uint32_t)(reinterpret_cast<const char*>(map) - reinterpret_cast<const char*>(&P)) << 21 : 0u));
  };
  int n = 16, aw = 0;
  uint32_t dl = 0;
  uint32_t back = 0x44444444u;
  for (int sg = 4; sg < 34; sg++) {
    const int part = sg & 3, si = (sg >> 2) - (part & 1), L = si >> 1, ch = si & 1;
    const int k0 = part == 2 ? 2 * q_split(si) : 0, k1 = part == 0 ? 2 * q_split(si) : 16;
    if (part == 3) continue;
    if (part != 1) {
      for (int k2 = k0; k2 < k1; k2 += 2, aw--, dl ^= 10u * UNIT)
        for (int ks = 0; ks < 2; ks++, n++, back = (back >> 4) | 0x40000000u)
          put(n - (int)(back & 15u), ks == 1 && aw == 1 ? (part == 2) ^ ch : -1, (ks * 5 + 2) * UNIT + dl, (k2 + ks) * 64, 1,
              B_FULL + (n & 7), 5, &P.wqkv[L & 1]);
    } else {
      const bool pre = w_pre(si);
      const WPlan& p = pl[pre ? 1 : (aw == 2 ? 2 : 0)];
      for (int kt = 0; kt < 17; kt++) {
        const bool early = kt < 16 && p.v[5][kt];
        put(p.v[4][kt] ? n + kt - p.v[3][kt] : -1, !pre && kt == 6 && aw == 2 ? ch ^ 1 : -1, unit_off(p.v[1][kt], dl),
            kt == 16 ? ch * 1024 : kt * 64, kt == 16 ? 2 : 0, kt == 16 ? B_RESF : B_FULL + ((n + kt) & 7),
            kt == 16 ? 2 : (early ? 1 : 3), kt == 16 ? &P.xr[L == 0 ? 0 : 1] : (early ? nullptr : &P.wo[L & 1]));
      }
      n += 16;
      if (!pre || PRE_FLIP) dl ^= 10u * UNIT;
      back = q_backs(false, 0, pre);
      aw = 2;
    }
  }
  P.ptab[np] = make_uint2(0, 0);
}

}

extern "C" void kernel_launch(void* const* d_in, const int* in_sizes, int n_in, void* d_out, int out_size) {
  (void)in_sizes; (void)n_in; (void)out_size;
  void *p_o, *p_x;
  cudaGetSymbolAddress(&p_o, g_o);
  cudaGetSymbolAddress(&p_x, g_x);
  static bool attr_done = false;
  if (!attr_done) {
    cudaFuncSetAttribute(fused_kernel, cudaFuncAttributeMaxDynamicSharedMemorySize, SMEM_BYTES);
    attr_done = true;
  }
  Params P;
  P.in_x = (const __nv_bfloat16*)d_in[0];
  P.wo_p[0] = (const __nv_bfloat16*)d_in[2];
  P.wqkv_p1 = (const __nv_bfloat16*)d_in[4];
  P.wo_p[1] = (const __nv_bfloat16*)d_in[5];
  P.zero = 0;
  P.xq[0] = make_map(P.in_x, S_LEN, DM, 64, 16, 64, 128, 1);
  P.xq[1] = make_map(p_x, S_LEN, DM, 64, 16, 64, 128, 1);
  P.xr[0] = make_map(P.in_x, S_LEN, DM, DM - 64, 2, 64, 64, 2);
  P.xr[1] = make_map(p_x, S_LEN, DM, DM - 64, 2, 64, 64, 2);
  P.xr[2] = make_map(d_out, S_LEN, DM, DM - 64, 2, 64, 64, 2);
  P.o = make_map(p_o, S_LEN, DM, 64, 16, 64, 64, 1);
  for (int t = 0; t < 2; t++) {
    P.wqkv[t] = make_map(d_in[3 * t + 1], DM, NQKV, 1024, 3, 1024, 64, 3);
    P.wo[t] = make_map(P.wo_p[t], DM, DM, DM - 64, 2, 64, 64, 2);
  }
  make_tables(P);
  fused_kernel<<<NCTA, 512, SMEM_BYTES>>>(P);
}
```

```cpp
#include <cuda_runtime.h>
#include <cuda_bf16.h>
#include <cuda.h>
#include <stdint.h>
#include <type_traits>

namespace {

constexpr int S_LEN = 2048;
constexpr int DM = 1024;
constexpr int NQKV = 3072;
constexpr int NCTA = 128;

__device__ __align__(1024) uint8_t g_kvA[2][16][16][2][16384];
__device__ __align__(1024) uint8_t g_kvB[2][16][16][4096];
__device__ __align__(1024) uint8_t g_zero[16384];
__device__ __align__(1024) __nv_bfloat16 g_o[S_LEN * DM];
__device__ __align__(1024) __nv_bfloat16 g_x[S_LEN * DM];
__device__ __align__(1024) float4 g_stats[4][8][S_LEN];
__device__ __align__(1024) float4 g_cs[2][16][8][64];
#define RSTR 1
constexpr int F_X = 0;
constexpr int XSTR = 32, OSTR = 32, KSTR = 32;
constexpr int F_O = F_X + 16 * XSTR;
constexpr int F_KV = F_O + 16 * OSTR;
constexpr int F_DONE = F_KV + 256 * KSTR;
constexpr int F_ROLE = F_DONE + 32;
__device__ __align__(1024) unsigned g_flags[F_ROLE + 64 * RSTR];

constexpr uint32_t SBASE = 1024;
constexpr int UNIT = 8192;
constexpr int NUNITS = 20;
constexpr int OFF_SLOT = NUNITS * UNIT;
constexpr int OFF_CS = OFF_SLOT + 4 * 16384;
constexpr int OFF_RS = OFF_CS + 1536;
constexpr int OFF_BAR = OFF_RS + 1024;
constexpr int OFF_EPOCH = OFF_BAR + 400, OFF_ROLE = OFF_BAR + 404;
constexpr int OFF_TS = OFF_BAR + 408;
constexpr int SMEM_BYTES = OFF_TS;
constexpr int B_FULL = 0, B_EMPTY = 8, B_PREP = 16, B_HALO = 18, B_REL = 22, B_AFREE = 25, B_TURN = 26, B_XRDY = 28,
              B_CS = 30, B_CSD = 31, B_GO = 32, B_RESF = 33, B_RESE = 34, B_PRE = 35, B_ROLE = 39, B_LOC = 40, B_HB = 48, B_KVS = 49;

__device__ __forceinline__ uint32_t smem_u32(const void* p) { return (uint32_t)__cvta_generic_to_shared(p); }
extern __shared__ __align__(1024) uint8_t smem_raw[];
__device__ __forceinline__ uint32_t sw(uint32_t a) {
  uint32_t r;
  asm volatile("add.u32 %0, %1, %2;" : "=r"(r) : "r"(a), "r"(smem_u32(smem_raw) - SBASE));
  return r;
}

__device__ __forceinline__ void mbar_init(uint32_t bar, uint32_t cnt) {
  asm volatile("mbarrier.init.shared::cta.b64 [%0], %1;" ::"r"(sw(bar)), "r"(cnt));
}
__device__ __forceinline__ void mbar_expect_tx(uint32_t bar, uint32_t bytes) {
  asm volatile("mbarrier.arrive.expect_tx.shared::cta.b64 _, [%0], %1;" ::"r"(sw(bar)), "r"(bytes) : "memory");
}
__device__ __forceinline__ void mbar_arrive(uint32_t bar) {
  asm volatile("mbarrier.arrive.shared::cta.b64 _, [%0];" ::"r"(sw(bar)) : "memory");
}
__device__ __forceinline__ void warp_arrive(uint32_t bar, bool cond = true) {
  asm volatile("{\n.reg .pred p;\nelect.sync _|p, 0xffffffff;\nsetp.ne.and.b32 p, %1, 0, p;\n"
               "@p mbarrier.arrive.shared::cta.b64 _, [%0];\n}\n" ::"r"(sw(bar)), "r"((uint32_t)cond) : "memory");
}
__device__ __forceinline__ void warp_arrive_cl(uint32_t bar, bool cond = true) {
  asm volatile("{\n.reg .pred p;\nelect.sync _|p, 0xffffffff;\nsetp.ne.and.b32 p, %1, 0, p;\n"
               "@p mbarrier.arrive.shared::cluster.b64 _, [%0];\n}\n" ::"r"(bar), "r"((uint32_t)cond) : "memory");
}
__device__ __forceinline__ bool mbar_try_wait(uint32_t bar, uint32_t parity) {
  uint32_t ok;
  asm volatile(
      "{\n.reg .pred p;\nmbarrier.try_wait.parity.shared::cta.b64 p, [%1], %2;\nselp.b32 %0, 1, 0, p;\n}\n"
      : "=r"(ok)
      : "r"(sw(bar)), "r"(parity)
      : "memory");
  return ok != 0;
}
__device__ __forceinline__ bool mbar_test(uint32_t bar, uint32_t parity) {
  uint32_t ok;
  asm volatile(
      "{\n.reg .pred p;\nmbarrier.test_wait.parity.shared::cta.b64 p, [%1], %2;\nselp.b32 %0, 1, 0, p;\n}\n"
      : "=r"(ok)
      : "r"(sw(bar)), "r"(parity)
      : "memory");
  return ok != 0;
}
__device__ __forceinline__ void mbar_wait(uint32_t bar, uint32_t parity) {
#pragma unroll 1
  for (uint32_t it = 0; it < (1u << 18); ++it) {
    if (mbar_try_wait(bar, parity)) return;
  }
}
__device__ __forceinline__ void mbar_wait_raw(uint32_t bar, uint32_t parity) {
#pragma unroll 1
  for (uint32_t it = 0; it < (1u << 18); ++it) {
    uint32_t ok;
    asm volatile(
        "{\n.reg .pred p;\nmbarrier.try_wait.parity.shared::cta.b64 p, [%1], %2;\nselp.b32 %0, 1, 0, p;\n}\n"
        : "=r"(ok)
        : "r"(bar), "r"(parity)
        : "memory");
    if (ok) return;
  }
}
__device__ __forceinline__ void spin(uint32_t cyc) {
  uint32_t c0, c;
  asm volatile("mov.u32 %0, %%clock;" : "=r"(c0));
  do { asm volatile("mov.u32 %0, %%clock;" : "=r"(c)); } while (c - c0 < cyc);
}
__device__ __forceinline__ void mbar_pace(uint32_t bar, uint32_t parity) {
#pragma unroll 1
  for (uint32_t it = 0; it < 24; ++it) {
    if (mbar_try_wait(bar, parity)) return;
  }
}
template <int NS>
__device__ __forceinline__ void mbar_wait_lazy(uint32_t bar, uint32_t parity) {
#pragma unroll 1
  for (uint32_t it = 0; it < (1u << 18); ++it) {
    if (mbar_try_wait(bar, parity)) return;
    __nanosleep(NS);
  }
}
__device__ __forceinline__ bool elect_one() {
  uint32_t ok;
  asm volatile("{\n.reg .pred p;\nelect.sync _|p, 0xffffffff;\nselp.b32 %0, 1, 0, p;\n}\n" : "=r"(ok));
  return ok != 0;
}
__device__ __forceinline__ void fence_barrier_init() { asm volatile("fence.mbarrier_init.release.cluster;" ::: "memory"); }
__device__ __forceinline__ void fence_proxy_async_smem() { asm volatile("fence.proxy.async.shared::cta;" ::: "memory"); }
__device__ __forceinline__ void fence_proxy_async_all() { asm volatile("fence.proxy.async.global;" ::: "memory"); }

__device__ __forceinline__ void tma_load_3d(uint32_t dst, const CUtensorMap* map, uint32_t bar, int c0, int c1, int c2) {
  asm volatile(
      "cp.async.bulk.tensor.3d.shared::cluster.global.mbarrier::complete_tx::bytes [%0], [%1, {%3, %4, %5}], [%2];" ::"r"(sw(dst)),
      "l"(map), "r"(sw(bar)), "r"(c0), "r"(c1), "r"(c2)
      : "memory");
}
__device__ __forceinline__ void tma_load_3d_mc(uint32_t dst, const CUtensorMap* map, uint32_t bar, int c0, int c1, int c2) {
  asm volatile(
      "cp.async.bulk.tensor.3d.shared::cluster.global.mbarrier::complete_tx::bytes.multicast::cluster [%0], [%1, {%3, %4, %5}], [%2], %6;" ::"r"(sw(dst)),
      "l"(map), "r"(sw(bar)), "r"(c0), "r"(c1), "r"(c2), "h"((unsigned short)3)
      : "memory");
}
__device__ __forceinline__ void bulk_load(uint32_t dst, const void* src, uint32_t bytes, uint32_t bar) {
  asm volatile("cp.async.bulk.shared::cluster.global.mbarrier::complete_tx::bytes [%0], [%1], %2, [%3];" ::"r"(sw(dst)),
               "l"(src), "r"(bytes), "r"(sw(bar))
               : "memory");
}
__device__ __forceinline__ void bulk_store(void* dst, uint32_t src, uint32_t bytes) {
  asm volatile("cp.async.bulk.global.shared::cta.bulk_group [%0], [%1], %2;" ::"l"(dst), "r"(sw(src)), "r"(bytes) : "memory");
}
__device__ __forceinline__ void tma_store_3d(const CUtensorMap* map, uint32_t src, int c0, int c1, int c2) {
  asm volatile("cp.async.bulk.tensor.3d.global.shared::cta.bulk_group [%0, {%2, %3, %4}], [%1];" ::"l"(map), "r"(sw(src)),
               "r"(c0), "r"(c1), "r"(c2)
               : "memory");
}
__device__ __forceinline__ void bulk_commit() { asm volatile("cp.async.bulk.commit_group;" ::: "memory"); }
__device__ __forceinline__ void bulk_wait_read0() { asm volatile("cp.async.bulk.wait_group.read 0;" ::: "memory"); }
__device__ __forceinline__ void bulk_wait0() { asm volatile("cp.async.bulk.wait_group 0;" ::: "memory"); }
__device__ __forceinline__ void named_bar_sync(int id, int nthreads) {
  asm volatile("bar.sync %0, %1;" ::"r"(id), "r"(nthreads) : "memory");
}
__device__ __forceinline__ void named_bar_arrive(int id, int nthreads) {
  asm volatile("bar.arrive %0, %1;" ::"r"(id), "r"(nthreads) : "memory");
}

__device__ __forceinline__ void wgmma_fence() { asm volatile("wgmma.fence.sync.aligned;\n" ::: "memory"); }
__device__ __forceinline__ void wgmma_commit() { asm volatile("wgmma.commit_group.sync.aligned;\n" ::: "memory"); }
template <int N>
__device__ __forceinline__ void wgmma_wait() {
  asm volatile("wgmma.wait_group.sync.aligned %0;\n" ::"n"(N) : "memory");
}
template <int R>
__device__ __forceinline__ void setmaxnreg_inc() { asm volatile("setmaxnreg.inc.sync.aligned.u32 %0;\n" ::"n"(R)); }
template <int R>
__device__ __forceinline__ void setmaxnreg_dec() { asm volatile("setmaxnreg.dec.sync.aligned.u32 %0;\n" ::"n"(R)); }
template <int N>
__device__ __forceinline__ void reg_fence(float* r) {
#pragma unroll
  for (int i = 0; i < N; i++) asm volatile("" : "+f"(r[i])::"memory");
}

template <int N>
__device__ __forceinline__ void reg_define(float* r) {
#pragma unroll
  for (int i = 0; i < N; i++) r[i] = 0.f;
}

__device__ __forceinline__ uint64_t desc_lo(uint32_t lo) {
  uint64_t d;
  asm("mov.b64 %0, {%1, %2};" : "=l"(d) : "r"(lo), "r"(0x40000040u));
  return d;
}
__device__ __forceinline__ uint64_t make_desc(uint32_t addr, uint32_t lbo_bytes) {
  return desc_lo((addr >> 4) + ((lbo_bytes >> 4) << 16));
}

__device__ __forceinline__ void wgmma_n192_ss_ta0_tb1(float* d, uint64_t descA, uint64_t descB, int scaleD) {
  asm volatile("{\n.reg .pred p;\nsetp.ne.b32 p, %98, 0;\n"
    "wgmma.mma_async.sync.aligned.m64n192k16.f32.bf16.bf16 {%0, %1, %2, %3, %4, %5, %6, %7, %8, %9, %10, %11, %12, %13, %14, %15, %16, %17, %18, %19, %20, %21, %22, %23, %24, %25, %26, %27, %28, %29, %30, %31, %32, %33, %34, %35, %36, %37, %38, %39, %40, %41, %42, %43, %44, %45, %46, %47, %48, %49, %50, %51, %52, %53, %54, %55, %56, %57, %58, %59, %60, %61, %62, %63, %64, %65, %66, %67, %68, %69, %70, %71, %72, %73, %74, %75, %76, %77, %78, %79, %80, %81, %82, %83, %84, %85, %86, %87, %88, %89, %90, %91, %92, %93, %94, %95}, %96, %97, p, 1, 1, 0, 1;\n}\n"
    : "+f"(d[0]), "+f"(d[1]), "+f"(d[2]), "+f"(d[3]), "+f"(d[4]), "+f"(d[5]), "+f"(d[6]), "+f"(d[7]), "+f"(d[8]), "+f"(d[9]), "+f"(d[10]), "+f"(d[11]), "+f"(d[12]), "+f"(d[13]), "+f"(d[14]), "+f"(d[15]), "+f"(d[16]), "+f"(d[17]), "+f"(d[18]), "+f"(d[19]), "+f"(d[20]), "+f"(d[21]), "+f"(d[22]), "+f"(d[23]), "+f"(d[24]), "+f"(d[25]), "+f"(d[26]), "+f"(d[27]), "+f"(d[28]), "+f"(d[29]), "+f"(d[30]), "+f"(d[31]), "+f"(d[32]), "+f"(d[33]), "+f"(d[34]), "+f"(d[35]), "+f"(d[36]), "+f"(d[37]), "+f"(d[38]), "+f"(d[39]), "+f"(d[40]), "+f"(d[41]), "+f"(d[42]), "+f"(d[43]), "+f"(d[44]), "+f"(d[45]), "+f"(d[46]), "+f"(d[47]), "+f"(d[48]), "+f"(d[49]), "+f"(d[50]), "+f"(d[51]), "+f"(d[52]), "+f"(d[53]), "+f"(d[54]), "+f"(d[55]), "+f"(d[56]), "+f"(d[57]), "+f"(d[58]), "+f"(d[59]), "+f"(d[60]), "+f"(d[61]), "+f"(d[62]), "+f"(d[63]), "+f"(d[64]), "+f"(d[65]), "+f"(d[66]), "+f"(d[67]), "+f"(d[68]), "+f"(d[69]), "+f"(d[70]), "+f"(d[71]), "+f"(d[72]), "+f"(d[73]), "+f"(d[74]), "+f"(d[75]), "+f"(d[76]), "+f"(d[77]), "+f"(d[78]), "+f"(d[79]), "+f"(d[80]), "+f"(d[81]), "+f"(d[82]), "+f"(d[83]), "+f"(d[84]), "+f"(d[85]), "+f"(d[86]), "+f"(d[87]), "+f"(d[88]), "+f"(d[89]), "+f"(d[90]), "+f"(d[91]), "+f"(d[92]), "+f"(d[93]), "+f"(d[94]), "+f"(d[95])
    : "l"(descA), "l"(descB), "r"(scaleD));
}

__device__ __forceinline__ void wgmma_n128_ss_ta0_tb1(float* d, uint64_t descA, uint64_t descB, int scaleD) {
  asm volatile("{\n.reg .pred p;\nsetp.ne.b32 p, %66, 0;\n"
    "wgmma.mma_async.sync.aligned.m64n128k16.f32.bf16.bf16 {%0, %1, %2, %3, %4, %5, %6, %7, %8, %9, %10, %11, %12, %13, %14, %15, %16, %17, %18, %19, %20, %21, %22, %23, %24, %25, %26, %27, %28, %29, %30, %31, %32, %33, %34, %35, %36, %37, %38, %39, %40, %41, %42, %43, %44, %45, %46, %47, %48, %49, %50, %51, %52, %53, %54, %55, %56, %57, %58, %59, %60, %61, %62, %63}, %64, %65, p, 1, 1, 0, 1;\n}\n"
    : "+f"(d[0]), "+f"(d[1]), "+f"(d[2]), "+f"(d[3]), "+f"(d[4]), "+f"(d[5]), "+f"(d[6]), "+f"(d[7]), "+f"(d[8]), "+f"(d[9]), "+f"(d[10]), "+f"(d[11]), "+f"(d[12]), "+f"(d[13]), "+f"(d[14]), "+f"(d[15]), "+f"(d[16]), "+f"(d[17]), "+f"(d[18]), "+f"(d[19]), "+f"(d[20]), "+f"(d[21]), "+f"(d[22]), "+f"(d[23]), "+f"(d[24]), "+f"(d[25]), "+f"(d[26]), "+f"(d[27]), "+f"(d[28]), "+f"(d[29]), "+f"(d[30]), "+f"(d[31]), "+f"(d[32]), "+f"(d[33]), "+f"(d[34]), "+f"(d[35]), "+f"(d[36]), "+f"(d[37]), "+f"(d[38]), "+f"(d[39]), "+f"(d[40]), "+f"(d[41]), "+f"(d[42]), "+f"(d[43]), "+f"(d[44]), "+f"(d[45]), "+f"(d[46]), "+f"(d[47]), "+f"(d[48]), "+f"(d[49]), "+f"(d[50]), "+f"(d[51]), "+f"(d[52]), "+f"(d[53]), "+f"(d[54]), "+f"(d[55]), "+f"(d[56]), "+f"(d[57]), "+f"(d[58]), "+f"(d[59]), "+f"(d[60]), "+f"(d[61]), "+f"(d[62]), "+f"(d[63])
    : "l"(descA), "l"(descB), "r"(scaleD));
}

__device__ __forceinline__ void wgmma_n192_ssz_ta0_tb1(float* d, uint64_t descA, uint64_t descB) {
  asm volatile("{\n.reg .pred p;\nsetp.ne.b32 p, 0, 0;\n"
    "wgmma.mma_async.sync.aligned.m64n192k16.f32.bf16.bf16 {%0, %1, %2, %3, %4, %5, %6, %7, %8, %9, %10, %11, %12, %13, %14, %15, %16, %17, %18, %19, %20, %21, %22, %23, %24, %25, %26, %27, %28, %29, %30, %31, %32, %33, %34, %35, %36, %37, %38, %39, %40, %41, %42, %43, %44, %45, %46, %47, %48, %49, %50, %51, %52, %53, %54, %55, %56, %57, %58, %59, %60, %61, %62, %63, %64, %65, %66, %67, %68, %69, %70, %71, %72, %73, %74, %75, %76, %77, %78, %79, %80, %81, %82, %83, %84, %85, %86, %87, %88, %89, %90, %91, %92, %93, %94, %95}, %96, %97, p, 1, 1, 0, 1;\n}\n"
    : "=f"(d[0]), "=f"(d[1]), "=f"(d[2]), "=f"(d[3]), "=f"(d[4]), "=f"(d[5]), "=f"(d[6]), "=f"(d[7]), "=f"(d[8]), "=f"(d[9]), "=f"(d[10]), "=f"(d[11]), "=f"(d[12]), "=f"(d[13]), "=f"(d[14]), "=f"(d[15]), "=f"(d[16]), "=f"(d[17]), "=f"(d[18]), "=f"(d[19]), "=f"(d[20]), "=f"(d[21]), "=f"(d[22]), "=f"(d[23]), "=f"(d[24]), "=f"(d[25]), "=f"(d[26]), "=f"(d[27]), "=f"(d[28]), "=f"(d[29]), "=f"(d[30]), "=f"(d[31]), "=f"(d[32]), "=f"(d[33]), "=f"(d[34]), "=f"(d[35]), "=f"(d[36]), "=f"(d[37]), "=f"(d[38]), "=f"(d[39]), "=f"(d[40]), "=f"(d[41]), "=f"(d[42]), "=f"(d[43]), "=f"(d[44]), "=f"(d[45]), "=f"(d[46]), "=f"(d[47]), "=f"(d[48]), "=f"(d[49]), "=f"(d[50]), "=f"(d[51]), "=f"(d[52]), "=f"(d[53]), "=f"(d[54]), "=f"(d[55]), "=f"(d[56]), "=f"(d[57]), "=f"(d[58]), "=f"(d[59]), "=f"(d[60]), "=f"(d[61]), "=f"(d[62]), "=f"(d[63]), "=f"(d[64]), "=f"(d[65]), "=f"(d[66]), "=f"(d[67]), "=f"(d[68]), "=f"(d[69]), "=f"(d[70]), "=f"(d[71]), "=f"(d[72]), "=f"(d[73]), "=f"(d[74]), "=f"(d[75]), "=f"(d[76]), "=f"(d[77]), "=f"(d[78]), "=f"(d[79]), "=f"(d[80]), "=f"(d[81]), "=f"(d[82]), "=f"(d[83]), "=f"(d[84]), "=f"(d[85]), "=f"(d[86]), "=f"(d[87]), "=f"(d[88]), "=f"(d[89]), "=f"(d[90]), "=f"(d[91]), "=f"(d[92]), "=f"(d[93]), "=f"(d[94]), "=f"(d[95])
    : "l"(descA), "l"(descB));
}

__device__ __forceinline__ void wgmma_n192_rs_tb1(float* d, uint32_t a0, uint32_t a1, uint64_t descB) {
  asm volatile("{\n.reg .pred p;\nsetp.eq.b32 p, 0, 0;\n"
    "wgmma.mma_async.sync.aligned.m64n192k16.f32.bf16.bf16 {%0, %1, %2, %3, %4, %5, %6, %7, %8, %9, %10, %11, %12, %13, %14, %15, %16, %17, %18, %19, %20, %21, %22, %23, %24, %25, %26, %27, %28, %29, %30, %31, %32, %33, %34, %35, %36, %37, %38, %39, %40, %41, %42, %43, %44, %45, %46, %47, %48, %49, %50, %51, %52, %53, %54, %55, %56, %57, %58, %59, %60, %61, %62, %63, %64, %65, %66, %67, %68, %69, %70, %71, %72, %73, %74, %75, %76, %77, %78, %79, %80, %81, %82, %83, %84, %85, %86, %87, %88, %89, %90, %91, %92, %93, %94, %95}, {%96, %97, %98, %98}, %99, p, 1, 1, 1;\n}\n"
    : "+f"(d[0]), "+f"(d[1]), "+f"(d[2]), "+f"(d[3]), "+f"(d[4]), "+f"(d[5]), "+f"(d[6]), "+f"(d[7]), "+f"(d[8]), "+f"(d[9]), "+f"(d[10]), "+f"(d[11]), "+f"(d[12]), "+f"(d[13]), "+f"(d[14]), "+f"(d[15]), "+f"(d[16]), "+f"(d[17]), "+f"(d[18]), "+f"(d[19]), "+f"(d[20]), "+f"(d[21]), "+f"(d[22]), "+f"(d[23]), "+f"(d[24]), "+f"(d[25]), "+f"(d[26]), "+f"(d[27]), "+f"(d[28]), "+f"(d[29]), "+f"(d[30]), "+f"(d[31]), "+f"(d[32]), "+f"(d[33]), "+f"(d[34]), "+f"(d[35]), "+f"(d[36]), "+f"(d[37]), "+f"(d[38]), "+f"(d[39]), "+f"(d[40]), "+f"(d[41]), "+f"(d[42]), "+f"(d[43]), "+f"(d[44]), "+f"(d[45]), "+f"(d[46]), "+f"(d[47]), "+f"(d[48]), "+f"(d[49]), "+f"(d[50]), "+f"(d[51]), "+f"(d[52]), "+f"(d[53]), "+f"(d[54]), "+f"(d[55]), "+f"(d[56]), "+f"(d[57]), "+f"(d[58]), "+f"(d[59]), "+f"(d[60]), "+f"(d[61]), "+f"(d[62]), "+f"(d[63]), "+f"(d[64]), "+f"(d[65]), "+f"(d[66]), "+f"(d[67]), "+f"(d[68]), "+f"(d[69]), "+f"(d[70]), "+f"(d[71]), "+f"(d[72]), "+f"(d[73]), "+f"(d[74]), "+f"(d[75]), "+f"(d[76]), "+f"(d[77]), "+f"(d[78]), "+f"(d[79]), "+f"(d[80]), "+f"(d[81]), "+f"(d[82]), "+f"(d[83]), "+f"(d[84]), "+f"(d[85]), "+f"(d[86]), "+f"(d[87]), "+f"(d[88]), "+f"(d[89]), "+f"(d[90]), "+f"(d[91]), "+f"(d[92]), "+f"(d[93]), "+f"(d[94]), "+f"(d[95])
    : "r"(a0), "r"(a1), "r"(0u), "l"(descB));
}

__device__ __forceinline__ void wgmma_n128_ssz_ta0_tb1(float* d, uint64_t descA, uint64_t descB) {
  asm volatile("{\n.reg .pred p;\nsetp.ne.b32 p, 0, 0;\n"
    "wgmma.mma_async.sync.aligned.m64n128k16.f32.bf16.bf16 {%0, %1, %2, %3, %4, %5, %6, %7, %8, %9, %10, %11, %12, %13, %14, %15, %16, %17, %18, %19, %20, %21, %22, %23, %24, %25, %26, %27, %28, %29, %30, %31, %32, %33, %34, %35, %36, %37, %38, %39, %40, %41, %42, %43, %44, %45, %46, %47, %48, %49, %50, %51, %52, %53, %54, %55, %56, %57, %58, %59, %60, %61, %62, %63}, %64, %65, p, 1, 1, 0, 1;\n}\n"
    : "=f"(d[0]), "=f"(d[1]), "=f"(d[2]), "=f"(d[3]), "=f"(d[4]), "=f"(d[5]), "=f"(d[6]), "=f"(d[7]), "=f"(d[8]), "=f"(d[9]), "=f"(d[10]), "=f"(d[11]), "=f"(d[12]), "=f"(d[13]), "=f"(d[14]), "=f"(d[15]), "=f"(d[16]), "=f"(d[17]), "=f"(d[18]), "=f"(d[19]), "=f"(d[20]), "=f"(d[21]), "=f"(d[22]), "=f"(d[23]), "=f"(d[24]), "=f"(d[25]), "=f"(d[26]), "=f"(d[27]), "=f"(d[28]), "=f"(d[29]), "=f"(d[30]), "=f"(d[31]), "=f"(d[32]), "=f"(d[33]), "=f"(d[34]), "=f"(d[35]), "=f"(d[36]), "=f"(d[37]), "=f"(d[38]), "=f"(d[39]), "=f"(d[40]), "=f"(d[41]), "=f"(d[42]), "=f"(d[43]), "=f"(d[44]), "=f"(d[45]), "=f"(d[46]), "=f"(d[47]), "=f"(d[48]), "=f"(d[49]), "=f"(d[50]), "=f"(d[51]), "=f"(d[52]), "=f"(d[53]), "=f"(d[54]), "=f"(d[55]), "=f"(d[56]), "=f"(d[57]), "=f"(d[58]), "=f"(d[59]), "=f"(d[60]), "=f"(d[61]), "=f"(d[62]), "=f"(d[63])
    : "l"(descA), "l"(descB));
}

__device__ __forceinline__ void wgmma_n64_ss_ta0_tb0(float* d, uint64_t descA, uint64_t descB, int scaleD) {
  asm volatile("{\n.reg .pred p;\nsetp.ne.b32 p, %34, 0;\n"
    "wgmma.mma_async.sync.aligned.m64n64k16.f32.bf16.bf16 {%0, %1, %2, %3, %4, %5, %6, %7, %8, %9, %10, %11, %12, %13, %14, %15, %16, %17, %18, %19, %20, %21, %22, %23, %24, %25, %26, %27, %28, %29, %30, %31}, %32, %33, p, 1, 1, 0, 0;\n}\n"
    : "+f"(d[0]), "+f"(d[1]), "+f"(d[2]), "+f"(d[3]), "+f"(d[4]), "+f"(d[5]), "+f"(d[6]), "+f"(d[7]), "+f"(d[8]), "+f"(d[9]), "+f"(d[10]), "+f"(d[11]), "+f"(d[12]), "+f"(d[13]), "+f"(d[14]), "+f"(d[15]), "+f"(d[16]), "+f"(d[17]), "+f"(d[18]), "+f"(d[19]), "+f"(d[20]), "+f"(d[21]), "+f"(d[22]), "+f"(d[23]), "+f"(d[24]), "+f"(d[25]), "+f"(d[26]), "+f"(d[27]), "+f"(d[28]), "+f"(d[29]), "+f"(d[30]), "+f"(d[31])
    : "l"(descA), "l"(descB), "r"(scaleD));
}

__device__ __forceinline__ void wgmma_n64_ssz_ta0_tb0(float* d, uint64_t descA, uint64_t descB) {
  asm volatile("{\n.reg .pred p;\nsetp.ne.b32 p, 0, 0;\n"
    "wgmma.mma_async.sync.aligned.m64n64k16.f32.bf16.bf16 {%0, %1, %2, %3, %4, %5, %6, %7, %8, %9, %10, %11, %12, %13, %14, %15, %16, %17, %18, %19, %20, %21, %22, %23, %24, %25, %26, %27, %28, %29, %30, %31}, %32, %33, p, 1, 1, 0, 0;\n}\n"
    : "=f"(d[0]), "=f"(d[1]), "=f"(d[2]), "=f"(d[3]), "=f"(d[4]), "=f"(d[5]), "=f"(d[6]), "=f"(d[7]), "=f"(d[8]), "=f"(d[9]), "=f"(d[10]), "=f"(d[11]), "=f"(d[12]), "=f"(d[13]), "=f"(d[14]), "=f"(d[15]), "=f"(d[16]), "=f"(d[17]), "=f"(d[18]), "=f"(d[19]), "=f"(d[20]), "=f"(d[21]), "=f"(d[22]), "=f"(d[23]), "=f"(d[24]), "=f"(d[25]), "=f"(d[26]), "=f"(d[27]), "=f"(d[28]), "=f"(d[29]), "=f"(d[30]), "=f"(d[31])
    : "l"(descA), "l"(descB));
}

__device__ __forceinline__ void wgmma_n80_ss_ta0_tb0(float* d, uint64_t descA, uint64_t descB, int scaleD) {
  asm volatile("{\n.reg .pred p;\nsetp.ne.b32 p, %42, 0;\n"
    "wgmma.mma_async.sync.aligned.m64n80k16.f32.bf16.bf16 {%0, %1, %2, %3, %4, %5, %6, %7, %8, %9, %10, %11, %12, %13, %14, %15, %16, %17, %18, %19, %20, %21, %22, %23, %24, %25, %26, %27, %28, %29, %30, %31, %32, %33, %34, %35, %36, %37, %38, %39}, %40, %41, p, 1, 1, 0, 0;\n}\n"
    : "+f"(d[0]), "+f"(d[1]), "+f"(d[2]), "+f"(d[3]), "+f"(d[4]), "+f"(d[5]), "+f"(d[6]), "+f"(d[7]), "+f"(d[8]), "+f"(d[9]), "+f"(d[10]), "+f"(d[11]), "+f"(d[12]), "+f"(d[13]), "+f"(d[14]), "+f"(d[15]), "+f"(d[16]), "+f"(d[17]), "+f"(d[18]), "+f"(d[19]), "+f"(d[20]), "+f"(d[21]), "+f"(d[22]), "+f"(d[23]), "+f"(d[24]), "+f"(d[25]), "+f"(d[26]), "+f"(d[27]), "+f"(d[28]), "+f"(d[29]), "+f"(d[30]), "+f"(d[31]), "+f"(d[32]), "+f"(d[33]), "+f"(d[34]), "+f"(d[35]), "+f"(d[36]), "+f"(d[37]), "+f"(d[38]), "+f"(d[39])
    : "l"(descA), "l"(descB), "r"(scaleD));
}

__device__ __forceinline__ void wgmma_n32_rs_tb1(float* d, const uint32_t* a, uint64_t descB, int scaleD) {
  asm volatile("{\n.reg .pred p;\nsetp.ne.b32 p, %21, 0;\n"
    "wgmma.mma_async.sync.aligned.m64n32k16.f32.bf16.bf16 {%0, %1, %2, %3, %4, %5, %6, %7, %8, %9, %10, %11, %12, %13, %14, %15}, {%16, %17, %18, %19}, %20, p, 1, 1, 1;\n}\n"
    : "+f"(d[0]), "+f"(d[1]), "+f"(d[2]), "+f"(d[3]), "+f"(d[4]), "+f"(d[5]), "+f"(d[6]), "+f"(d[7]), "+f"(d[8]), "+f"(d[9]), "+f"(d[10]), "+f"(d[11]), "+f"(d[12]), "+f"(d[13]), "+f"(d[14]), "+f"(d[15])
    : "r"(a[0]), "r"(a[1]), "r"(a[2]), "r"(a[3]), "l"(descB), "r"(scaleD));
}

__device__ __forceinline__ uint32_t pack_bf16x2(float lo, float hi) {
  uint32_t r;
  asm("cvt.rn.bf16x2.f32 %0, %1, %2;" : "=r"(r) : "f"(hi), "f"(lo));
  return r;
}
__device__ __forceinline__ float bf_lo(uint32_t p) { return __uint_as_float(p << 16); }
__device__ __forceinline__ float bf_hi(uint32_t p) { return __uint_as_float(p & 0xffff0000u); }
__device__ __forceinline__ float bf16_round(float v) { return __bfloat162float(__float2bfloat16_rn(v)); }
__device__ __forceinline__ float ex2_approx(float x) {
  float r;
  asm("ex2.approx.ftz.f32 %0, %1;" : "=f"(r) : "f"(x));
  return r;
}
__device__ __forceinline__ float rcp_fast(float x) {
  float r;
  asm("rcp.approx.ftz.f32 %0, %1;" : "=f"(r) : "f"(x));
  return r;
}
__device__ __forceinline__ void ldmatrix_x4(uint32_t (&r)[4], uint32_t addr) {
  asm volatile("ldmatrix.sync.aligned.m8n8.x4.shared.b16 {%0,%1,%2,%3}, [%4];"
               : "=r"(r[0]), "=r"(r[1]), "=r"(r[2]), "=r"(r[3])
               : "r"(sw(addr))
               : "memory");
}
__device__ __forceinline__ void stmatrix_x4(uint32_t addr, uint32_t r0, uint32_t r1, uint32_t r2, uint32_t r3) {
  asm volatile("stmatrix.sync.aligned.m8n8.x4.shared.b16 [%0], {%1,%2,%3,%4};" ::"r"(sw(addr)), "r"(r0), "r"(r1), "r"(r2),
               "r"(r3));
}
__device__ __forceinline__ uint32_t add_bf16x2(uint32_t a, uint32_t b) {
  uint32_t r;
  asm("add.rn.bf16x2 %0, %1, %2;" : "=r"(r) : "r"(a), "r"(b));
  return r;
}
__device__ __forceinline__ uint4 lds128(uint32_t addr) {
  uint4 v;
  asm volatile("ld.shared.v4.b32 {%0,%1,%2,%3}, [%4];" : "=r"(v.x), "=r"(v.y), "=r"(v.z), "=r"(v.w) : "r"(sw(addr)) : "memory");
  return v;
}
__device__ __forceinline__ uint32_t lds32(uint32_t addr) {
  uint32_t v;
  asm volatile("ld.shared.b32 %0, [%1];" : "=r"(v) : "r"(sw(addr)) : "memory");
  return v;
}
__device__ __forceinline__ void sts32(uint32_t addr, uint32_t v) {
  asm volatile("st.shared.b32 [%0], %1;" ::"r"(sw(addr)), "r"(v) : "memory");
}

__device__ __forceinline__ unsigned ld_acquire_u32(const unsigned* p) {
  unsigned v;
  asm volatile("ld.acquire.gpu.global.u32 %0, [%1];" : "=r"(v) : "l"(p) : "memory");
  return v;
}
__device__ __forceinline__ unsigned atom_add(unsigned* p, unsigned v, bool on) {
  unsigned r = 0;
  asm volatile("{\n.reg .pred p;\nsetp.ne.u32 p, %3, 0;\n@p atom.relaxed.gpu.global.add.u32 %0, [%1], %2;\n}\n"
               : "+r"(r) : "l"(p), "r"(v), "r"((uint32_t)on) : "memory");
  return r;
}
__device__ __forceinline__ void announce(unsigned* p) {
  asm volatile("red.release.gpu.global.add.u32 [%0], 1;" ::"l"(p) : "memory");
}
__device__ __forceinline__ void poison(uint8_t* p, int n, uint32_t gap) {
#pragma unroll 1
  for (int i = 0; i < n; i++, p += 2048) {
    asm volatile("st.global.v4.b32 [%0], {%1,%1,%1,%1};" ::"l"(p), "r"(0xffffffffu) : "memory");
    __nanosleep(gap);
  }
}
__device__ __forceinline__ void wait_ge2(const unsigned* p, unsigned t0, unsigned t1) {
#pragma unroll 1
  for (uint32_t it = 0; it < (1u << 17); ++it) {
    unsigned long long v;
    asm volatile("ld.acquire.gpu.global.u64 %0, [%1];" : "=l"(v) : "l"(p) : "memory");
    if ((int)((unsigned)v - t0) >= 0 && (int)((unsigned)(v >> 32) - t1) >= 0) return;
  }
}

#define RELNS 100
#define PCM 0x22
#define HBD 700
#define POI1 100
#define WU 3
constexpr int WUNR = WU;
#define PCS 4096
#define PCN 30
template <bool SLOW>
__device__ __forceinline__ void wait_mask(const unsigned* f, int cnt, unsigned target, uint32_t need, uint32_t& seen, int lane) {
  if ((seen & need) == need) return;
  const unsigned* fp = f + (lane & (cnt - 1));
#pragma unroll 1
  for (uint32_t it = 0; it < (1u << 17); ++it) {
    seen = __ballot_sync(0xffffffffu, (int)(ld_acquire_u32(fp) - target) >= 0);
    if ((seen & need) == need) break;
    if (SLOW) __nanosleep(400);
  }
  fence_proxy_async_all();
}
__device__ __forceinline__ void wait_lanes(const unsigned* fp, unsigned target, uint32_t need, uint32_t& seen) {
  if ((seen & need) == need) return;
#pragma unroll 1
  for (uint32_t it = 0; it < (1u << 17); ++it) {
    seen |= __ballot_sync(0xffffffffu, (int)(ld_acquire_u32(fp) - target) >= 0);
    if ((seen & need) == need) break;
  }
  fence_proxy_async_all();
}
__device__ __forceinline__ float4 ld_rec(const float4* p) {
  float4 v;
  asm volatile("ld.relaxed.gpu.global.v4.f32 {%0,%1,%2,%3}, [%4];" : "=f"(v.x), "=f"(v.y), "=f"(v.z), "=f"(v.w) : "l"(p) : "memory");
  return v;
}
__device__ __forceinline__ void st_rec(float4* p, float a, float b, float c, unsigned tag) {
  asm volatile("st.relaxed.gpu.global.v4.f32 [%0], {%1,%2,%3,%4};" ::"l"(p), "f"(a), "f"(b), "f"(c), "f"(__uint_as_float(tag)) : "memory");
}
template <int N>
__device__ __forceinline__ float4 sum_recs(const float4* p, int stride, unsigned tag) {
  float4 s;
#pragma unroll 1
  for (uint32_t it = 0; it < (1u << 17); ++it) {
    float4 v[N];
#pragma unroll
    for (int t = 0; t < N; t++) v[t] = ld_rec(p + t * stride);
    bool ok = true;
    s = make_float4(0.f, 0.f, 0.f, 0.f);
#pragma unroll
    for (int t = 0; t < N; t++) {
      ok &= __float_as_uint(v[t].w) == tag;
      s.x += v[t].x;
      s.y += v[t].y;
      s.z += v[t].z;
    }
    if (ok) break;
    __nanosleep(200);
  }
  return s;
}

__device__ __forceinline__ int fresh_tid() {
  int t;
  asm volatile("mov.u32 %0, %%tid.x;" : "=r"(t));
  return t;
}
#define PHASE_IDS                                  \
  const int tid_ = fresh_tid();                    \
  const int lane = tid_ & 31, wwarp = __shfl_sync(0xffffffffu, (tid_ >> 5) & 3, 0), tid = tid_ & 127; \
  const int g = lane >> 2, c = lane & 3;           \
  (void)tid; (void)g; (void)c; (void)wwarp;

#define STAMPW(cond, i) do { } while (0)
#define STAMP(cond, i) do { } while (0)
#define KSPN true
#define KSAON false
#define STA(i) do { } while (0)
#define GTL(i) do { } while (0)
#define GTLX(c, i) do { } while (0)
#define TGET(v) do { } while (0)
#define TPUT(c, i, v) do { } while (0)

constexpr float SM_C = 0.17677669529663687f * 1.4426950408889634f;

constexpr uint32_t OA_TILE = SBASE + OFF_SLOT + 16384;

__device__ __forceinline__ void sched_fence(uint32_t never) {
  asm volatile("{\n.reg .pred p;\nsetp.ne.u32 p, %0, 0;\n@p exit;\n}\n" ::"r"(never) : "memory");
}

template <int K0, int K1>
__device__ __forceinline__ void attn_exp(float (&s)[32]) {
#pragma unroll
  for (int k = K0; k < K1; k++) s[k] = ex2_approx(s[k]);
}
#define ASPL 16
#define ASPD 6
#define ASPE 6
#define ASPF 6
template <int MODE, bool NEXT>
__device__ __forceinline__ void attn_unit(float (&s)[32], float (&sn)[32], float (&o)[16], float (&l)[2], bool valid,
                                          uint32_t vdesc, uint32_t qdesc, uint32_t kdesc, uint32_t tri, int w,
                                          uint32_t hbar, uint32_t hpar, uint32_t rel, uint32_t zero, bool stampon = false) {
  float x[9][2];
  constexpr int ASPM = MODE == 1 ? ASPD : (NEXT ? ASPE : ASPF);
  if (MODE == 0) {
    attn_exp<0, ASPL>(s);
  } else {
#pragma unroll
    for (int e = 0; e < 2; e++) {
#pragma unroll
      for (int j = 0; j < 4; j++) x[j][e] = MODE == 1 ? s[4 * j + 2 + e] : s[16 + 4 * j + e];
      x[4][e] = MODE == 1 ? s[e] : s[30 + e];
      x[5][e] = MODE == 1 ? s[18 + e] : s[12 + e];
#pragma unroll
      for (int u = 1; u < 4; u++)
        x[5 + u][e] = MODE == 1 ? (w >= u ? s[4 * u + e] : s[4 * (8 - u) + 2 + e]) : (w >= u ? s[4 * (7 - u) + 2 + e] : s[4 * (u - 1) + e]);
    }
#pragma unroll
    for (int k = 0; k < 2 * ASPM; k++) x[k >> 1][k & 1] = ex2_approx(x[k >> 1][k & 1]);
  }
  sched_fence(zero);
  if (hbar) mbar_wait(hbar, hpar);
  wgmma_wait<0>();
  if (rel) mbar_arrive(rel);
  if (NEXT) {
    wgmma_fence();
    wgmma_n64_ssz_ta0_tb0(sn, desc_lo(qdesc), desc_lo(kdesc));
    wgmma_n64_ss_ta0_tb0(sn, desc_lo(qdesc + 2), desc_lo(kdesc + 2), 1);
    wgmma_commit();
    sched_fence(zero);
  }
  uint32_t p[16];
  if (MODE == 0) {
    attn_exp<ASPL, 32>(s);
#pragma unroll
    for (int k = 0; k < 16; k++) p[k] = pack_bf16x2(s[2 * k], s[2 * k + 1]);
  } else {
#pragma unroll
    for (int k = 2 * ASPM; k < 18; k++) x[k >> 1][k & 1] = ex2_approx(x[k >> 1][k & 1]);
    const uint32_t tm = MODE == 1 ? tri : ~tri;
#pragma unroll
    for (int j = 0; j < 4; j++) {
      p[MODE == 1 ? 2 * j + 1 : 8 + 2 * j] = pack_bf16x2(x[j][0], x[j][1]);
      p[MODE == 1 ? 8 + 2 * j : 2 * j + 1] = 0u;
    }
    p[MODE == 1 ? 0 : 15] = pack_bf16x2(x[4][0], x[4][1]) & (w == 0 ? tm : 0xffffffffu);
    p[MODE == 1 ? 9 : 6] = pack_bf16x2(x[5][0], x[5][1]) & (w == 3 ? tm : 0xffffffffu);
#pragma unroll
    for (int u = 1; u < 4; u++) {
      const uint32_t q = pack_bf16x2(x[5 + u][0], x[5 + u][1]);
      p[MODE == 1 ? 2 * u : 2 * (7 - u) + 1] = q & (w > u ? 0xffffffffu : (w == u ? tm : 0u));
      p[MODE == 1 ? 2 * (8 - u) + 1 : 2 * (u - 1)] = q & (w < u - 1 ? 0xffffffffu : (w == u - 1 ? tm : 0u));
    }
  }
  wgmma_fence();
#pragma unroll
  for (int k = 0; k < 4; k++) wgmma_n32_rs_tb1(o, p + 4 * k, desc_lo(vdesc + k * 128), 1);
  wgmma_commit();
#pragma unroll
  for (int r = 0; r < 2; r++) {
    float t = 0.f;
#pragma unroll
    for (int hf = 0; hf < 2; hf++) {
      if (MODE != 0 && r == MODE - 1 && hf == 2 - MODE) continue;
      const uint32_t* q = p + 8 * hf + r;
      const uint32_t v = add_bf16x2(add_bf16x2(q[0], q[2]), add_bf16x2(q[4], q[6]));
      t = (MODE != 0 && r == MODE - 1) || hf == 0 ? bf_lo(v) + bf_hi(v) : t + (bf_lo(v) + bf_hi(v));
    }
    if (valid) l[r] += t;
  }
  if (NEXT) {
    wgmma_wait<1>();
    reg_fence<32>(sn);
  }
}

__device__ __forceinline__ void attn_a_slow(const uint8_t* __restrict__ kvimg, int L, int gb, int hp,
                                         int hh, int wwarp, int lane, int t0, int t1) {
  constexpr uint32_t sq = SBASE + OFF_SLOT + 3 * 16384;
  const unsigned ep = (*(volatile unsigned*)(g_flags + F_DONE)) / NCTA;
  wait_ge2(g_flags + F_KV + (gb * 16 + hp) * KSTR, 2u * ep + (L >> 1) + 1u, 2u * ep + (L >> 1) + 1u);
#pragma unroll 1
  for (int t = t0; t < t1; t++) {
    const int row = (t >> 4) * 64 + ((t & 8) ? 7 - wwarp : wwarp) * 8 + (t & 7);
    const int qpos = gb * 128 + row;
    const uint32_t qaddr = sq + ((t >> 4) * 64 + wwarp * 16 + (t & 15)) * 128;
    float mx = -INFINITY, sum = 0.f, acc = 0.f;
#pragma unroll 1
    for (int pass = 0; pass < 2; pass++) {
#pragma unroll 1
      for (int j = 0; j < 8; j++) {
        const int kp = qpos - (lane + 32 * j);
        const uint8_t* kr = kvimg + ((size_t)((kp >> 7) * 16 + hp) * 2 + ((kp >> 6) & 1)) * 16384 + (kp & 63) * 128;
        float d = -INFINITY;
        if (kp >= 0) {
          d = 0.f;
#pragma unroll 1
          for (int q = 0; q < 4; q++) {
            const uint4 kv = __ldcg(reinterpret_cast<const uint4*>(kr + (((hh * 4 + q) ^ (kp & 7)) << 4)));
            const uint4 qv = lds128(qaddr + (((hh * 4 + q) ^ (row & 7)) << 4));
            const uint32_t kw[4] = {kv.x, kv.y, kv.z, kv.w}, qw[4] = {qv.x, qv.y, qv.z, qv.w};
#pragma unroll
            for (int e = 0; e < 4; e++) d = fmaf(bf_lo(kw[e]), bf_lo(qw[e]), fmaf(bf_hi(kw[e]), bf_hi(qw[e]), d));
          }
        }
        if (pass == 0) {
          mx = fmaxf(mx, d);
        } else {
          const float ev = ex2_approx(d - mx);
          sum += ev;
          const float pv = bf16_round(ev);
#pragma unroll 1
          for (int kk = 0; kk < 32; kk++) {
            const float pk = __shfl_sync(0xffffffffu, pv, kk);
            const int k2 = qpos - (kk + 32 * j);
            if (k2 >= 0) {
              const uint8_t* vr = kvimg + ((size_t)((k2 >> 7) * 16 + hp) * 2 + ((k2 >> 6) & 1)) * 16384 + 8192 + (k2 & 63) * 128;
              const unsigned short vv =
                  __ldcg(reinterpret_cast<const unsigned short*>(vr + (((hh * 4 + (lane >> 3)) ^ (k2 & 7)) << 4) + (lane & 7) * 2));
              acc = fmaf(pk, __uint_as_float((uint32_t)vv << 16), acc);
            }
          }
        }
      }
      if (pass == 0) {
#pragma unroll
        for (int o = 16; o > 0; o >>= 1) mx = fmaxf(mx, __shfl_xor_sync(0xffffffffu, mx, o));
      }
    }
#pragma unroll
    for (int o = 16; o > 0; o >>= 1) sum += __shfl_xor_sync(0xffffffffu, sum, o);
    acc *= rcp_fast(sum);
    const float hi = __shfl_down_sync(0xffffffffu, acc, 1);
    __syncwarp();
    if ((lane & 1) == 0)
      sts32(OA_TILE + row * 128 + (((hh * 4 + (lane >> 3)) ^ (row & 7)) << 4) + (lane & 7) * 2, pack_bf16x2(acc, hi));
    __syncwarp();
  }
}

__device__ __forceinline__ void store_o(const float (&o)[16], const float (&inv)[2], uint32_t rowaddr, int hh, int lane) {
  const int mat = lane >> 3, r7 = lane & 7;
#pragma unroll
  for (int jp = 0; jp < 2; jp++)
    stmatrix_x4(rowaddr + (((hh * 4 + 2 * jp + (mat >> 1)) ^ r7) << 4),
                pack_bf16x2(o[8 * jp] * inv[0], o[8 * jp + 1] * inv[0]),
                pack_bf16x2(o[8 * jp + 2] * inv[1], o[8 * jp + 3] * inv[1]),
                pack_bf16x2(o[8 * jp + 4] * inv[0], o[8 * jp + 5] * inv[0]),
                pack_bf16x2(o[8 * jp + 6] * inv[1], o[8 * jp + 7] * inv[1]));
}

__device__ __forceinline__ void attention_a(int HH, int L, int gb, int hp, uint32_t par0, uint32_t parA, int wwarp, int lane,
                                            uint32_t zero) {
  constexpr uint32_t bars = SBASE + OFF_BAR;
  const uint32_t dslot = ((SBASE + OFF_SLOT) >> 4) + 0x10000u + HH * 4;
  const uint32_t dq = dslot + 3 * 1024;
  float sa[32], sb[32], o[2][16], l[2][2];
  auto dch = [&](int n) { return dslot + 1024u * (n % 3 == 0 ? 1 : (n % 3 == 1 ? 0 : 2)); };
  wgmma_fence();
  wgmma_n64_ssz_ta0_tb0(sa, desc_lo(dq + 512), desc_lo(dch(0)));
  wgmma_n64_ss_ta0_tb0(sa, desc_lo(dq + 512 + 2), desc_lo(dch(0) + 2), 1);
  wgmma_commit();
#pragma unroll
  for (int h = 0; h < 2; h++) {
#pragma unroll
    for (int i = 0; i < 16; i++) o[h][i] = 0.f;
    l[h][0] = l[h][1] = 0.f;
  }
  const int dg = (lane >> 2) - 2 * (lane & 3);
  const uint32_t tri = (dg >= 0 ? 0xffffu : 0u) | (dg >= 1 ? 0xffff0000u : 0u);
  const int nmax = 2 * gb + 1;
  wgmma_wait<0>();
  reg_fence<32>(sa);
#define STON false
#define ATT_STEP(i, MODE)                                                                                            \
  attn_unit<MODE, true>(sa, sb, o[1], l[1], i <= nmax, dch(i) + 512, dq, dch(i + 1), tri, wwarp,                     \
                        i >= 1 ? bars + 8u * (B_HALO + i - 1) : 0u, i == 1 ? par0 : parA, 0u, zero, STON); \
  attn_unit<MODE, (i < 4)>(sb, sa, o[0], l[0], i + 1 <= nmax, dch(i + 1) + 512, dq + 512, dch(i + 1), tri, wwarp, 0u, \
                           0u, i < 3 && lane == 0 ? bars + 8u * (B_REL + i) : 0u, zero);
  ATT_STEP(0, 1)
  ATT_STEP(1, 0)
  ATT_STEP(2, 0)
  ATT_STEP(3, 0)
  ATT_STEP(4, 2)
#undef ATT_STEP
  const uint32_t ra = OA_TILE + (((lane & 8) ? 7 - wwarp : wwarp) * 8 + (lane & 7)) * 128;
  bool redo[2];
#pragma unroll
  for (int h = 1; h >= 0; h--) {
    float inv[2];
    bool bad = false;
#pragma unroll
    for (int r = 0; r < 2; r++) {
      float v = l[h][r];
      v += __shfl_xor_sync(0xffffffffu, v, 1);
      v += __shfl_xor_sync(0xffffffffu, v, 2);
      bad |= !(v <= 1.152921504606846976e18f && v >= 8.673617379884035e-19f);
      inv[r] = rcp_fast(v);
    }
    if (h == 0) wgmma_wait<0>();
    reg_fence<16>(o[h]);
    store_o(o[h], inv, ra + h * 8192, HH, lane);
    redo[h] = __any_sync(0xffffffffu, bad);
    if (h == 1 && !redo[1]) {
      fence_proxy_async_smem();
      named_bar_arrive(9, 288);
    }
  }
  if (HH == 0) GTL(45);
  if (redo[0] || redo[1]) {
    attn_a_slow(g_kvA[L >> 1][0][0][0], L, gb, hp, HH, wwarp, lane, redo[0] ? 0 : 16, redo[1] ? 32 : 16);
    fence_proxy_async_smem();
    if (redo[1]) named_bar_arrive(9, 288);
  }
}

constexpr uint32_t KB_ROW0 = SBASE + OFF_SLOT + 2048, VB_ROW0 = SBASE + OFF_SLOT + 24576 + 2048;

__device__ __forceinline__ void attnB_soft(const float (&s)[40], int wwarp, int D, bool edge, bool odd,
                                           uint32_t (&p)[5][4], float (&sum)[2]) {
  float z[2][3];
#define GATHER_(W)                                                                                  \
  _Pragma("unroll") for (int r = 0; r < 2; r++) _Pragma("unroll") for (int t = 0; t < 3; t++)       \
      z[r][t] = odd ? s[4 * (2 * W + r + t) + 2 * r + 1] : s[4 * (2 * W + r + t) + 2 * r];
  if (wwarp < 2) {
    if (wwarp == 0) { GATHER_(0) } else { GATHER_(1) }
  } else {
    if (wwarp == 2) { GATHER_(2) } else { GATHER_(3) }
  }
#undef GATHER_
  float y[2];
  y[0] = D >= 2 ? z[0][0] : z[0][2];
  y[1] = D >= 2 ? z[1][0] : z[1][2];
  if (edge) {
    z[0][1] = -INFINITY;
    if (D >= 2) y[0] = y[1] = -INFINITY;
  }
  float m0 = fmaxf(z[0][1], y[0]), m1 = fmaxf(z[1][1], y[1]);
  m0 = fmaxf(m0, __shfl_xor_sync(0xffffffffu, m0, 1));
  m1 = fmaxf(m1, __shfl_xor_sync(0xffffffffu, m1, 1));
  m0 = fmaxf(m0, __shfl_xor_sync(0xffffffffu, m0, 2));
  m1 = fmaxf(m1, __shfl_xor_sync(0xffffffffu, m1, 2));
  const float e00 = ex2_approx(z[0][1] - m0), e01 = ex2_approx(y[0] - m0);
  const float e10 = ex2_approx(z[1][1] - m1), e11 = ex2_approx(y[1] - m1);
  sum[0] = e00 + e01;
  sum[1] = e10 + e11;
  const int sh = odd ? 16 : 0;
  const uint32_t a0 = pack_bf16x2(e00, 0.f) << sh, a1 = pack_bf16x2(e10, 0.f) << sh;
  const uint32_t b0 = pack_bf16x2(e01, 0.f) << sh, b1 = pack_bf16x2(e11, 0.f) << sh;
  const int kb = wwarp + (D >= 2 ? 0 : 1);
#pragma unroll
  for (int k = 0; k < 5; k++) {
    p[k][0] = k == kb ? b0 : 0u;
    p[k][1] = k == wwarp + 1 ? a1 : 0u;
    p[k][2] = k == wwarp ? a0 : 0u;
    p[k][3] = k == kb ? b1 : 0u;
#pragma unroll
    for (int q = 0; q < 4; q++) asm volatile("" : "+r"(p[k][q]));
  }
}

__device__ __forceinline__ void attnB_s(float (&s)[40], int HH, int h) {
  constexpr uint32_t sq = SBASE + OFF_SLOT + 3 * 16384;
#pragma unroll
  for (int ks = 0; ks < 2; ks++)
    wgmma_n80_ss_ta0_tb0(s, make_desc(sq + h * 8192 + HH * 64 + ks * 32, 16),
                         make_desc(KB_ROW0 + h * 8192 - 2048 + HH * 64 + ks * 32, 16), ks);
}
__device__ __forceinline__ void attnB_pv(float (&o)[16], const uint32_t (&p)[5][4], int HH, int h) {
#pragma unroll
  for (int k = 0; k < 5; k++)
    wgmma_n32_rs_tb1(o, p[k], make_desc(VB_ROW0 + h * 8192 - 2048 + k * 2048 + HH * 64, 16), k);
}

__device__ __forceinline__ void attention_b(int HH, int gb, uint32_t par0, int wwarp, int lane, bool ston) {
  constexpr uint32_t bars = SBASE + OFF_BAR, sq = SBASE + OFF_SLOT + 3 * 16384;
  float s[40];
  reg_define<40>(s);
  wgmma_fence();
  attnB_s(s, HH, 1);
  wgmma_commit();
  const int g = lane >> 2;
  const bool odd = g & 1;
  const int D = 2 * (lane & 3) + (g & 1) - g;
  const uint32_t ra = sq + (wwarp * 16 + ((lane >> 3) & 1) * 8 + (lane & 7)) * 128;
  wgmma_wait<0>();
  reg_fence<40>(s);
  STAMP(ston, 21);
#pragma unroll 1
  for (int h = 1; h >= 0; h--) {
    float o[16], inv[2];
    uint32_t p[5][4];
    reg_define<16>(o);
    attnB_soft(s, wwarp, D, h == 0 && gb == 0 && wwarp == 0, odd, p, inv);
    STAMP(ston, 25 - 3 * h);
    wgmma_fence();
    attnB_pv(o, p, HH, h);
    wgmma_commit();
#pragma unroll
    for (int r = 0; r < 2; r++) {
      inv[r] += __shfl_xor_sync(0xffffffffu, inv[r], 1);
      inv[r] += __shfl_xor_sync(0xffffffffu, inv[r], 2);
      inv[r] = rcp_fast(inv[r]);
    }
    if (h == 1) {
      mbar_wait(bars + 8u * B_HALO, par0);
      STAMP(ston, 23);
      wgmma_fence();
      attnB_s(s, HH, 0);
      wgmma_commit();
      wgmma_wait<1>();
    } else {
      wgmma_wait<0>();
    }
    reg_fence<16>(o);
    store_o(o, inv, ra + h * 8192, HH, lane);
    if (h == 1) {
      fence_proxy_async_smem();
      named_bar_arrive(9, 288);
    }
    wgmma_wait<0>();
    reg_fence<40>(s);
    STAMP(ston, 26 - 2 * h);
  }
}

#define TRICKLE 300
#define TRSP 10
#define TRICK2 150
#define PDL 600
#define CSN 1000
#define CSI 1
#define PCA 1
#define PCB 3
#define PXB 4
#define EPW1 4
#define EPW0 12
#define PRENS 800
#define LOCE 1
#define QTURN 2
constexpr int NPT = 240 + 8;
struct Params {
  CUtensorMap xq[2], xr[2], xw[2], o, wqkv[2], wo[2];
  const __nv_bfloat16* in_x;
  const __nv_bfloat16* wqkv_p1;
  const __nv_bfloat16* wo_p[2];
  uint32_t zero;
  uint2 wtab[4][17];
  uint2 ptab[NPT + 1];
};
static_assert(sizeof(Params) <= 4096, "");

__device__ __forceinline__ void colsum_part(const CUtensorMap* wmap, int ty, int qr, int hp) {
  constexpr uint32_t bars = SBASE + OFF_BAR, slots = SBASE + OFF_SLOT;
  PHASE_IDS
  const unsigned ep1 = (*(volatile unsigned*)(g_flags + F_DONE)) / NCTA + 1u;
  if (wwarp == 0 && elect_one()) {
    mbar_expect_tx(bars + 8u * B_CS, 6 * UNIT);
#pragma unroll 1
    for (int j = 0; j < 2; j++) {
      if (ty == 0) mbar_pace(bars + 8u * (B_EMPTY + PCA + PCB * j), 0);
      else __nanosleep(CSN);
      tma_load_3d(slots + j * 3 * UNIT, wmap, bars + 8u * B_CS, hp * 64, qr * 128 + j * 64, 0);
    }
  }
  __syncwarp();
  if (ty) {
#pragma unroll 1
    for (int j = 0; j < 4; j++) poison(g_kvB[j >> 1][(j & 1) * 8 + qr][hp] + tid * 16, 2, POI1);
  }
  mbar_wait(bars + 8u * B_CS, ty);
  STAMP(KSQ == 0 && ty == 0, 49);
  const uint32_t src = slots + (tid >> 3) * 128 + (((tid & 7) ^ ((tid >> 3) & 7)) << 4);
#pragma unroll 1
  for (int p = 0; p < 3; p++) {
    float s[8];
#pragma unroll
    for (int e = 0; e < 8; e++) s[e] = 0.f;
#pragma unroll
    for (int j = 0; j < 8; j++) {
      const uint4 v = lds128(src + p * UNIT + (j >> 2) * 3 * UNIT + (j & 3) * 2048);
      const uint32_t x[4] = {v.x, v.y, v.z, v.w};
#pragma unroll
      for (int e = 0; e < 4; e++) {
        s[2 * e] += bf_lo(x[e]);
        s[2 * e + 1] += bf_hi(x[e]);
      }
    }
#pragma unroll
    for (int st = 0; st < 2; st++) {
      const bool up = (lane >> (st + 3)) & 1;
#pragma unroll
      for (int e = 0; e < (4 >> st); e++) {
        const float keep = up ? s[e + (4 >> st)] : s[e], give = up ? s[e] : s[e + (4 >> st)];
        s[e] = keep + __shfl_xor_sync(0xffffffffu, give, 8 << st);
      }
    }
    const uint32_t dst = slots + 6 * UNIT + ((wwarp * 3 + p) * 64 + (lane & 7) * 8 + ((lane >> 3) & 1) * 4 + (lane >> 4) * 2) * 4;
    sts32(dst, __float_as_uint(s[0]));
    sts32(dst + 4, __float_as_uint(s[1]));
  }
  named_bar_sync(6, 128);
  float r[3] = {0.f, 0.f, 0.f};
#pragma unroll
  for (int e = 0; e < 12; e++) r[e % 3] += __uint_as_float(lds32(slots + 6 * UNIT + (e * 64 + (tid & 63)) * 4));
  __syncwarp();
  warp_arrive(bars + 8u * (ty ? B_CSD : B_AFREE), ty || wwarp < 2);
  if (tid < 64) {
    if (ty) {
      asm volatile("fence.release.gpu;" ::: "memory");
      fence_proxy_async_all();
    }
    st_rec(&g_cs[ty][hp][qr][tid], r[0], r[1], r[2], ep1);
    STAMP(KSQ == 0 && ty == 0, 50);
  }
}

__device__ __forceinline__ void cs_put(int blk, int ty, int col, float v) {
  const uint32_t hi = pack_bf16x2(v, 0.f), lo = pack_bf16x2(v - bf_lo(hi), 0.f);
  const uint32_t a = SBASE + OFF_CS + blk * 512 + ty * 256 + col * 2;
  asm volatile("st.shared.b16 [%0], %1;" ::"r"(sw(a ^ (((a >> 7) & 7) << 4))), "h"((unsigned short)hi) : "memory");
  asm volatile("st.shared.b16 [%0], %1;" ::"r"(sw((a + 128) ^ ((((a >> 7) + 1) & 7) << 4))), "h"((unsigned short)lo) : "memory");
}

__device__ __forceinline__ uint32_t ln_params(float s1, float s2) {
  const float mean = s1 * (1.0f / DM);
  const float var = fmaxf(fmaf(-mean, mean, s2 * (1.0f / DM)), 0.f);
  float sd;
  asm("sqrt.approx.f32 %0, %1;" : "=f"(sd) : "f"(bf16_round(bf16_round(var) + 1e-5f)));
  return pack_bf16x2(mean, sd);
}

#define SPLITS 0x085866688ull
__host__ __device__ __forceinline__ int q_split(int inst) { return (int)((SPLITS >> (4 * inst)) & 15ull); }
__device__ __forceinline__ int q_first(int inst) { return inst == 0 ? 0 : 32 * inst - 16; }
__device__ __forceinline__ int w_first(int inst) { return 32 * inst + 16 + 2 * q_split(inst + 1); }
#define PREMASK 0x2Cu
#define WBUF 0x0400103000201000ull
static_assert((PREMASK & 0xC0u) == 0, "");
__host__ __device__ __forceinline__ bool w_pre(int inst) { return (PREMASK >> inst) & 1u; }
struct WPlan {
  int v[6][21];
  int own[28], len;
};
__host__ __device__ constexpr WPlan w_plan(int mode) {
  WPlan p{};
  for (int u = 0; u < 28; u++) p.own[u] = u < 20 ? u / 5 - 4 : -16;
  if (mode == 2) {
    const WPlan q = w_plan(0);
    for (int u = 0; u < 20; u++) p.own[u] = q.own[(u + q.len) % 20] - 16;
  }
  int pos = 0, mx = -16;
  for (int kt = 0; kt < 21; kt++) {
    const int code = mode == 1 && kt < 16 ? (int)(WBUF >> (4 * kt)) & 15 : 0, st = kt > 16 ? kt - 1 : kt;
    const int na = kt == 16 ? 0 : (kt < 16 ? 1 : 2), nb = kt < 17 ? 2 : 3;
    const bool hole = code == 0 || (code & 8), swap = kt < 16 && hole && pos % 10 == 8;
    const int ua = (pos + (swap ? 2 : 0)) % 20, ub = code ? NUNITS - 2 + 2 * (code & 7) : (pos + (swap ? 0 : na)) % 20;
    int ra = st - 8, rb = kt == 16 ? -16 : st - 8;
    for (int i = 0; i < na; i++) ra = p.own[ua + i] > ra ? p.own[ua + i] : ra;
    for (int i = 0; i < nb; i++) rb = p.own[ub + i] > rb ? p.own[ub + i] : rb;
    p.v[0][kt] = ua;
    p.v[1][kt] = ub;
    p.v[2][kt] = st - ra;
    p.v[3][kt] = st - rb;
    p.v[4][kt] = rb > mx;
    p.v[5][kt] = p.own[ub] == -16;
    mx = rb > mx ? rb : mx;
    if (kt < 17) {
      for (int i = 0; i < na; i++) p.own[ua + i] = kt;
      for (int i = 0; i < nb; i++) p.own[ub + i] = kt < 16 ? kt : 15;
    }
    pos += na + (hole ? nb : 0);
    if (kt == 16) p.len = pos;
  }
  return p;
}
__host__ __device__ constexpr uint64_t w_tab(int f, int mode, int k0, int dk, int n, int bits) {
  const WPlan p = w_plan(mode);
  uint64_t r = 0;
  for (int j = 0; j < n; j++) r |= (uint64_t)p.v[f][k0 + j * dk] << (bits * j);
  return r;
}
__host__ __device__ constexpr uint32_t q_backs(bool act, int rank, bool pre) {
  return act ? 0x44444400u | (uint32_t)w_tab(2, pre, 17 + rank, 2, 2, 4) : 0x44440000u | (uint32_t)w_tab(3, pre, 17, 1, 4, 4);
}
__host__ __device__ constexpr uint32_t w_early() {
  const WPlan p = w_plan(1);
  uint32_t r = 0;
  for (int kt = 0; kt < 16; kt++)
    if (p.v[5][kt]) r |= (uint32_t)kt << (2 * (p.v[1][kt] - NUNITS));
  return r;
}
__host__ __device__ constexpr uint32_t w_emask() {
  const WPlan p = w_plan(1);
  uint32_t r = 0;
  for (int kt = 0; kt < 16; kt++) r |= (uint32_t)p.v[5][kt] << kt;
  return r;
}
static_assert((w_emask() & 3) == 0 && (w_early() & 15) < ((w_early() >> 4) & 15) && ((w_early() >> 4) & 15) < ((w_early() >> 8) & 15) &&
              ((w_early() >> 8) & 15) < (w_early() >> 12), "");
static_assert(w_plan(1).len % 10 == 0 && w_tab(2, 0, 0, 2, 8, 4) == 0x77776654u && w_tab(2, 2, 1, 2, 8, 4) == 0x77777666u &&
              q_backs(false, 0, false) == 0x44444445u && q_backs(true, 0, false) == 0x44444456u, "");
constexpr bool PRE_FLIP = w_plan(1).len % 20 != 0;
__device__ __forceinline__ int w_flips(int n) { return PRE_FLIP ? n : __popc(~PREMASK & ((1u << n) - 1u)); }
__host__ __device__ __forceinline__ uint32_t unit_off(int u, uint32_t dl) { return u * UNIT + (u < 10 ? dl : (u < 20 ? 0u - dl : 0u)); }

__global__ void __cluster_dims__(2, 1, 1) __launch_bounds__(512, 1) fused_kernel(const __grid_constant__ Params P) {
  constexpr uint32_t base = SBASE, bars = base + OFF_BAR, slots = base + OFF_SLOT;
  const int warp = __shfl_sync(0xffffffffu, threadIdx.x >> 5, 0), lane = threadIdx.x & 31;
  const int b = blockIdx.x, rank = b & 1;
  if (smem_u32(smem_raw) != base + (rank << 24)) __trap();
  int role = 0;
  {
    unsigned smid;
    asm volatile("mov.u32 %0, %smid;" : "=r"(smid));
    const int tc = smid >> 1;
    role = (tc < 32 ? (tc & 7) * 8 + (tc >> 3) : (tc < 62 ? ((tc - 32) % 7 + 1) * 8 + 4 + (tc - 32) / 7 : tc - 58)) & 63;
  }
  if (warp == 12) {
    if (elect_one()) {
#pragma unroll
      for (int s = 0; s < 8; s++) {
        mbar_init(bars + 8u * (B_FULL + s), 1);
        mbar_init(bars + 8u * (B_EMPTY + s), LOCE ? 2 : 4);
        mbar_init(bars + 8u * (B_LOC + s), 2);
      }
      mbar_init(bars + 8u * B_GO, 1);
      mbar_init(bars + 8u * B_ROLE, 1);
      mbar_expect_tx(bars + 8u * B_ROLE, 4);
      fence_barrier_init();
    }
    __syncwarp();
  }
  asm volatile("barrier.cluster.arrive.relaxed.aligned;" ::: "memory");
  if (threadIdx.x == 0) {
    mbar_init(bars + 8u * B_PREP, 1);
    mbar_init(bars + 8u * (B_PREP + 1), 1);
    for (int s = 0; s < 4; s++) mbar_init(bars + 8u * (B_HALO + s), 1);
    for (int s = 0; s < 3; s++) mbar_init(bars + 8u * (B_REL + s), 8);
    mbar_init(bars + 8u * B_AFREE, 2);
    mbar_init(bars + 8u * B_TURN, 4);
    mbar_init(bars + 8u * (B_TURN + 1), 4);
    mbar_init(bars + 8u * B_CS, 1);
    mbar_init(bars + 8u * B_HB, 1);
    mbar_init(bars + 8u * B_KVS, 1);
    for (int s = 0; s < 4; s++) mbar_init(bars + 8u * (B_PRE + s), 1);
    mbar_init(bars + 8u * B_RESF, 1);
    mbar_init(bars + 8u * B_RESE, 4);
    mbar_init(bars + 8u * B_CSD, 4);
    mbar_init(bars + 8u * B_XRDY, 1);
    mbar_init(bars + 8u * (B_XRDY + 1), 1);
    fence_barrier_init();
  }
  if (warp == 15 && rank == 0) {
    const unsigned ep = *(volatile unsigned*)(g_flags + F_DONE);
    int r = role;
#pragma unroll 1
    for (int it = 0; it < 64; it++, r = (r + 1) & 63) {
      if (__all_sync(0xffffffffu, (ep - atom_add(g_flags + F_ROLE + r * RSTR, NCTA, lane == 0) < NCTA) | (lane != 0))) break;
      atom_add(g_flags + F_ROLE + r * RSTR, 0u - NCTA, lane == 0);
    }
    asm volatile("barrier.cluster.wait.aligned;" ::: "memory");
    asm volatile("{\n.reg .pred p;\nsetp.lt.u32 p, %3, 2;\n"
                 "@p st.async.weak.shared::cluster.mbarrier::complete_tx::bytes.b32 [%0], %1, [%2];\n}\n" ::"r"(base + OFF_ROLE + (lane << 24)),
                 "r"(r), "r"(bars + 8u * B_ROLE + (lane << 24)), "r"(lane)
                 : "memory");
  } else if (warp != 12) {
    asm volatile("barrier.cluster.wait.aligned;" ::: "memory");
  }
#define ROLE_IDS                                                                                   \
  const int qr = role & 7, hp = (role >> 3) * 2 + rank, rt = role & 15, ct = ((role >> 3) & 6) + rank; \
  (void)qr; (void)hp; (void)rt; (void)ct;
#define ROLE_GET                                                          \
  named_bar_sync(0, 512);                                                 \
  role = __shfl_sync(0xffffffffu, (int)lds32(base + OFF_ROLE), 0);

  if (warp < 12) {
    const bool asst = warp >= 8;
    ROLE_GET
    ROLE_IDS
    uint32_t tpar = 0;
    const uint32_t ebar = LOCE && (warp & 2) ? bars + 8u * B_LOC + (rank << 24) : bars + 8u * B_EMPTY + ((warp & 1) << 24);
    GTL(0);
#pragma unroll 1
    for (int inst = (warp < 4 ? 0 : -1) + (int)P.zero; inst < 8; inst += asst ? 1 : 2) {
      const int L = inst >> 1, ch = inst & 1, gb = ch * 8 + qr;
      if (inst >= 0) {
      if (asst) {
        setmaxnreg_dec<24>();
        named_bar_sync(4, 256);
        setmaxnreg_inc<128>();
      } else {
      setmaxnreg_inc<224>();
      {
        float acc[2][96];
        const int ksp = q_split(inst);
        int n = q_first(inst);
        uint32_t dlt = inst > 0 && (w_flips(inst - 1) & 1) ? 10u * (UNIT >> 4) : 0u;
        if (inst == 1 || (inst > 1 && q_split(inst - 1) != 8)) {
          mbar_wait_lazy<100>(bars + 8u * (B_TURN + ch), tpar);
          tpar ^= 1u;
        }
        if (L == 3) GTL(37);
        mbar_wait(bars + 8u * (B_FULL + (n & 7)), (n >> 3) & 1);
        GTL(1 + L * 8);
        {
          const uint32_t da = (base >> 4) + 0x10000u + dlt;
          const uint64_t db = desc_lo(da - 0x10000u + ((UNIT >> 4) << 16) + 2 * (UNIT >> 4));
          wgmma_fence();
          wgmma_n192_ssz_ta0_tb1(acc[0], desc_lo(da), db);
          wgmma_commit();
          wgmma_n192_ssz_ta0_tb1(acc[1], desc_lo(da + (UNIT >> 4)), db);
          wgmma_commit();
        }
#pragma unroll 1
        for (int k2 = 0; k2 < 7; k2++) {
          const bool brk = k2 + 1 == ksp;
#pragma unroll
          for (int ks = 0; ks < 2; ks++, n++) {
            STAMP(inst == KSQ, k2 * 2 + ks);
            const uint32_t da = ((base + ks * 5 * UNIT) >> 4) + 0x10000u + dlt;
            const uint32_t dbb = da - 0x10000u + ((UNIT >> 4) << 16) + 2 * (UNIT >> 4);
#pragma unroll
            for (int k16 = 0; k16 < 4; k16++) {
              if (ks == 0 && k16 == 0 && k2 == 0) continue;
              const uint64_t db = desc_lo(dbb + k16 * 128);
              wgmma_fence();
              wgmma_n192_ss_ta0_tb1(acc[0], desc_lo(da + k16 * 2), db, 1);
              wgmma_commit();
              wgmma_wait<1>();
              if (k16 == 0) warp_arrive_cl(ebar + 8u * ((n - 1) & 7), ks != 0 || k2 != ksp);
              wgmma_fence();
              wgmma_n192_ss_ta0_tb1(acc[1], desc_lo(da + (UNIT >> 4) + k16 * 2), db, 1);
              wgmma_commit();
              bool ok = true;
              if (k16 == 2) ok = mbar_test(bars + 8u * (B_FULL + ((n + 1) & 7)), ((n + 1) >> 3) & 1) || (ks == 1 && brk);
              if (k16 == QTURN && ks == 1) warp_arrive(bars + 8u * (B_TURN + (ch ^ 1)), brk);
              if (ks == 0 || k16 < 3) wgmma_wait<1>();
              if (k16 == 2 && !ok) mbar_wait(bars + 8u * (B_FULL + ((n + 1) & 7)), ((n + 1) >> 3) & 1);
            }
          }
          if (brk) {
            wgmma_wait<0>();
            warp_arrive_cl(ebar + 8u * ((n - 1) & 7));
            n += 16;
            mbar_wait_lazy<100>(bars + 8u * (B_TURN + ch), tpar);
            tpar ^= 1u;
            STAMP(inst == KSQ, 17);
            mbar_wait(bars + 8u * (B_FULL + (n & 7)), (n >> 3) & 1);
          }
          if (!brk || (!PRE_FLIP && w_pre(inst - 1))) dlt ^= 10u * (UNIT >> 4);
        }
        auto tail_group = [&](int u) {
          const uint32_t da = ((base + (u & 1) * 5 * UNIT) >> 4) + 0x10000u + dlt;
          const uint32_t dbb = da - 0x10000u + ((UNIT >> 4) << 16) + 2 * (UNIT >> 4);
          if (u < 3) wgmma_fence();
#pragma unroll
          for (int k16 = 0; k16 < 4; k16++)
            wgmma_n192_ss_ta0_tb1(acc[u < 2], desc_lo(da + (u < 2 ? UNIT >> 4 : 0) + k16 * 2), desc_lo(dbb + k16 * 128), 1);
          wgmma_commit();
        };
        STAMP(inst == KSQ, 14);
        tail_group(0);
        wgmma_wait<1>();
        STAMP(inst == KSQ && KSPN, 42);
        warp_arrive_cl(ebar + 8u * ((n - 1) & 7), ksp != 7);
        PHASE_IDS
        mbar_wait(bars + 8u * (B_PREP + ch), L & 1);
        STAMP(inst == KSQ && KSPN, 43);
        uint32_t rs[4];
#pragma unroll
        for (int i = 0; i < 4; i++)
          rs[i] = lds32(base + OFF_RS + (ch * 128 + (i >> 1) * 64 + wwarp * 16 + g + 8 * (i & 1)) * 4);
        auto fold = [&](int h) {
          uint32_t a[2];
#pragma unroll
          for (int r = 0; r < 2; r++) a[r] = c == (L & 1) ? __byte_perm(rs[2 * h + r], 0, 0x1010) ^ 0x80008000u : 0u;
          uint64_t d;
          asm("mov.b64 %0, {%1, %2};" : "=l"(d) : "r"(((base + OFF_CS) >> 4) + ((512 >> 4) << 16)), "r"(0x40000000u));
          wgmma_fence();
          wgmma_n192_rs_tb1(acc[h], a[0], a[1], d);
        };
        fold(1);
        wgmma_commit();
        mbar_wait(bars + 8u * (B_FULL + ((n + 1) & 7)), ((n + 1) >> 3) & 1);
        STAMP(inst == KSQ && KSPN, 44);
        tail_group(1);
        tail_group(2);
        STAMP(inst == KSQ && KSPN, 45);
        const bool ppre = ksp == 7 && w_pre(inst - 1);
        const uint32_t fbar = bars + 8u * (ppre ? (LOCE ? B_LOC : B_EMPTY) + ((n - 1) & 7) : (inst == CSI + 1 ? B_CSD : B_AFREE));
        const uint32_t fpar = ppre ? ((n - 1) >> 3) & 1 : (inst == CSI + 1 ? 0 : ch);
        const bool afree = mbar_test(fbar, fpar);
        float rinv[2][2];
#pragma unroll
        for (int i = 0; i < 4; i++) rinv[i >> 1][i & 1] = rcp_fast(bf_hi(rs[i]));
        const int mat = lane >> 3;
        const uint32_t soff = (wwarp * 16 + (mat & 1) * 8 + (lane & 7)) * 128;
        const uint32_t kdst = ((L & 1) ? KB_ROW0 : slots) + soff, vdst = ((L & 1) ? VB_ROW0 : slots + 8192) + soff;
        const uint32_t hs = (L & 1) ? 8192 : 16384;
        const int rg = 2 * wwarp + (mat & 1);
        const uint32_t qdst = slots + 3 * 16384 + ((L & 1) ? soff : ((rg < 4 ? 2 * rg : 15 - 2 * rg) * 8 + (lane & 7)) * 128);
        wgmma_wait<2>();
        STAMP(inst == KSQ && KSPN, 46);
        fold(0);
        tail_group(3);
        STAMP(inst == KSQ && KSPN, 47);
        warp_arrive(bars + 8u * (B_TURN + (ch ^ 1)));
        if (!afree) {
          wgmma_wait<1>();
          warp_arrive_cl(ebar + 8u * (n & 7));
          wgmma_wait<0>();
          warp_arrive_cl(ebar + 8u * ((n + 1) & 7));
          mbar_wait(fbar, fpar);
        }
        wgmma_wait<2>();
        reg_fence<96>(acc[1]);
        STAMP(inst == KSQ, 15);
#pragma unroll
        for (int t = 0; t < 24; t++) {
          const int h = t < 12 ? 1 : 0, p = (t % 12 / 4 + 1) % 3, jp = t & 3;
          if (t == EPW1) {
            wgmma_wait<1>();
            warp_arrive_cl(ebar + 8u * (n & 7), afree);
          }
          if (t == EPW0) {
            wgmma_wait<0>();
            reg_fence<96>(acc[0]);
            warp_arrive_cl(ebar + 8u * ((n + 1) & 7), afree);
            STAMP(inst == KSQ, 16);
            GTL(2 + L * 8);
          }
          if (t % 12 == 8) {
            rinv[h][0] *= SM_C;
            rinv[h][1] *= SM_C;
          }
          const uint32_t swz = ((2 * jp + (mat >> 1)) ^ (lane & 7)) << 4;
          const float* a = &acc[h][32 * p + 8 * jp];
          const uint32_t dst = p == 0 ? qdst + h * 8192 : (p == 1 ? kdst : vdst) + h * hs;
          stmatrix_x4(dst + swz, pack_bf16x2(a[0] * rinv[h][0], a[1] * rinv[h][0]), pack_bf16x2(a[2] * rinv[h][1], a[3] * rinv[h][1]),
                      pack_bf16x2(a[4] * rinv[h][0], a[5] * rinv[h][0]), pack_bf16x2(a[6] * rinv[h][1], a[7] * rinv[h][1]));
          if (t % 12 == 7) {
            fence_proxy_async_smem();
            if (t == 7) named_bar_arrive(3, (L & 1) ? 192 : 160);
            else if ((L & 1) == 0) named_bar_arrive(7, 160);
            if (t > EPW0) sched_fence(P.zero);
          }
        }
      }
      fence_proxy_async_smem();
      setmaxnreg_dec<128>();
      named_bar_sync(4, 256);
      }
      GTL(3 + L * 8);
      {
        PHASE_IDS
        if ((L & 1) == 0) attention_a(asst, L, gb, hp, inst & 1, ch, (tid_ >> 5) & 3, lane, P.zero);
        else attention_b(asst, gb, inst & 1, wwarp, lane, KSAON);
        GTL(4 + L * 8);
        fence_proxy_async_smem();
      }
      if (!asst) {
      {
        named_bar_sync(5, 256);
        STAMP(KSAON, 27);
        if ((warp & 3) == 0 && elect_one()) {
          tma_store_3d(&P.o, (L & 1) ? slots + 3 * 16384 : OA_TILE, 0, gb * 128, hp);
          bulk_commit();
          bulk_wait0();
          STAMP(KSAON, 31);
          mbar_arrive(bars + 8u * B_AFREE);
          mbar_wait(bars + 8u * B_AFREE, ch ^ 1);
          announce(g_flags + F_O + gb * OSTR + hp);
        }
        __syncwarp();
      }
      GTL(5 + L * 8);

      {
        float acc[64];
        const int n0 = w_first(inst);
        const bool pre = w_pre(inst);
        const uint32_t dl = ((w_flips(inst) + q_split(inst + 1)) & 1) * 10u * UNIT;
        const uint2* tab = P.wtab[2 * pre + (dl != 0)];
        const uint32_t ppar = __popc(PREMASK & ((1u << inst) - 1u)) & 1;
        uint32_t pbar = bars + 8u * B_PRE;
        const uint32_t flg = (pre ? w_emask() >> 1 : 0u) | (inst >= 6 || q_split(inst + 1) != 8 ? 1u << 30 : 0u);
        uint2 e = tab[0];
        mbar_wait_lazy<100>(bars + 8u * (B_TURN + ch), tpar);
        tpar ^= 1u;
        mbar_wait(bars + 8u * (B_FULL + (n0 & 7)), (n0 >> 3) & 1);
        GTL(6 + L * 8);
        auto wstep = [&](auto first_, int kt) {
          constexpr bool first = decltype(first_)::value;
          const int n = n0 + kt;
          STAMP(inst == KSW, 20 + kt);
          wgmma_fence();
          if (first) wgmma_n128_ssz_ta0_tb1(acc, desc_lo(e.x), desc_lo(e.y));
#pragma unroll
          for (int k16 = first ? 1 : 0; k16 < 4; k16++) wgmma_n128_ss_ta0_tb1(acc, desc_lo(e.x + 2 * k16), desc_lo(e.y + 128 * k16), 1);
          wgmma_commit();
          if (!first) warp_arrive(bars + 8u * (B_TURN + (ch ^ 1)), (flg >> kt) & 0x8000u);
          e = tab[kt + 1];
          const uint32_t nb = bars + 8u * (kt == 15 ? B_RESF : B_FULL + ((n + 1) & 7)), np = kt == 15 ? ch : ((n + 1) >> 3) & 1;
          const bool ok = mbar_test(nb, np);
          if (!first) {
            wgmma_wait<1>();
            warp_arrive_cl(ebar + 8u * ((n - 1) & 7));
            if ((flg >> kt) & 1u) {
              mbar_wait(pbar, ppar);
              pbar += 8u;
            }
          }
          if (!ok) mbar_wait(nb, np);
        };
        wstep(std::true_type(), 0);
#pragma unroll WUNR
        for (int kt = 1; kt < 16; kt++) wstep(std::false_type(), kt);
        PHASE_IDS
        const uint32_t xb = e.x;
        const int grow = ch * 1024 + rt * 64;
        const int mat = lane >> 3;
        const uint32_t xrow = xb + (wwarp * 16 + (mat & 1) * 8 + (lane & 7)) * 128;
        uint32_t xv[8][4];
#pragma unroll
        for (int jp = 0; jp < 8; jp++)
          ldmatrix_x4(xv[jp], xrow + (jp >> 2) * UNIT + (((2 * (jp & 3) + (mat >> 1)) ^ (lane & 7)) << 4));
        wgmma_wait<0>();
        reg_fence<64>(acc);
        warp_arrive_cl(ebar + 8u * ((n0 + 15) & 7));
        STAMP(inst == KSW, 36);
        GTL(7 + L * 8);
#pragma unroll
        for (int jp = 0; jp < 8; jp++) {
#pragma unroll
          for (int q = 0; q < 4; q++) xv[jp][q] = add_bf16x2(xv[jp][q], pack_bf16x2(acc[8 * jp + 2 * q], acc[8 * jp + 2 * q + 1]));
          stmatrix_x4(xrow + (jp >> 2) * UNIT + (((2 * (jp & 3) + (mat >> 1)) ^ (lane & 7)) << 4), xv[jp][0], xv[jp][1],
                      xv[jp][2], xv[jp][3]);
          if ((jp & 3) == 3) {
            fence_proxy_async_smem();
            __syncwarp();
            if (elect_one()) {
              tma_store_3d(&P.xw[L == 3], xb + (jp >> 2) * UNIT + wwarp * 2048, 0, grow + wwarp * 16, ct * 2 + (jp >> 2));
              bulk_commit();
            }
            __syncwarp();
          }
        }
        STAMP(inst == KSW, 37);
        if (elect_one()) {
          bulk_wait0();
          mbar_arrive(bars + 8u * B_RESE);
        }
        __syncwarp();
        if (wwarp == 0 && L < 3) {
          mbar_wait(bars + 8u * B_RESE, ch);
          STAMP(inst == KSW, 38);
          if (elect_one()) announce(g_flags + F_X + (ch * 8 + (rt >> 1)) * XSTR + ct);
          __syncwarp();
          STAMP(inst == KSW, 39);
        }
        if (L < 3) {
          const unsigned ep1 = lds32(base + OFF_EPOCH);
          float s1[2] = {0.f, 0.f}, s2[2] = {0.f, 0.f};
#pragma unroll
          for (int jp = 0; jp < 8; jp++)
#pragma unroll
            for (int q = 0; q < 4; q++) {
              const float x0 = bf_lo(xv[jp][q]), x1 = bf_hi(xv[jp][q]);
              s1[q & 1] += x0 + x1;
              s2[q & 1] = fmaf(x0, x0, fmaf(x1, x1, s2[q & 1]));
            }
#pragma unroll
          for (int r = 0; r < 2; r++) {
            s1[r] += __shfl_xor_sync(0xffffffffu, s1[r], 1);
            s2[r] += __shfl_xor_sync(0xffffffffu, s2[r], 1);
            s1[r] += __shfl_xor_sync(0xffffffffu, s1[r], 2);
            s2[r] += __shfl_xor_sync(0xffffffffu, s2[r], 2);
            if (c == 0) st_rec(&g_stats[L + 1][ct][grow + wwarp * 16 + g + 8 * r], s1[r], s2[r], 0.f, ep1);
          }
        }
        GTL(8 + L * 8);
      }
      continue;
      }
      named_bar_arrive(5, 256);
      if (inst != CSI) continue;
      mbar_wait(bars + 8u * B_AFREE, CSI ^ 1);
      }
      if (asst) {
        colsum_part(&P.wqkv[inst >= 0], inst >= 0, qr, hp);
      } else {
      PHASE_IDS
      {
        const unsigned ep1 = (*(volatile unsigned*)(g_flags + F_DONE)) / NCTA + 1u;
        const int row = b * 16 + (tid >> 3);
        const uint4* src = reinterpret_cast<const uint4*>(P.in_x + (size_t)row * DM) + (tid & 7);
        float s1 = 0.f, s2 = 0.f;
#pragma unroll 1
        for (int k = 0; k < 4; k++) {
          mbar_pace(bars + 8u * (B_EMPTY + PXB * k / 2), 0);
          uint4 v[4];
#pragma unroll
          for (int j = 0; j < 4; j++) v[j] = __ldg(src + (k * 4 + j) * 8);
#pragma unroll
          for (int j = 0; j < 4; j++) {
            const uint32_t w[4] = {v[j].x, v[j].y, v[j].z, v[j].w};
#pragma unroll
            for (int e = 0; e < 4; e++) {
              const float x0 = bf_lo(w[e]), x1 = bf_hi(w[e]);
              s1 += x0 + x1;
              s2 = fmaf(x0, x0, fmaf(x1, x1, s2));
            }
          }
        }
#pragma unroll
        for (int o = 1; o < 8; o <<= 1) {
          s1 += __shfl_xor_sync(0xffffffffu, s1, o);
          s2 += __shfl_xor_sync(0xffffffffu, s2, o);
        }
        if ((tid & 7) == 0) st_rec(&g_stats[0][0][row], s1, s2, 0.f, ep1);
        if (tid == 0) sts32(base + OFF_EPOCH, ep1);
        STAMP(KSQ == 0, 51);
        float4 v[6];
#pragma unroll 1
        for (uint32_t it = 0; it < (1u << 17); ++it) {
          bool ok = true;
#pragma unroll
          for (int t = 0; t < 6; t++) {
            v[t] = ld_rec(t < 2 ? &g_stats[0][0][(t * 8 + qr) * 128 + tid] : &g_cs[0][hp][(tid & 1) * 4 + t - 2][tid >> 1]);
            ok &= __float_as_uint(v[t].w) == ep1;
          }
          STAMP(KSQ == 0 && it == 0, 18);
          if (ok) break;
          __nanosleep(100);
        }
        STAMP(KSQ == 0, 17);
        __syncwarp();
        STAMP(KSQ == 0, 19);
#pragma unroll
        for (int cc = 0; cc < 2; cc++) sts32(base + OFF_RS + (cc * 128 + tid) * 4, ln_params(v[cc].x, v[cc].y));
        const float cs[3] = {(v[2].x + v[3].x) + (v[4].x + v[5].x), (v[2].y + v[3].y) + (v[4].y + v[5].y),
                             (v[2].z + v[3].z) + (v[4].z + v[5].z)};
#pragma unroll
        for (int blk = 0; blk < 3; blk++) {
          const float t = cs[blk] + __shfl_xor_sync(0xffffffffu, cs[blk], 1);
          cs_put(blk, tid & 1, tid >> 1, (tid & 1) ? 0.f : t);
        }
        fence_proxy_async_smem();
        named_bar_sync(2, 128);
        if (tid < 2) mbar_arrive(bars + 8u * (B_PREP + tid));
        STAMP(KSQ == 0, 48);
      }
      }
    }
    if (threadIdx.x == 128) atomicAdd(g_flags + F_DONE, 1u);
    if (!asst) asm volatile("barrier.cluster.arrive.relaxed.aligned;\nbarrier.cluster.wait.aligned;" ::: "memory");
    if (P.zero == 0) return;
  } else {
    setmaxnreg_dec<32>();
    if (warp != 12) {
      ROLE_GET
    }
    if (warp != 15) {
    if (warp == 14) {
      ROLE_IDS
      const unsigned ep1 = (*(volatile unsigned*)(g_flags + F_DONE)) / NCTA + 1u;
      uint32_t hbp = 0;
#pragma unroll 1
      for (int inst = 0; inst < 8; inst++) {
        const int L = inst >> 1, ch = inst & 1, gb = ch * 8 + qr;
        if ((L & 1) == 0) {
          const unsigned* fp = g_flags + F_KV + (max(gb - 1 - ((lane >> 1) & 1), 0) * 16 + hp) * KSTR + (lane & 1);
          uint32_t seen = gb == 0 ? 15u : (gb == 1 ? 12u : 0u);
          named_bar_sync(3, 160);
          STA(34);
          if (elect_one()) {
#pragma unroll 1
            for (int o = 0, pc = (PCM >> inst) & 1 ? PCS : 16384; o < 16384; o += pc) {
              bulk_store(g_kvA[L >> 1][gb][hp][1] + o, slots + 16384 + o, pc);
              if ((PCM >> inst) & 1) spin(PCN);
            }
            bulk_commit();
            bulk_wait0();
            STA(35);
            announce(g_flags + F_KV + (gb * 16 + hp) * KSTR);
            STA(41);
          }
          __syncwarp();
#pragma unroll 1
          for (int i = 0; i < 4; i++) {
            wait_lanes(fp, 2u * ep1 - 1u + (L >> 1), 1u << i, seen);
            STA(36 + i);
            if (i > 0) mbar_wait_lazy<RELNS>(bars + 8u * (B_REL + i - 1), ch);
            if (i == 2) mbar_wait(bars + 8u * B_KVS, ch);
            if (elect_one()) {
              mbar_expect_tx(bars + 8u * (B_HALO + i), 16384);
              bulk_load(slots + (i == 3 ? 2 : 2 - i) * 16384, gb > (i >> 1) ? g_kvA[L >> 1][gb - 1 - (i >> 1)][hp][(i & 1) ^ 1] : g_zero,
                        16384, bars + 8u * (B_HALO + i));
            }
          }
        } else {
          const uint8_t* src = gb > 0 ? g_kvB[L >> 1][gb - 1][hp] : g_zero;
          const uint32_t o = slots + lane * 32 + (lane & 28);
          named_bar_sync(3, 192);
          STA(34);
          if (elect_one()) spin(HBD);
          __syncwarp();
#pragma unroll 1
          for (uint32_t it = 0; it < (1u << 16); ++it) {
            if (elect_one()) {
              mbar_expect_tx(bars + 8u * B_HB, 4096);
              bulk_load(KB_ROW0 - 2048, src, 2048, bars + 8u * B_HB);
              bulk_load(VB_ROW0 - 2048, src + 2048, 2048, bars + 8u * B_HB);
            }
            mbar_wait(bars + 8u * B_HB, hbp);
            hbp ^= 1u;
            const uint32_t m = max(max(lds32(o), lds32(o + 1024)), max(lds32(o + 24576), lds32(o + 24576 + 1024)));
            STA(36 + min(it, 3u));
            if (__reduce_max_sync(0xffffffffu, m) != 0xffffffffu) break;
            fence_proxy_async_smem();
            __syncwarp();
          }
          warp_arrive(bars + 8u * B_HALO);
        }
        named_bar_sync(9, 288);
        if (elect_one()) {
          tma_store_3d(&P.o, ((L & 1) ? slots + 3 * 16384 : OA_TILE) + 8192, 0, gb * 128 + 64, hp);
          bulk_commit();
          bulk_wait0();
          mbar_arrive(bars + 8u * B_AFREE);
        }
        __syncwarp();
        if (w_pre(inst)) {
          mbar_wait(bars + 8u * B_KVS, ch);
          mbar_wait(bars + 8u * B_AFREE, (inst & 1) ^ 1);
          if (inst == CSI) mbar_wait(bars + 8u * B_CSD, 0);
#pragma unroll 1
          for (int j = 0; j < 4; j++) {
            constexpr uint32_t early = w_early();
            if (elect_one()) {
              mbar_expect_tx(bars + 8u * (B_PRE + j), 2 * UNIT);
              tma_load_3d(slots + j * 2 * UNIT, &P.wo[L & 1], bars + 8u * (B_PRE + j), ct * 128, ((early >> (4 * j)) & 15) * 64, 0);
            }
            __nanosleep(PRENS);
          }
        }
      }
    } else if (warp == 13) {
      ROLE_IDS
      uint32_t n = 16 + rank, dl = 0;
      uint32_t back = 0x44444444u;
      mbar_wait(bars + 8u * B_GO, 0);
      const unsigned ep1 = __shfl_sync(0xffffffffu, (*(volatile unsigned*)(g_flags + F_DONE)) / NCTA + 1u, 0);
#pragma unroll 1
      for (int sg = 4; sg < 34; sg++) {
        const int part = sg & 3, si = (sg >> 2) - (part & 1), L = si >> 1, ch = si & 1;
        const int k0 = part == 2 ? 2 * q_split(si) : 0, k1 = part == 0 ? 2 * q_split(si) : 16;
        if (part == 3 || k0 == k1) continue;
        const bool wj = part == 1;
        uint32_t seen = 0u;
        if (!wj && (L == 0 || __any_sync(0xffffffffu, mbar_test(bars + 8u * (B_XRDY + ch), (L & 1) ^ 1)))) {
          seen = 0xFFFFu;
          fence_proxy_async_all();
        }
        const CUtensorMap* map = wj ? &P.o : &P.xq[L == 0 ? 0 : 1];
        const unsigned* fl = g_flags + (wj ? F_O + (ch * 8 + (rt >> 1)) * OSTR : F_X + (ch * 8 + qr) * XSTR);
        const unsigned target = wj ? 4u * ep1 - 3u + L : 6u * ep1 - 6u + 2u * L;
        const int row = ch * 1024 + (wj ? rt * 64 : qr * 128);
        const bool pre = w_pre(si);
        uint64_t units = rank ? 0x0f050f050f050f05ull : 0x0a000a000a000a00ull;
        if (wj) {
          constexpr uint32_t b00 = (uint32_t)w_tab(2, 0, 0, 2, 8, 4), b01 = (uint32_t)w_tab(2, 0, 1, 2, 8, 4), b10 = (uint32_t)w_tab(2, 1, 0, 2, 8, 4),
                             b11 = (uint32_t)w_tab(2, 1, 1, 2, 8, 4), b20 = (uint32_t)w_tab(2, 2, 0, 2, 8, 4), b21 = (uint32_t)w_tab(2, 2, 1, 2, 8, 4);
          constexpr uint64_t u00 = w_tab(0, 0, 0, 2, 8, 8), u01 = w_tab(0, 0, 1, 2, 8, 8), u10 = w_tab(0, 1, 0, 2, 8, 8), u11 = w_tab(0, 1, 1, 2, 8, 8);
          back = pre ? (rank ? b11 : b10) : (si == 7 ? (rank ? b21 : b20) : (rank ? b01 : b00));
          units = pre ? (rank ? u11 : u10) : (rank ? u01 : u00);
        }
#pragma unroll 1
        for (int kt = k0 + rank; kt < k1; kt += 2, n += 2, back = (back >> 4) | 0x40000000u, units >>= 8) {
          wait_mask<false>(fl, 16, target, 1u << (wj ? kt : kt >> 1), seen, lane);
          const uint32_t nw = n - (back & 15u), pos = ((uint32_t)units & 31u) * UNIT + dl;
          mbar_wait(bars + 8u * (B_EMPTY + (nw & 7u)), (nw >> 3) & 1u);
          if (elect_one())
            tma_load_3d_mc(base + (pos >= 20 * UNIT ? pos - 20 * UNIT : pos), map, bars + 8u * (B_FULL + (n & 7u)), 0, row, kt);
        }
        if (wj ? !pre || PRE_FLIP : ((k1 - k0) & 2)) dl ^= 10u * UNIT;
        constexpr uint32_t q00 = q_backs(true, 0, false), q01 = q_backs(true, 1, false), q10 = q_backs(true, 0, true), q11 = q_backs(true, 1, true);
        if (wj) back = pre ? (rank ? q11 : q10) : (rank ? q01 : q00);
      }
    } else {
#pragma unroll 1
      for (int att = P.zero; att < 2; att++) {
        ROLE_IDS
#pragma unroll 1
        for (int s = 0; s < 4; s++) {
          if (elect_one()) {
            mbar_expect_tx(bars + 8u * (B_FULL + s), 5 * UNIT);
            tma_load_3d(base + s * 5 * UNIT, &P.xq[0], bars + 8u * (B_FULL + s), 0, qr * 128, s);
            tma_load_3d(base + (s * 5 + 2) * UNIT, &P.wqkv[0], bars + 8u * (B_FULL + s), hp * 64, s * 64, 0);
          }
        }
        if (att) break;
        asm volatile("barrier.cluster.wait.aligned;" ::: "memory");
        mbar_wait(bars + 8u * B_ROLE, 0);
        const int r = __shfl_sync(0xffffffffu, (int)lds32(base + OFF_ROLE), 0);
        if (r == role) break;
        role = r;
#pragma unroll 1
        for (int s = 0; s < 4; s++) {
          mbar_wait(bars + 8u * (B_FULL + s), 0);
          __syncwarp();
          if (elect_one()) {
            asm volatile("mbarrier.inval.shared::cta.b64 [%0];" ::"r"(sw(bars + 8u * (B_FULL + s))) : "memory");
            mbar_init(bars + 8u * (B_FULL + s), 1);
          }
        }
        fence_barrier_init();
        fence_proxy_async_smem();
        __syncwarp();
      }
      named_bar_arrive(0, 512);
      ROLE_IDS
#pragma unroll 1
      for (int s = 4; s < 16; s++) {
        const uint32_t fb = bars + 8u * (B_FULL + (s & 7)), sa = base + (s & 3) * 5 * UNIT;
        mbar_wait(bars + 8u * (B_EMPTY + ((s - 4) & 7)), ((s - 4) >> 3) & 1);
        if (elect_one()) {
          mbar_expect_tx(fb, 5 * UNIT);
          if ((s & 1) == rank) tma_load_3d_mc(sa, &P.xq[0], fb, 0, qr * 128, s);
          tma_load_3d(sa + 2 * UNIT, &P.wqkv[0], fb, hp * 64, s * 64, 0);
        }
      }
      if (elect_one()) mbar_arrive(bars + 8u * B_GO);
      const uint32_t wbase = sw(base), wbars = sw(bars);
      uint2 e = P.ptab[0];
#pragma unroll 1
      for (int i = 1; i <= NPT; i++) {
        const uint32_t wb = (e.x & 0x1f8u) | wbars, par = e.x >> 31, fl = e.x;
        uint32_t dst = (e.x & 0x3e000u) | wbase, fb = (e.y & 0x1f8u) | wbars, bytes = e.y & 0xe000u, nold = e.y & 1u;
        int c0 = (e.x & (1u << 29)) ? hp * 64 : ct * 128, c1 = ((e.x >> 18) & 0x7ffu) + ((e.x & (1u << 30)) ? rt * 64 : 0);
        const char* map = reinterpret_cast<const char*>(&P) + (e.y >> 21);
        asm volatile("" : "+r"(dst), "+r"(fb), "+r"(bytes), "+r"(nold), "+r"(c0), "+r"(c1), "+l"(map));
        e = P.ptab[i];
        if (fl & 2u) mbar_wait(bars + 8u * B_RESE, (fl >> 2) & 1u);
        if (!(fl & 1u)) mbar_wait_raw(wb, par);
        asm volatile(
            "{\n.reg .pred p, q;\nelect.sync _|p, 0xffffffff;\nsetp.eq.and.u32 q, %6, 0, p;\n"
            "@p mbarrier.arrive.expect_tx.shared::cta.b64 _, [%2], %5;\n"
            "@q cp.async.bulk.tensor.3d.shared::cluster.global.mbarrier::complete_tx::bytes [%0], [%1, {%3, %4, %7}], [%2];\n}\n" ::"r"(dst),
            "l"(map), "r"(fb), "r"(c0), "r"(c1), "r"(bytes), "r"(nold), "r"(0)
            : "memory");
      }
    }
    return;
    }
  }
  {
    {
      ROLE_IDS
      const unsigned ep1 = (*(volatile unsigned*)(g_flags + F_DONE)) / NCTA + 1u;
#pragma unroll 1
      for (int inst = 0; inst < 8; inst++) {
        const int L = inst >> 1, ch = inst & 1, gb = ch * 8 + qr;
        if (inst == 1 || inst == 2) {
#pragma unroll 1
          for (int i = inst == 1 ? 0 : TRSP; i < (inst == 1 ? TRSP : 20); i++) {
            const char* src = i < 4 ? reinterpret_cast<const char*>(P.wo_p[0]) + i * 524288
                                    : (i < 16 ? reinterpret_cast<const char*>(P.wqkv_p1) + (i - 4) * 524288
                                              : reinterpret_cast<const char*>(P.wo_p[1]) + (i - 16) * 524288);
            asm volatile("prefetch.global.L2 [%0];" ::"l"(src + b * 4096 + lane * 128));
            __nanosleep(inst == 1 ? TRICKLE : TRICK2);
          }
        }
        if (inst >= 2) {
        uint32_t seen = 0;
        wait_mask<true>(g_flags + F_X + gb * XSTR, 8, 6u * ep1 - 6u + 2u * L, 0xFFu, seen, lane);
        if (lane == 0) mbar_arrive(bars + 8u * (B_XRDY + ch));
#pragma unroll 1
        for (int h = 0; h < 4; h++) {
          const float4* sp = &g_stats[L][0][gb * 128 + h * 32 + lane];
          const float4 s0 = sum_recs<4>(sp, S_LEN, ep1), s1 = sum_recs<4>(sp + 4 * S_LEN, S_LEN, ep1);
          sts32(base + OFF_RS + (ch * 128 + h * 32 + lane) * 4, ln_params(s0.x + s1.x, s0.y + s1.y));
        }
        if (inst == 2) {
          mbar_wait(bars + 8u * B_CSD, 0);
#pragma unroll 1
          for (int hf = 0; hf < 2; hf++) {
            const float4* cp = &g_cs[1][hp][0][hf * 32 + lane];
            const float4 s0 = sum_recs<4>(cp, 64, ep1), s1 = sum_recs<4>(cp + 4 * 64, 64, ep1);
            cs_put(0, 1, hf * 32 + lane, s0.x + s1.x);
            cs_put(1, 1, hf * 32 + lane, s0.y + s1.y);
            cs_put(2, 1, hf * 32 + lane, s0.z + s1.z);
          }
          fence_proxy_async_smem();
        }
        __syncwarp();
        if (lane == 0) mbar_arrive(bars + 8u * (B_PREP + ch));
        }
        named_bar_sync((L & 1) ? 3 : 7, (L & 1) ? 192 : 160);
        if (elect_one()) {
          if (L & 1) {
            bulk_store(g_kvB[L >> 1][gb][hp], KB_ROW0 + 112 * 128, 2048);
            bulk_store(g_kvB[L >> 1][gb][hp] + 2048, VB_ROW0 + 112 * 128, 2048);
          } else {
            spin(PDL);
#pragma unroll 1
            for (int o = 0, pc = (PCM >> inst) & 1 ? PCS : 16384; o < 16384; o += pc) {
              bulk_store(g_kvA[L >> 1][gb][hp][0] + o, slots + o, pc);
              if ((PCM >> inst) & 1) spin(PCN);
            }
          }
          bulk_commit();
          bulk_wait0();
          mbar_arrive(bars + 8u * B_KVS);
          STA(32);
          if ((L & 1) == 0) {
            announce(g_flags + F_KV + (gb * 16 + hp) * KSTR + 1);
          }
          STA(33);
        }
        __syncwarp();
      }
    }
  }
}

typedef CUresult (*PFN_tmEncode)(CUtensorMap*, CUtensorMapDataType, cuuint32_t, void*, const cuuint64_t*,
                                 const cuuint64_t*, const cuuint32_t*, const cuuint32_t*, CUtensorMapInterleave,
                                 CUtensorMapSwizzle, CUtensorMapL2promotion, CUtensorMapFloatOOBfill);

PFN_tmEncode get_encode_fn() {
  static PFN_tmEncode fn = nullptr;
  if (!fn) {
    cudaDriverEntryPointQueryResult qr;
    void* p = nullptr;
    cudaGetDriverEntryPoint("cuTensorMapEncodeTiled", &p, cudaEnableDefault, &qr);
    fn = (PFN_tmEncode)p;
  }
  return fn;
}

CUtensorMap make_map(const void* ptr, int rows, int cols, int inner, int blocks, int bs, int box_rows, int box_blk) {
  CUtensorMap m;
  cuuint64_t gdim[3] = {(cuuint64_t)inner, (cuuint64_t)rows, (cuuint64_t)blocks};
  cuuint64_t gstr[2] = {(cuuint64_t)cols * 2, (cuuint64_t)bs * 2};
  cuuint32_t box[3] = {64, (cuuint32_t)box_rows, (cuuint32_t)box_blk};
  cuuint32_t estr[3] = {1, 1, 1};
  get_encode_fn()(&m, CU_TENSOR_MAP_DATA_TYPE_BFLOAT16, 3, const_cast<void*>(ptr), gdim, gstr, box, estr,
                  CU_TENSOR_MAP_INTERLEAVE_NONE, CU_TENSOR_MAP_SWIZZLE_128B, CU_TENSOR_MAP_L2_PROMOTION_L2_128B,
                  CU_TENSOR_MAP_FLOAT_OOB_FILL_NONE);
  return m;
}

void make_tables(Params& P) {
  const WPlan pl[3] = {w_plan(0), w_plan(1), w_plan(2)};
  for (int m = 0; m < 4; m++)
    for (int kt = 0; kt < 17; kt++) {
      const WPlan& p = pl[m >> 1];
      const uint32_t dl = (m & 1) * 10u * UNIT;
      P.wtab[m][kt] = make_uint2(kt == 16 ? SBASE + unit_off(p.v[1][kt], dl) : ((SBASE + unit_off(p.v[0][kt], dl)) >> 4) + 0x10000u,
                                 ((SBASE + unit_off(p.v[1][kt], dl)) >> 4) + ((UNIT >> 4) << 16));
    }
  int np = 0;
  auto put = [&](int nw, int rp, uint32_t off, int c1, int kind, int fb, int units, const CUtensorMap* map) {
    P.ptab[np++] = make_uint2((nw < 0 ? 1u : 8u * ((LOCE ? B_LOC : B_EMPTY) + (nw & 7)) | (uint32_t)((nw >> 3) & 1) << 31) | (rp < 0 ? 0u : 2u | 4u * rp) |
                                  off | (uint32_t)c1 << 18 | (uint32_t)kind << 29,
                              8u * fb | (map ? 0u : 1u) | units * UNIT |
                                  (map ? (uint32_t)(reinterpret_cast<const char*>(map) - reinterpret_cast<const char*>(&P)) << 21 : 0u));
  };
  int n = 16, aw = 0;
  uint32_t dl = 0;
  uint32_t back = 0x44444444u;
  for (int sg = 4; sg < 34; sg++) {
    const int part = sg & 3, si = (sg >> 2) - (part & 1), L = si >> 1, ch = si & 1;
    const int k0 = part == 2 ? 2 * q_split(si) : 0, k1 = part == 0 ? 2 * q_split(si) : 16;
    if (part == 3) continue;
    if (part != 1) {
      for (int k2 = k0; k2 < k1; k2 += 2, aw--, dl ^= 10u * UNIT)
        for (int ks = 0; ks < 2; ks++, n++, back = (back >> 4) | 0x40000000u)
          put(n - (int)(back & 15u), ks == 1 && aw == 1 ? (part == 2) ^ ch : -1, (ks * 5 + 2) * UNIT + dl, (k2 + ks) * 64, 1,
              B_FULL + (n & 7), 5, &P.wqkv[L & 1]);
    } else {
      const bool pre = w_pre(si);
      const WPlan& p = pl[pre ? 1 : (aw == 2 ? 2 : 0)];
      for (int kt = 0; kt < 17; kt++) {
        const bool early = kt < 16 && p.v[5][kt];
        put(p.v[4][kt] ? n + kt - p.v[3][kt] : -1, !pre && kt == 6 && aw == 2 ? ch ^ 1 : -1, unit_off(p.v[1][kt], dl),
            kt == 16 ? ch * 1024 : kt * 64, kt == 16 ? 2 : 0, kt == 16 ? B_RESF : B_FULL + ((n + kt) & 7),
            kt == 16 ? 2 : (early ? 1 : 3), kt == 16 ? &P.xr[L == 0 ? 0 : 1] : (early ? nullptr : &P.wo[L & 1]));
      }
      n += 16;
      if (!pre || PRE_FLIP) dl ^= 10u * UNIT;
      back = q_backs(false, 0, pre);
      aw = 2;
    }
  }
  P.ptab[np] = make_uint2(0, 0);
}

}

extern "C" void kernel_launch(void* const* d_in, const int* in_sizes, int n_in, void* d_out, int out_size) {
  (void)in_sizes; (void)n_in; (void)out_size;
  void *p_o, *p_x;
  cudaGetSymbolAddress(&p_o, g_o);
  cudaGetSymbolAddress(&p_x, g_x);
  static bool attr_done = false;
  if (!attr_done) {
    cudaFuncSetAttribute(fused_kernel, cudaFuncAttributeMaxDynamicSharedMemorySize, SMEM_BYTES);
    attr_done = true;
  }
  Params P;
  P.in_x = (const __nv_bfloat16*)d_in[0];
  P.wo_p[0] = (const __nv_bfloat16*)d_in[2];
  P.wqkv_p1 = (const __nv_bfloat16*)d_in[4];
  P.wo_p[1] = (const __nv_bfloat16*)d_in[5];
  P.zero = 0;
  P.xq[0] = make_map(P.in_x, S_LEN, DM, 64, 16, 64, 128, 1);
  P.xq[1] = make_map(p_x, S_LEN, DM, 64, 16, 64, 128, 1);
  P.xr[0] = make_map(P.in_x, S_LEN, DM, DM - 64, 2, 64, 64, 2);
  P.xr[1] = make_map(p_x, S_LEN, DM, DM - 64, 2, 64, 64, 2);
  P.xw[0] = make_map(p_x, S_LEN, DM, 64, 16, 64, 16, 1);
  P.xw[1] = make_map(d_out, S_LEN, DM, 64, 16, 64, 16, 1);
  P.o = make_map(p_o, S_LEN, DM, 64, 16, 64, 64, 1);
  for (int t = 0; t < 2; t++) {
    P.wqkv[t] = make_map(d_in[3 * t + 1], DM, NQKV, 1024, 3, 1024, 64, 3);
    P.wo[t] = make_map(P.wo_p[t], DM, DM, DM - 64, 2, 64, 64, 2);
  }
  make_tables(P);
  fused_kernel<<<NCTA, 512, SMEM_BYTES>>>(P);
}
```

```cpp
#include <cuda_runtime.h>
#include <cuda_bf16.h>
#include <cuda.h>
#include <stdint.h>
#include <type_traits>

namespace {

constexpr int S_LEN = 2048;
constexpr int DM = 1024;
constexpr int NQKV = 3072;
constexpr int NCTA = 128;

__device__ __align__(1024) uint8_t g_kvA[2][16][16][2][16384];
__device__ __align__(1024) uint8_t g_kvB[2][16][16][4096];
__device__ __align__(1024) uint8_t g_zero[16384];
__device__ __align__(1024) __nv_bfloat16 g_o[S_LEN * DM];
__device__ __align__(1024) __nv_bfloat16 g_x[S_LEN * DM];
__device__ __align__(1024) float4 g_stats[4][8][S_LEN];
__device__ __align__(1024) float4 g_cs[2][16][8][64];
#define RSTR 1
constexpr int F_X = 0;
constexpr int XSTR = 32, OSTR = 32, KSTR = 32;
constexpr int F_O = F_X + 16 * XSTR;
constexpr int F_KV = F_O + 16 * OSTR;
constexpr int F_DONE = F_KV + 256 * KSTR;
constexpr int F_ROLE = F_DONE + 32;
__device__ __align__(1024) unsigned g_flags[F_ROLE + 64 * RSTR];

constexpr uint32_t SBASE = 1024;
constexpr int UNIT = 8192;
constexpr int NUNITS = 20;
constexpr int OFF_SLOT = NUNITS * UNIT;
constexpr int OFF_CS = OFF_SLOT + 4 * 16384;
constexpr int OFF_RS = OFF_CS + 1536;
constexpr int OFF_BAR = OFF_RS + 1024;
constexpr int OFF_EPOCH = OFF_BAR + 400, OFF_ROLE = OFF_BAR + 404;
constexpr int OFF_TS = OFF_BAR + 408;
constexpr int SMEM_BYTES = OFF_TS;
constexpr int B_FULL = 0, B_EMPTY = 8, B_PREP = 16, B_HALO = 18, B_REL = 22, B_AFREE = 25, B_TURN = 26, B_XRDY = 28,
              B_CS = 30, B_CSD = 31, B_GO = 32, B_RESF = 33, B_RESE = 34, B_PRE = 35, B_ROLE = 39, B_LOC = 40, B_HB = 48, B_KVS = 49;

__device__ __forceinline__ uint32_t smem_u32(const void* p) { return (uint32_t)__cvta_generic_to_shared(p); }
extern __shared__ __align__(1024) uint8_t smem_raw[];
__device__ __forceinline__ uint32_t sw(uint32_t a) {
  uint32_t r;
  asm volatile("add.u32 %0, %1, %2;" : "=r"(r) : "r"(a), "r"(smem_u32(smem_raw) - SBASE));
  return r;
}

__device__ __forceinline__ void mbar_init(uint32_t bar, uint32_t cnt) {
  asm volatile("mbarrier.init.shared::cta.b64 [%0], %1;" ::"r"(sw(bar)), "r"(cnt));
}
__device__ __forceinline__ void mbar_expect_tx(uint32_t bar, uint32_t bytes) {
  asm volatile("mbarrier.arrive.expect_tx.shared::cta.b64 _, [%0], %1;" ::"r"(sw(bar)), "r"(bytes) : "memory");
}
__device__ __forceinline__ void mbar_arrive(uint32_t bar) {
  asm volatile("mbarrier.arrive.shared::cta.b64 _, [%0];" ::"r"(sw(bar)) : "memory");
}
__device__ __forceinline__ void warp_arrive(uint32_t bar, bool cond = true) {
  asm volatile("{\n.reg .pred p;\nelect.sync _|p, 0xffffffff;\nsetp.ne.and.b32 p, %1, 0, p;\n"
               "@p mbarrier.arrive.shared::cta.b64 _, [%0];\n}\n" ::"r"(sw(bar)), "r"((uint32_t)cond) : "memory");
}
__device__ __forceinline__ void warp_arrive_cl(uint32_t bar, bool cond = true) {
  asm volatile("{\n.reg .pred p;\nelect.sync _|p, 0xffffffff;\nsetp.ne.and.b32 p, %1, 0, p;\n"
               "@p mbarrier.arrive.shared::cluster.b64 _, [%0];\n}\n" ::"r"(bar), "r"((uint32_t)cond) : "memory");
}
__device__ __forceinline__ bool mbar_try_wait(uint32_t bar, uint32_t parity) {
  uint32_t ok;
  asm volatile(
      "{\n.reg .pred p;\nmbarrier.try_wait.parity.shared::cta.b64 p, [%1], %2;\nselp.b32 %0, 1, 0, p;\n}\n"
      : "=r"(ok)
      : "r"(sw(bar)), "r"(parity)
      : "memory");
  return ok != 0;
}
__device__ __forceinline__ bool mbar_test(uint32_t bar, uint32_t parity) {
  uint32_t ok;
  asm volatile(
      "{\n.reg .pred p;\nmbarrier.test_wait.parity.shared::cta.b64 p, [%1], %2;\nselp.b32 %0, 1, 0, p;\n}\n"
      : "=r"(ok)
      : "r"(sw(bar)), "r"(parity)
      : "memory");
  return ok != 0;
}
__device__ __forceinline__ void mbar_wait(uint32_t bar, uint32_t parity) {
#pragma unroll 1
  for (uint32_t it = 0; it < (1u << 18); ++it) {
    if (mbar_try_wait(bar, parity)) return;
  }
}
__device__ __forceinline__ void mbar_wait_raw(uint32_t bar, uint32_t parity) {
#pragma unroll 1
  for (uint32_t it = 0; it < (1u << 18); ++it) {
    uint32_t ok;
    asm volatile(
        "{\n.reg .pred p;\nmbarrier.try_wait.parity.shared::cta.b64 p, [%1], %2;\nselp.b32 %0, 1, 0, p;\n}\n"
        : "=r"(ok)
        : "r"(bar), "r"(parity)
        : "memory");
    if (ok) return;
  }
}
__device__ __forceinline__ void spin(uint32_t cyc) {
  uint32_t c0, c;
  asm volatile("mov.u32 %0, %%clock;" : "=r"(c0));
  do { asm volatile("mov.u32 %0, %%clock;" : "=r"(c)); } while (c - c0 < cyc);
}
__device__ __forceinline__ void mbar_pace(uint32_t bar, uint32_t parity) {
#pragma unroll 1
  for (uint32_t it = 0; it < 24; ++it) {
    if (mbar_try_wait(bar, parity)) return;
  }
}
template <int NS>
__device__ __forceinline__ void mbar_wait_lazy(uint32_t bar, uint32_t parity) {
#pragma unroll 1
  for (uint32_t it = 0; it < (1u << 18); ++it) {
    if (mbar_try_wait(bar, parity)) return;
    __nanosleep(NS);
  }
}
__device__ __forceinline__ bool elect_one() {
  uint32_t ok;
  asm volatile("{\n.reg .pred p;\nelect.sync _|p, 0xffffffff;\nselp.b32 %0, 1, 0, p;\n}\n" : "=r"(ok));
  return ok != 0;
}
__device__ __forceinline__ void fence_barrier_init() { asm volatile("fence.mbarrier_init.release.cluster;" ::: "memory"); }
__device__ __forceinline__ void fence_proxy_async_smem() { asm volatile("fence.proxy.async.shared::cta;" ::: "memory"); }
__device__ __forceinline__ void fence_proxy_async_all() { asm volatile("fence.proxy.async.global;" ::: "memory"); }

__device__ __forceinline__ void tma_load_3d(uint32_t dst, const CUtensorMap* map, uint32_t bar, int c0, int c1, int c2) {
  asm volatile(
      "cp.async.bulk.tensor.3d.shared::cluster.global.mbarrier::complete_tx::bytes [%0], [%1, {%3, %4, %5}], [%2];" ::"r"(sw(dst)),
      "l"(map), "r"(sw(bar)), "r"(c0), "r"(c1), "r"(c2)
      : "memory");
}
__device__ __forceinline__ void tma_load_3d_mc(uint32_t dst, const CUtensorMap* map, uint32_t bar, int c0, int c1, int c2) {
  asm volatile(
      "cp.async.bulk.tensor.3d.shared::cluster.global.mbarrier::complete_tx::bytes.multicast::cluster [%0], [%1, {%3, %4, %5}], [%2], %6;" ::"r"(sw(dst)),
      "l"(map), "r"(sw(bar)), "r"(c0), "r"(c1), "r"(c2), "h"((unsigned short)3)
      : "memory");
}
__device__ __forceinline__ void bulk_load(uint32_t dst, const void* src, uint32_t bytes, uint32_t bar) {
  asm volatile("cp.async.bulk.shared::cluster.global.mbarrier::complete_tx::bytes [%0], [%1], %2, [%3];" ::"r"(sw(dst)),
               "l"(src), "r"(bytes), "r"(sw(bar))
               : "memory");
}
__device__ __forceinline__ void bulk_store(void* dst, uint32_t src, uint32_t bytes) {
  asm volatile("cp.async.bulk.global.shared::cta.bulk_group [%0], [%1], %2;" ::"l"(dst), "r"(sw(src)), "r"(bytes) : "memory");
}
__device__ __forceinline__ void tma_store_3d(const CUtensorMap* map, uint32_t src, int c0, int c1, int c2) {
  asm volatile("cp.async.bulk.tensor.3d.global.shared::cta.bulk_group [%0, {%2, %3, %4}], [%1];" ::"l"(map), "r"(sw(src)),
               "r"(c0), "r"(c1), "r"(c2)
               : "memory");
}
__device__ __forceinline__ void bulk_commit() { asm volatile("cp.async.bulk.commit_group;" ::: "memory"); }
__device__ __forceinline__ void bulk_wait0() { asm volatile("cp.async.bulk.wait_group 0;" ::: "memory"); }
__device__ __forceinline__ void named_bar_sync(int id, int nthreads) {
  asm volatile("bar.sync %0, %1;" ::"r"(id), "r"(nthreads) : "memory");
}
__device__ __forceinline__ void named_bar_arrive(int id, int nthreads) {
  asm volatile("bar.arrive %0, %1;" ::"r"(id), "r"(nthreads) : "memory");
}

__device__ __forceinline__ void wgmma_fence() { asm volatile("wgmma.fence.sync.aligned;\n" ::: "memory"); }
__device__ __forceinline__ void wgmma_commit() { asm volatile("wgmma.commit_group.sync.aligned;\n" ::: "memory"); }
template <int N>
__device__ __forceinline__ void wgmma_wait() {
  asm volatile("wgmma.wait_group.sync.aligned %0;\n" ::"n"(N) : "memory");
}
template <int R>
__device__ __forceinline__ void setmaxnreg_inc() { asm volatile("setmaxnreg.inc.sync.aligned.u32 %0;\n" ::"n"(R)); }
template <int R>
__device__ __forceinline__ void setmaxnreg_dec() { asm volatile("setmaxnreg.dec.sync.aligned.u32 %0;\n" ::"n"(R)); }
template <int N>
__device__ __forceinline__ void reg_fence(float* r) {
#pragma unroll
  for (int i = 0; i < N; i++) asm volatile("" : "+f"(r[i])::"memory");
}

template <int N>
__device__ __forceinline__ void reg_define(float* r) {
#pragma unroll
  for (int i = 0; i < N; i++) r[i] = 0.f;
}

__device__ __forceinline__ uint64_t desc_lo(uint32_t lo) {
  uint64_t d;
  asm("mov.b64 %0, {%1, %2};" : "=l"(d) : "r"(lo), "r"(0x40000040u));
  return d;
}
__device__ __forceinline__ uint64_t make_desc(uint32_t addr, uint32_t lbo_bytes) {
  return desc_lo((addr >> 4) + ((lbo_bytes >> 4) << 16));
}

__device__ __forceinline__ void wgmma_n192_ss_ta0_tb1(float* d, uint64_t descA, uint64_t descB, int scaleD) {
  asm volatile("{\n.reg .pred p;\nsetp.ne.b32 p, %98, 0;\n"
    "wgmma.mma_async.sync.aligned.m64n192k16.f32.bf16.bf16 {%0, %1, %2, %3, %4, %5, %6, %7, %8, %9, %10, %11, %12, %13, %14, %15, %16, %17, %18, %19, %20, %21, %22, %23, %24, %25, %26, %27, %28, %29, %30, %31, %32, %33, %34, %35, %36, %37, %38, %39, %40, %41, %42, %43, %44, %45, %46, %47, %48, %49, %50, %51, %52, %53, %54, %55, %56, %57, %58, %59, %60, %61, %62, %63, %64, %65, %66, %67, %68, %69, %70, %71, %72, %73, %74, %75, %76, %77, %78, %79, %80, %81, %82, %83, %84, %85, %86, %87, %88, %89, %90, %91, %92, %93, %94, %95}, %96, %97, p, 1, 1, 0, 1;\n}\n"
    : "+f"(d[0]), "+f"(d[1]), "+f"(d[2]), "+f"(d[3]), "+f"(d[4]), "+f"(d[5]), "+f"(d[6]), "+f"(d[7]), "+f"(d[8]), "+f"(d[9]), "+f"(d[10]), "+f"(d[11]), "+f"(d[12]), "+f"(d[13]), "+f"(d[14]), "+f"(d[15]), "+f"(d[16]), "+f"(d[17]), "+f"(d[18]), "+f"(d[19]), "+f"(d[20]), "+f"(d[21]), "+f"(d[22]), "+f"(d[23]), "+f"(d[24]), "+f"(d[25]), "+f"(d[26]), "+f"(d[27]), "+f"(d[28]), "+f"(d[29]), "+f"(d[30]), "+f"(d[31]), "+f"(d[32]), "+f"(d[33]), "+f"(d[34]), "+f"(d[35]), "+f"(d[36]), "+f"(d[37]), "+f"(d[38]), "+f"(d[39]), "+f"(d[40]), "+f"(d[41]), "+f"(d[42]), "+f"(d[43]), "+f"(d[44]), "+f"(d[45]), "+f"(d[46]), "+f"(d[47]), "+f"(d[48]), "+f"(d[49]), "+f"(d[50]), "+f"(d[51]), "+f"(d[52]), "+f"(d[53]), "+f"(d[54]), "+f"(d[55]), "+f"(d[56]), "+f"(d[57]), "+f"(d[58]), "+f"(d[59]), "+f"(d[60]), "+f"(d[61]), "+f"(d[62]), "+f"(d[63]), "+f"(d[64]), "+f"(d[65]), "+f"(d[66]), "+f"(d[67]), "+f"(d[68]), "+f"(d[69]), "+f"(d[70]), "+f"(d[71]), "+f"(d[72]), "+f"(d[73]), "+f"(d[74]), "+f"(d[75]), "+f"(d[76]), "+f"(d[77]), "+f"(d[78]), "+f"(d[79]), "+f"(d[80]), "+f"(d[81]), "+f"(d[82]), "+f"(d[83]), "+f"(d[84]), "+f"(d[85]), "+f"(d[86]), "+f"(d[87]), "+f"(d[88]), "+f"(d[89]), "+f"(d[90]), "+f"(d[91]), "+f"(d[92]), "+f"(d[93]), "+f"(d[94]), "+f"(d[95])
    : "l"(descA), "l"(descB), "r"(scaleD));
}

__device__ __forceinline__ void wgmma_n128_ss_ta0_tb1(float* d, uint64_t descA, uint64_t descB, int scaleD) {
  asm volatile("{\n.reg .pred p;\nsetp.ne.b32 p, %66, 0;\n"
    "wgmma.mma_async.sync.aligned.m64n128k16.f32.bf16.bf16 {%0, %1, %2, %3, %4, %5, %6, %7, %8, %9, %10, %11, %12, %13, %14, %15, %16, %17, %18, %19, %20, %21, %22, %23, %24, %25, %26, %27, %28, %29, %30, %31, %32, %33, %34, %35, %36, %37, %38, %39, %40, %41, %42, %43, %44, %45, %46, %47, %48, %49, %50, %51, %52, %53, %54, %55, %56, %57, %58, %59, %60, %61, %62, %63}, %64, %65, p, 1, 1, 0, 1;\n}\n"
    : "+f"(d[0]), "+f"(d[1]), "+f"(d[2]), "+f"(d[3]), "+f"(d[4]), "+f"(d[5]), "+f"(d[6]), "+f"(d[7]), "+f"(d[8]), "+f"(d[9]), "+f"(d[10]), "+f"(d[11]), "+f"(d[12]), "+f"(d[13]), "+f"(d[14]), "+f"(d[15]), "+f"(d[16]), "+f"(d[17]), "+f"(d[18]), "+f"(d[19]), "+f"(d[20]), "+f"(d[21]), "+f"(d[22]), "+f"(d[23]), "+f"(d[24]), "+f"(d[25]), "+f"(d[26]), "+f"(d[27]), "+f"(d[28]), "+f"(d[29]), "+f"(d[30]), "+f"(d[31]), "+f"(d[32]), "+f"(d[33]), "+f"(d[34]), "+f"(d[35]), "+f"(d[36]), "+f"(d[37]), "+f"(d[38]), "+f"(d[39]), "+f"(d[40]), "+f"(d[41]), "+f"(d[42]), "+f"(d[43]), "+f"(d[44]), "+f"(d[45]), "+f"(d[46]), "+f"(d[47]), "+f"(d[48]), "+f"(d[49]), "+f"(d[50]), "+f"(d[51]), "+f"(d[52]), "+f"(d[53]), "+f"(d[54]), "+f"(d[55]), "+f"(d[56]), "+f"(d[57]), "+f"(d[58]), "+f"(d[59]), "+f"(d[60]), "+f"(d[61]), "+f"(d[62]), "+f"(d[63])
    : "l"(descA), "l"(descB), "r"(scaleD));
}

__device__ __forceinline__ void wgmma_n192_ssz_ta0_tb1(float* d, uint64_t descA, uint64_t descB) {
  asm volatile("{\n.reg .pred p;\nsetp.ne.b32 p, 0, 0;\n"
    "wgmma.mma_async.sync.aligned.m64n192k16.f32.bf16.bf16 {%0, %1, %2, %3, %4, %5, %6, %7, %8, %9, %10, %11, %12, %13, %14, %15, %16, %17, %18, %19, %20, %21, %22, %23, %24, %25, %26, %27, %28, %29, %30, %31, %32, %33, %34, %35, %36, %37, %38, %39, %40, %41, %42, %43, %44, %45, %46, %47, %48, %49, %50, %51, %52, %53, %54, %55, %56, %57, %58, %59, %60, %61, %62, %63, %64, %65, %66, %67, %68, %69, %70, %71, %72, %73, %74, %75, %76, %77, %78, %79, %80, %81, %82, %83, %84, %85, %86, %87, %88, %89, %90, %91, %92, %93, %94, %95}, %96, %97, p, 1, 1, 0, 1;\n}\n"
    : "=f"(d[0]), "=f"(d[1]), "=f"(d[2]), "=f"(d[3]), "=f"(d[4]), "=f"(d[5]), "=f"(d[6]), "=f"(d[7]), "=f"(d[8]), "=f"(d[9]), "=f"(d[10]), "=f"(d[11]), "=f"(d[12]), "=f"(d[13]), "=f"(d[14]), "=f"(d[15]), "=f"(d[16]), "=f"(d[17]), "=f"(d[18]), "=f"(d[19]), "=f"(d[20]), "=f"(d[21]), "=f"(d[22]), "=f"(d[23]), "=f"(d[24]), "=f"(d[25]), "=f"(d[26]), "=f"(d[27]), "=f"(d[28]), "=f"(d[29]), "=f"(d[30]), "=f"(d[31]), "=f"(d[32]), "=f"(d[33]), "=f"(d[34]), "=f"(d[35]), "=f"(d[36]), "=f"(d[37]), "=f"(d[38]), "=f"(d[39]), "=f"(d[40]), "=f"(d[41]), "=f"(d[42]), "=f"(d[43]), "=f"(d[44]), "=f"(d[45]), "=f"(d[46]), "=f"(d[47]), "=f"(d[48]), "=f"(d[49]), "=f"(d[50]), "=f"(d[51]), "=f"(d[52]), "=f"(d[53]), "=f"(d[54]), "=f"(d[55]), "=f"(d[56]), "=f"(d[57]), "=f"(d[58]), "=f"(d[59]), "=f"(d[60]), "=f"(d[61]), "=f"(d[62]), "=f"(d[63]), "=f"(d[64]), "=f"(d[65]), "=f"(d[66]), "=f"(d[67]), "=f"(d[68]), "=f"(d[69]), "=f"(d[70]), "=f"(d[71]), "=f"(d[72]), "=f"(d[73]), "=f"(d[74]), "=f"(d[75]), "=f"(d[76]), "=f"(d[77]), "=f"(d[78]), "=f"(d[79]), "=f"(d[80]), "=f"(d[81]), "=f"(d[82]), "=f"(d[83]), "=f"(d[84]), "=f"(d[85]), "=f"(d[86]), "=f"(d[87]), "=f"(d[88]), "=f"(d[89]), "=f"(d[90]), "=f"(d[91]), "=f"(d[92]), "=f"(d[93]), "=f"(d[94]), "=f"(d[95])
    : "l"(descA), "l"(descB));
}

__device__ __forceinline__ void wgmma_n192_rs_tb1(float* d, uint32_t a0, uint32_t a1, uint64_t descB) {
  asm volatile("{\n.reg .pred p;\nsetp.eq.b32 p, 0, 0;\n"
    "wgmma.mma_async.sync.aligned.m64n192k16.f32.bf16.bf16 {%0, %1, %2, %3, %4, %5, %6, %7, %8, %9, %10, %11, %12, %13, %14, %15, %16, %17, %18, %19, %20, %21, %22, %23, %24, %25, %26, %27, %28, %29, %30, %31, %32, %33, %34, %35, %36, %37, %38, %39, %40, %41, %42, %43, %44, %45, %46, %47, %48, %49, %50, %51, %52, %53, %54, %55, %56, %57, %58, %59, %60, %61, %62, %63, %64, %65, %66, %67, %68, %69, %70, %71, %72, %73, %74, %75, %76, %77, %78, %79, %80, %81, %82, %83, %84, %85, %86, %87, %88, %89, %90, %91, %92, %93, %94, %95}, {%96, %97, %98, %98}, %99, p, 1, 1, 1;\n}\n"
    : "+f"(d[0]), "+f"(d[1]), "+f"(d[2]), "+f"(d[3]), "+f"(d[4]), "+f"(d[5]), "+f"(d[6]), "+f"(d[7]), "+f"(d[8]), "+f"(d[9]), "+f"(d[10]), "+f"(d[11]), "+f"(d[12]), "+f"(d[13]), "+f"(d[14]), "+f"(d[15]), "+f"(d[16]), "+f"(d[17]), "+f"(d[18]), "+f"(d[19]), "+f"(d[20]), "+f"(d[21]), "+f"(d[22]), "+f"(d[23]), "+f"(d[24]), "+f"(d[25]), "+f"(d[26]), "+f"(d[27]), "+f"(d[28]), "+f"(d[29]), "+f"(d[30]), "+f"(d[31]), "+f"(d[32]), "+f"(d[33]), "+f"(d[34]), "+f"(d[35]), "+f"(d[36]), "+f"(d[37]), "+f"(d[38]), "+f"(d[39]), "+f"(d[40]), "+f"(d[41]), "+f"(d[42]), "+f"(d[43]), "+f"(d[44]), "+f"(d[45]), "+f"(d[46]), "+f"(d[47]), "+f"(d[48]), "+f"(d[49]), "+f"(d[50]), "+f"(d[51]), "+f"(d[52]), "+f"(d[53]), "+f"(d[54]), "+f"(d[55]), "+f"(d[56]), "+f"(d[57]), "+f"(d[58]), "+f"(d[59]), "+f"(d[60]), "+f"(d[61]), "+f"(d[62]), "+f"(d[63]), "+f"(d[64]), "+f"(d[65]), "+f"(d[66]), "+f"(d[67]), "+f"(d[68]), "+f"(d[69]), "+f"(d[70]), "+f"(d[71]), "+f"(d[72]), "+f"(d[73]), "+f"(d[74]), "+f"(d[75]), "+f"(d[76]), "+f"(d[77]), "+f"(d[78]), "+f"(d[79]), "+f"(d[80]), "+f"(d[81]), "+f"(d[82]), "+f"(d[83]), "+f"(d[84]), "+f"(d[85]), "+f"(d[86]), "+f"(d[87]), "+f"(d[88]), "+f"(d[89]), "+f"(d[90]), "+f"(d[91]), "+f"(d[92]), "+f"(d[93]), "+f"(d[94]), "+f"(d[95])
    : "r"(a0), "r"(a1), "r"(0u), "l"(descB));
}

__device__ __forceinline__ void wgmma_n128_ssz_ta0_tb1(float* d, uint64_t descA, uint64_t descB) {
  asm volatile("{\n.reg .pred p;\nsetp.ne.b32 p, 0, 0;\n"
    "wgmma.mma_async.sync.aligned.m64n128k16.f32.bf16.bf16 {%0, %1, %2, %3, %4, %5, %6, %7, %8, %9, %10, %11, %12, %13, %14, %15, %16, %17, %18, %19, %20, %21, %22, %23, %24, %25, %26, %27, %28, %29, %30, %31, %32, %33, %34, %35, %36, %37, %38, %39, %40, %41, %42, %43, %44, %45, %46, %47, %48, %49, %50, %51, %52, %53, %54, %55, %56, %57, %58, %59, %60, %61, %62, %63}, %64, %65, p, 1, 1, 0, 1;\n}\n"
    : "=f"(d[0]), "=f"(d[1]), "=f"(d[2]), "=f"(d[3]), "=f"(d[4]), "=f"(d[5]), "=f"(d[6]), "=f"(d[7]), "=f"(d[8]), "=f"(d[9]), "=f"(d[10]), "=f"(d[11]), "=f"(d[12]), "=f"(d[13]), "=f"(d[14]), "=f"(d[15]), "=f"(d[16]), "=f"(d[17]), "=f"(d[18]), "=f"(d[19]), "=f"(d[20]), "=f"(d[21]), "=f"(d[22]), "=f"(d[23]), "=f"(d[24]), "=f"(d[25]), "=f"(d[26]), "=f"(d[27]), "=f"(d[28]), "=f"(d[29]), "=f"(d[30]), "=f"(d[31]), "=f"(d[32]), "=f"(d[33]), "=f"(d[34]), "=f"(d[35]), "=f"(d[36]), "=f"(d[37]), "=f"(d[38]), "=f"(d[39]), "=f"(d[40]), "=f"(d[41]), "=f"(d[42]), "=f"(d[43]), "=f"(d[44]), "=f"(d[45]), "=f"(d[46]), "=f"(d[47]), "=f"(d[48]), "=f"(d[49]), "=f"(d[50]), "=f"(d[51]), "=f"(d[52]), "=f"(d[53]), "=f"(d[54]), "=f"(d[55]), "=f"(d[56]), "=f"(d[57]), "=f"(d[58]), "=f"(d[59]), "=f"(d[60]), "=f"(d[61]), "=f"(d[62]), "=f"(d[63])
    : "l"(descA), "l"(descB));
}

__device__ __forceinline__ void wgmma_n64_ss_ta0_tb0(float* d, uint64_t descA, uint64_t descB, int scaleD) {
  asm volatile("{\n.reg .pred p;\nsetp.ne.b32 p, %34, 0;\n"
    "wgmma.mma_async.sync.aligned.m64n64k16.f32.bf16.bf16 {%0, %1, %2, %3, %4, %5, %6, %7, %8, %9, %10, %11, %12, %13, %14, %15, %16, %17, %18, %19, %20, %21, %22, %23, %24, %25, %26, %27, %28, %29, %30, %31}, %32, %33, p, 1, 1, 0, 0;\n}\n"
    : "+f"(d[0]), "+f"(d[1]), "+f"(d[2]), "+f"(d[3]), "+f"(d[4]), "+f"(d[5]), "+f"(d[6]), "+f"(d[7]), "+f"(d[8]), "+f"(d[9]), "+f"(d[10]), "+f"(d[11]), "+f"(d[12]), "+f"(d[13]), "+f"(d[14]), "+f"(d[15]), "+f"(d[16]), "+f"(d[17]), "+f"(d[18]), "+f"(d[19]), "+f"(d[20]), "+f"(d[21]), "+f"(d[22]), "+f"(d[23]), "+f"(d[24]), "+f"(d[25]), "+f"(d[26]), "+f"(d[27]), "+f"(d[28]), "+f"(d[29]), "+f"(d[30]), "+f"(d[31])
    : "l"(descA), "l"(descB), "r"(scaleD));
}

__device__ __forceinline__ void wgmma_n64_ssz_ta0_tb0(float* d, uint64_t descA, uint64_t descB) {
  asm volatile("{\n.reg .pred p;\nsetp.ne.b32 p, 0, 0;\n"
    "wgmma.mma_async.sync.aligned.m64n64k16.f32.bf16.bf16 {%0, %1, %2, %3, %4, %5, %6, %7, %8, %9, %10, %11, %12, %13, %14, %15, %16, %17, %18, %19, %20, %21, %22, %23, %24, %25, %26, %27, %28, %29, %30, %31}, %32, %33, p, 1, 1, 0, 0;\n}\n"
    : "=f"(d[0]), "=f"(d[1]), "=f"(d[2]), "=f"(d[3]), "=f"(d[4]), "=f"(d[5]), "=f"(d[6]), "=f"(d[7]), "=f"(d[8]), "=f"(d[9]), "=f"(d[10]), "=f"(d[11]), "=f"(d[12]), "=f"(d[13]), "=f"(d[14]), "=f"(d[15]), "=f"(d[16]), "=f"(d[17]), "=f"(d[18]), "=f"(d[19]), "=f"(d[20]), "=f"(d[21]), "=f"(d[22]), "=f"(d[23]), "=f"(d[24]), "=f"(d[25]), "=f"(d[26]), "=f"(d[27]), "=f"(d[28]), "=f"(d[29]), "=f"(d[30]), "=f"(d[31])
    : "l"(descA), "l"(descB));
}

__device__ __forceinline__ void wgmma_n80_ss_ta0_tb0(float* d, uint64_t descA, uint64_t descB, int scaleD) {
  asm volatile("{\n.reg .pred p;\nsetp.ne.b32 p, %42, 0;\n"
    "wgmma.mma_async.sync.aligned.m64n80k16.f32.bf16.bf16 {%0, %1, %2, %3, %4, %5, %6, %7, %8, %9, %10, %11, %12, %13, %14, %15, %16, %17, %18, %19, %20, %21, %22, %23, %24, %25, %26, %27, %28, %29, %30, %31, %32, %33, %34, %35, %36, %37, %38, %39}, %40, %41, p, 1, 1, 0, 0;\n}\n"
    : "+f"(d[0]), "+f"(d[1]), "+f"(d[2]), "+f"(d[3]), "+f"(d[4]), "+f"(d[5]), "+f"(d[6]), "+f"(d[7]), "+f"(d[8]), "+f"(d[9]), "+f"(d[10]), "+f"(d[11]), "+f"(d[12]), "+f"(d[13]), "+f"(d[14]), "+f"(d[15]), "+f"(d[16]), "+f"(d[17]), "+f"(d[18]), "+f"(d[19]), "+f"(d[20]), "+f"(d[21]), "+f"(d[22]), "+f"(d[23]), "+f"(d[24]), "+f"(d[25]), "+f"(d[26]), "+f"(d[27]), "+f"(d[28]), "+f"(d[29]), "+f"(d[30]), "+f"(d[31]), "+f"(d[32]), "+f"(d[33]), "+f"(d[34]), "+f"(d[35]), "+f"(d[36]), "+f"(d[37]), "+f"(d[38]), "+f"(d[39])
    : "l"(descA), "l"(descB), "r"(scaleD));
}

__device__ __forceinline__ void wgmma_n32_rs_tb1(float* d, const uint32_t* a, uint64_t descB, int scaleD) {
  asm volatile("{\n.reg .pred p;\nsetp.ne.b32 p, %21, 0;\n"
    "wgmma.mma_async.sync.aligned.m64n32k16.f32.bf16.bf16 {%0, %1, %2, %3, %4, %5, %6, %7, %8, %9, %10, %11, %12, %13, %14, %15}, {%16, %17, %18, %19}, %20, p, 1, 1, 1;\n}\n"
    : "+f"(d[0]), "+f"(d[1]), "+f"(d[2]), "+f"(d[3]), "+f"(d[4]), "+f"(d[5]), "+f"(d[6]), "+f"(d[7]), "+f"(d[8]), "+f"(d[9]), "+f"(d[10]), "+f"(d[11]), "+f"(d[12]), "+f"(d[13]), "+f"(d[14]), "+f"(d[15])
    : "r"(a[0]), "r"(a[1]), "r"(a[2]), "r"(a[3]), "l"(descB), "r"(scaleD));
}

__device__ __forceinline__ uint32_t pack_bf16x2(float lo, float hi) {
  uint32_t r;
  asm("cvt.rn.bf16x2.f32 %0, %1, %2;" : "=r"(r) : "f"(hi), "f"(lo));
  return r;
}
__device__ __forceinline__ float bf_lo(uint32_t p) { return __uint_as_float(p << 16); }
__device__ __forceinline__ float bf_hi(uint32_t p) { return __uint_as_float(p & 0xffff0000u); }
__device__ __forceinline__ float bf16_round(float v) { return __bfloat162float(__float2bfloat16_rn(v)); }
__device__ __forceinline__ float ex2_approx(float x) {
  float r;
  asm("ex2.approx.ftz.f32 %0, %1;" : "=f"(r) : "f"(x));
  return r;
}
__device__ __forceinline__ float rcp_fast(float x) {
  float r;
  asm("rcp.approx.ftz.f32 %0, %1;" : "=f"(r) : "f"(x));
  return r;
}
__device__ __forceinline__ void ldmatrix_x4(uint32_t (&r)[4], uint32_t addr) {
  asm volatile("ldmatrix.sync.aligned.m8n8.x4.shared.b16 {%0,%1,%2,%3}, [%4];"
               : "=r"(r[0]), "=r"(r[1]), "=r"(r[2]), "=r"(r[3])
               : "r"(sw(addr))
               : "memory");
}
__device__ __forceinline__ void stmatrix_x4(uint32_t addr, uint32_t r0, uint32_t r1, uint32_t r2, uint32_t r3) {
  asm volatile("stmatrix.sync.aligned.m8n8.x4.shared.b16 [%0], {%1,%2,%3,%4};" ::"r"(sw(addr)), "r"(r0), "r"(r1), "r"(r2),
               "r"(r3));
}
__device__ __forceinline__ uint32_t add_bf16x2(uint32_t a, uint32_t b) {
  uint32_t r;
  asm("add.rn.bf16x2 %0, %1, %2;" : "=r"(r) : "r"(a), "r"(b));
  return r;
}
__device__ __forceinline__ uint4 lds128(uint32_t addr) {
  uint4 v;
  asm volatile("ld.shared.v4.b32 {%0,%1,%2,%3}, [%4];" : "=r"(v.x), "=r"(v.y), "=r"(v.z), "=r"(v.w) : "r"(sw(addr)) : "memory");
  return v;
}
__device__ __forceinline__ uint32_t lds32(uint32_t addr) {
  uint32_t v;
  asm volatile("ld.shared.b32 %0, [%1];" : "=r"(v) : "r"(sw(addr)) : "memory");
  return v;
}
__device__ __forceinline__ void sts32(uint32_t addr, uint32_t v) {
  asm volatile("st.shared.b32 [%0], %1;" ::"r"(sw(addr)), "r"(v) : "memory");
}

__device__ __forceinline__ unsigned ld_acquire_u32(const unsigned* p) {
  unsigned v;
  asm volatile("ld.acquire.gpu.global.u32 %0, [%1];" : "=r"(v) : "l"(p) : "memory");
  return v;
}
__device__ __forceinline__ unsigned atom_add(unsigned* p, unsigned v, bool on) {
  unsigned r = 0;
  asm volatile("{\n.reg .pred p;\nsetp.ne.u32 p, %3, 0;\n@p atom.relaxed.gpu.global.add.u32 %0, [%1], %2;\n}\n"
               : "+r"(r) : "l"(p), "r"(v), "r"((uint32_t)on) : "memory");
  return r;
}
__device__ __forceinline__ void announce(unsigned* p) {
  asm volatile("red.release.gpu.global.add.u32 [%0], 1;" ::"l"(p) : "memory");
}
__device__ __forceinline__ void poison(uint8_t* p, int n, uint32_t gap) {
#pragma unroll 1
  for (int i = 0; i < n; i++, p += 2048) {
    asm volatile("st.global.v4.b32 [%0], {%1,%1,%1,%1};" ::"l"(p), "r"(0xffffffffu) : "memory");
    __nanosleep(gap);
  }
}
__device__ __forceinline__ void wait_ge2(const unsigned* p, unsigned t0, unsigned t1) {
#pragma unroll 1
  for (uint32_t it = 0; it < (1u << 17); ++it) {
    unsigned long long v;
    asm volatile("ld.acquire.gpu.global.u64 %0, [%1];" : "=l"(v) : "l"(p) : "memory");
    if ((int)((unsigned)v - t0) >= 0 && (int)((unsigned)(v >> 32) - t1) >= 0) return;
  }
}

#define RELNS 100
#define PCM 0x33
#define HBD 700
#define POI1 100
#define WU 3
constexpr int WUNR = WU;
#define PCS 4096
#define PCN 30
template <bool SLOW>
__device__ __forceinline__ void wait_mask(const unsigned* f, int cnt, unsigned target, uint32_t need, uint32_t& seen, int lane) {
  if ((seen & need) == need) return;
  const unsigned* fp = f + (lane & (cnt - 1));
#pragma unroll 1
  for (uint32_t it = 0; it < (1u << 17); ++it) {
    seen = __ballot_sync(0xffffffffu, (int)(ld_acquire_u32(fp) - target) >= 0);
    if ((seen & need) == need) break;
    if (SLOW) __nanosleep(400);
  }
  fence_proxy_async_all();
}
__device__ __forceinline__ void wait_lanes(const unsigned* fp, unsigned target, uint32_t need, uint32_t& seen) {
  if ((seen & need) == need) return;
#pragma unroll 1
  for (uint32_t it = 0; it < (1u << 17); ++it) {
    seen |= __ballot_sync(0xffffffffu, (int)(ld_acquire_u32(fp) - target) >= 0);
    if ((seen & need) == need) break;
  }
  fence_proxy_async_all();
}
__device__ __forceinline__ float4 ld_rec(const float4* p) {
  float4 v;
  asm volatile("ld.relaxed.gpu.global.v4.f32 {%0,%1,%2,%3}, [%4];" : "=f"(v.x), "=f"(v.y), "=f"(v.z), "=f"(v.w) : "l"(p) : "memory");
  return v;
}
__device__ __forceinline__ void st_rec(float4* p, float a, float b, float c, unsigned tag) {
  asm volatile("st.relaxed.gpu.global.v4.f32 [%0], {%1,%2,%3,%4};" ::"l"(p), "f"(a), "f"(b), "f"(c), "f"(__uint_as_float(tag)) : "memory");
}
template <int N>
__device__ __forceinline__ float4 sum_recs(const float4* p, int stride, unsigned tag) {
  float4 s;
#pragma unroll 1
  for (uint32_t it = 0; it < (1u << 17); ++it) {
    float4 v[N];
#pragma unroll
    for (int t = 0; t < N; t++) v[t] = ld_rec(p + t * stride);
    bool ok = true;
    s = make_float4(0.f, 0.f, 0.f, 0.f);
#pragma unroll
    for (int t = 0; t < N; t++) {
      ok &= __float_as_uint(v[t].w) == tag;
      s.x += v[t].x;
      s.y += v[t].y;
      s.z += v[t].z;
    }
    if (ok) break;
    __nanosleep(200);
  }
  return s;
}

__device__ __forceinline__ int fresh_tid() {
  int t;
  asm volatile("mov.u32 %0, %%tid.x;" : "=r"(t));
  return t;
}
#define PHASE_IDS                                  \
  const int tid_ = fresh_tid();                    \
  const int lane = tid_ & 31, wwarp = __shfl_sync(0xffffffffu, (tid_ >> 5) & 3, 0), tid = tid_ & 127; \
  const int g = lane >> 2, c = lane & 3;           \
  (void)tid; (void)g; (void)c; (void)wwarp;

#define STAMPW(cond, i) do { } while (0)
#define STAMP(cond, i) do { } while (0)
#define KSPN true
#define KSAON false
#define STA(i) do { } while (0)
#define GTL(i) do { } while (0)
#define GTLX(c, i) do { } while (0)
#define TGET(v) do { } while (0)
#define TPUT(c, i, v) do { } while (0)

constexpr float SM_C = 0.17677669529663687f * 1.4426950408889634f;

constexpr uint32_t OA_TILE = SBASE + OFF_SLOT + 16384;

__device__ __forceinline__ void sched_fence(uint32_t never) {
  asm volatile("{\n.reg .pred p;\nsetp.ne.u32 p, %0, 0;\n@p exit;\n}\n" ::"r"(never) : "memory");
}

template <int K0, int K1>
__device__ __forceinline__ void attn_exp(float (&s)[32]) {
#pragma unroll
  for (int k = K0; k < K1; k++) s[k] = ex2_approx(s[k]);
}
#define ASPL 16
#define ASPD 6
#define ASPE 6
#define ASPF 6
template <int MODE, bool NEXT>
__device__ __forceinline__ void attn_unit(float (&s)[32], float (&sn)[32], float (&o)[16], float (&l)[2], bool valid,
                                          uint32_t vdesc, uint32_t qdesc, uint32_t kdesc, uint32_t tri, int w,
                                          uint32_t hbar, uint32_t hpar, uint32_t rel, uint32_t zero, bool stampon = false) {
  float x[9][2];
  constexpr int ASPM = MODE == 1 ? ASPD : (NEXT ? ASPE : ASPF);
  if (MODE == 0) {
    attn_exp<0, ASPL>(s);
  } else {
#pragma unroll
    for (int e = 0; e < 2; e++) {
#pragma unroll
      for (int j = 0; j < 4; j++) x[j][e] = MODE == 1 ? s[4 * j + 2 + e] : s[16 + 4 * j + e];
      x[4][e] = MODE == 1 ? s[e] : s[30 + e];
      x[5][e] = MODE == 1 ? s[18 + e] : s[12 + e];
#pragma unroll
      for (int u = 1; u < 4; u++)
        x[5 + u][e] = MODE == 1 ? (w >= u ? s[4 * u + e] : s[4 * (8 - u) + 2 + e]) : (w >= u ? s[4 * (7 - u) + 2 + e] : s[4 * (u - 1) + e]);
    }
#pragma unroll
    for (int k = 0; k < 2 * ASPM; k++) x[k >> 1][k & 1] = ex2_approx(x[k >> 1][k & 1]);
  }
  sched_fence(zero);
  if (hbar) mbar_wait(hbar, hpar);
  wgmma_wait<0>();
  if (rel) mbar_arrive(rel);
  if (NEXT) {
    wgmma_fence();
    wgmma_n64_ssz_ta0_tb0(sn, desc_lo(qdesc), desc_lo(kdesc));
    wgmma_n64_ss_ta0_tb0(sn, desc_lo(qdesc + 2), desc_lo(kdesc + 2), 1);
    wgmma_commit();
    sched_fence(zero);
  }
  uint32_t p[16];
  if (MODE == 0) {
    attn_exp<ASPL, 32>(s);
#pragma unroll
    for (int k = 0; k < 16; k++) p[k] = pack_bf16x2(s[2 * k], s[2 * k + 1]);
  } else {
#pragma unroll
    for (int k = 2 * ASPM; k < 18; k++) x[k >> 1][k & 1] = ex2_approx(x[k >> 1][k & 1]);
    const uint32_t tm = MODE == 1 ? tri : ~tri;
#pragma unroll
    for (int j = 0; j < 4; j++) {
      p[MODE == 1 ? 2 * j + 1 : 8 + 2 * j] = pack_bf16x2(x[j][0], x[j][1]);
      p[MODE == 1 ? 8 + 2 * j : 2 * j + 1] = 0u;
    }
    p[MODE == 1 ? 0 : 15] = pack_bf16x2(x[4][0], x[4][1]) & (w == 0 ? tm : 0xffffffffu);
    p[MODE == 1 ? 9 : 6] = pack_bf16x2(x[5][0], x[5][1]) & (w == 3 ? tm : 0xffffffffu);
#pragma unroll
    for (int u = 1; u < 4; u++) {
      const uint32_t q = pack_bf16x2(x[5 + u][0], x[5 + u][1]);
      p[MODE == 1 ? 2 * u : 2 * (7 - u) + 1] = q & (w > u ? 0xffffffffu : (w == u ? tm : 0u));
      p[MODE == 1 ? 2 * (8 - u) + 1 : 2 * (u - 1)] = q & (w < u - 1 ? 0xffffffffu : (w == u - 1 ? tm : 0u));
    }
  }
  wgmma_fence();
#pragma unroll
  for (int k = 0; k < 4; k++) wgmma_n32_rs_tb1(o, p + 4 * k, desc_lo(vdesc + k * 128), 1);
  wgmma_commit();
#pragma unroll
  for (int r = 0; r < 2; r++) {
    float t = 0.f;
#pragma unroll
    for (int hf = 0; hf < 2; hf++) {
      if (MODE != 0 && r == MODE - 1 && hf == 2 - MODE) continue;
      const uint32_t* q = p + 8 * hf + r;
      const uint32_t v = add_bf16x2(add_bf16x2(q[0], q[2]), add_bf16x2(q[4], q[6]));
      t = (MODE != 0 && r == MODE - 1) || hf == 0 ? bf_lo(v) + bf_hi(v) : t + (bf_lo(v) + bf_hi(v));
    }
    if (valid) l[r] += t;
  }
  if (NEXT) {
    wgmma_wait<1>();
    reg_fence<32>(sn);
  }
}

__device__ __forceinline__ void attn_a_slow(const uint8_t* __restrict__ kvimg, int L, int gb, int hp,
                                         int hh, int wwarp, int lane, int t0, int t1) {
  constexpr uint32_t sq = SBASE + OFF_SLOT + 3 * 16384;
  const unsigned ep = (*(volatile unsigned*)(g_flags + F_DONE)) / NCTA;
  wait_ge2(g_flags + F_KV + (gb * 16 + hp) * KSTR, 2u * ep + (L >> 1) + 1u, 2u * ep + (L >> 1) + 1u);
#pragma unroll 1
  for (int t = t0; t < t1; t++) {
    const int row = (t >> 4) * 64 + ((t & 8) ? 7 - wwarp : wwarp) * 8 + (t & 7);
    const int qpos = gb * 128 + row;
    const uint32_t qaddr = sq + ((t >> 4) * 64 + wwarp * 16 + (t & 15)) * 128;
    float mx = -INFINITY, sum = 0.f, acc = 0.f;
#pragma unroll 1
    for (int pass = 0; pass < 2; pass++) {
#pragma unroll 1
      for (int j = 0; j < 8; j++) {
        const int kp = qpos - (lane + 32 * j);
        const uint8_t* kr = kvimg + ((size_t)((kp >> 7) * 16 + hp) * 2 + ((kp >> 6) & 1)) * 16384 + (kp & 63) * 128;
        float d = -INFINITY;
        if (kp >= 0) {
          d = 0.f;
#pragma unroll 1
          for (int q = 0; q < 4; q++) {
            const uint4 kv = __ldcg(reinterpret_cast<const uint4*>(kr + (((hh * 4 + q) ^ (kp & 7)) << 4)));
            const uint4 qv = lds128(qaddr + (((hh * 4 + q) ^ (row & 7)) << 4));
            const uint32_t kw[4] = {kv.x, kv.y, kv.z, kv.w}, qw[4] = {qv.x, qv.y, qv.z, qv.w};
#pragma unroll
            for (int e = 0; e < 4; e++) d = fmaf(bf_lo(kw[e]), bf_lo(qw[e]), fmaf(bf_hi(kw[e]), bf_hi(qw[e]), d));
          }
        }
        if (pass == 0) {
          mx = fmaxf(mx, d);
        } else {
          const float ev = ex2_approx(d - mx);
          sum += ev;
          const float pv = bf16_round(ev);
#pragma unroll 1
          for (int kk = 0; kk < 32; kk++) {
            const float pk = __shfl_sync(0xffffffffu, pv, kk);
            const int k2 = qpos - (kk + 32 * j);
            if (k2 >= 0) {
              const uint8_t* vr = kvimg + ((size_t)((k2 >> 7) * 16 + hp) * 2 + ((k2 >> 6) & 1)) * 16384 + 8192 + (k2 & 63) * 128;
              const unsigned short vv =
                  __ldcg(reinterpret_cast<const unsigned short*>(vr + (((hh * 4 + (lane >> 3)) ^ (k2 & 7)) << 4) + (lane & 7) * 2));
              acc = fmaf(pk, __uint_as_float((uint32_t)vv << 16), acc);
            }
          }
        }
      }
      if (pass == 0) {
#pragma unroll
        for (int o = 16; o > 0; o >>= 1) mx = fmaxf(mx, __shfl_xor_sync(0xffffffffu, mx, o));
      }
    }
#pragma unroll
    for (int o = 16; o > 0; o >>= 1) sum += __shfl_xor_sync(0xffffffffu, sum, o);
    acc *= rcp_fast(sum);
    const float hi = __shfl_down_sync(0xffffffffu, acc, 1);
    __syncwarp();
    if ((lane & 1) == 0)
      sts32(OA_TILE + row * 128 + (((hh * 4 + (lane >> 3)) ^ (row & 7)) << 4) + (lane & 7) * 2, pack_bf16x2(acc, hi));
    __syncwarp();
  }
}

__device__ __forceinline__ void store_o(const float (&o)[16], const float (&inv)[2], uint32_t rowaddr, int hh, int lane) {
  const int mat = lane >> 3, r7 = lane & 7;
#pragma unroll
  for (int jp = 0; jp < 2; jp++)
    stmatrix_x4(rowaddr + (((hh * 4 + 2 * jp + (mat >> 1)) ^ r7) << 4),
                pack_bf16x2(o[8 * jp] * inv[0], o[8 * jp + 1] * inv[0]),
                pack_bf16x2(o[8 * jp + 2] * inv[1], o[8 * jp + 3] * inv[1]),
                pack_bf16x2(o[8 * jp + 4] * inv[0], o[8 * jp + 5] * inv[0]),
                pack_bf16x2(o[8 * jp + 6] * inv[1], o[8 * jp + 7] * inv[1]));
}

__device__ __forceinline__ void attention_a(int HH, int L, int gb, int hp, uint32_t par0, uint32_t parA, int wwarp, int lane,
                                            uint32_t zero) {
  constexpr uint32_t bars = SBASE + OFF_BAR;
  const uint32_t dslot = ((SBASE + OFF_SLOT) >> 4) + 0x10000u + HH * 4;
  const uint32_t dq = dslot + 3 * 1024;
  float sa[32], sb[32], o[2][16], l[2][2];
  auto dch = [&](int n) { return dslot + 1024u * (n % 3 == 0 ? 1 : (n % 3 == 1 ? 0 : 2)); };
  wgmma_fence();
  wgmma_n64_ssz_ta0_tb0(sa, desc_lo(dq + 512), desc_lo(dch(0)));
  wgmma_n64_ss_ta0_tb0(sa, desc_lo(dq + 512 + 2), desc_lo(dch(0) + 2), 1);
  wgmma_commit();
#pragma unroll
  for (int h = 0; h < 2; h++) {
#pragma unroll
    for (int i = 0; i < 16; i++) o[h][i] = 0.f;
    l[h][0] = l[h][1] = 0.f;
  }
  const int dg = (lane >> 2) - 2 * (lane & 3);
  const uint32_t tri = (dg >= 0 ? 0xffffu : 0u) | (dg >= 1 ? 0xffff0000u : 0u);
  const int nmax = 2 * gb + 1;
  wgmma_wait<0>();
  reg_fence<32>(sa);
#define STON false
#define ATT_STEP(i, MODE)                                                                                            \
  attn_unit<MODE, true>(sa, sb, o[1], l[1], i <= nmax, dch(i) + 512, dq, dch(i + 1), tri, wwarp,                     \
                        i >= 1 ? bars + 8u * (B_HALO + i - 1) : 0u, i == 1 ? par0 : parA, 0u, zero, STON); \
  attn_unit<MODE, (i < 4)>(sb, sa, o[0], l[0], i + 1 <= nmax, dch(i + 1) + 512, dq + 512, dch(i + 1), tri, wwarp, 0u, \
                           0u, i < 3 && lane == 0 ? bars + 8u * (B_REL + i) : 0u, zero);
  ATT_STEP(0, 1)
  ATT_STEP(1, 0)
  ATT_STEP(2, 0)
  ATT_STEP(3, 0)
  ATT_STEP(4, 2)
#undef ATT_STEP
  const uint32_t ra = OA_TILE + (((lane & 8) ? 7 - wwarp : wwarp) * 8 + (lane & 7)) * 128;
  bool redo[2];
#pragma unroll
  for (int h = 1; h >= 0; h--) {
    float inv[2];
    bool bad = false;
#pragma unroll
    for (int r = 0; r < 2; r++) {
      float v = l[h][r];
      v += __shfl_xor_sync(0xffffffffu, v, 1);
      v += __shfl_xor_sync(0xffffffffu, v, 2);
      bad |= !(v <= 1.152921504606846976e18f && v >= 8.673617379884035e-19f);
      inv[r] = rcp_fast(v);
    }
    if (h == 0) wgmma_wait<0>();
    reg_fence<16>(o[h]);
    store_o(o[h], inv, ra + h * 8192, HH, lane);
    redo[h] = __any_sync(0xffffffffu, bad);
    if (h == 1 && !redo[1]) {
      fence_proxy_async_smem();
      named_bar_arrive(9, 288);
    }
  }
  if (HH == 0) GTL(45);
  if (redo[0] || redo[1]) {
    attn_a_slow(g_kvA[L >> 1][0][0][0], L, gb, hp, HH, wwarp, lane, redo[0] ? 0 : 16, redo[1] ? 32 : 16);
    fence_proxy_async_smem();
    if (redo[1]) named_bar_arrive(9, 288);
  }
}

constexpr uint32_t KB_ROW0 = SBASE + OFF_SLOT + 2048, VB_ROW0 = SBASE + OFF_SLOT + 24576 + 2048;

__device__ __forceinline__ void attnB_soft(const float (&s)[40], int wwarp, int D, bool edge, bool odd,
                                           uint32_t (&p)[5][4], float (&sum)[2]) {
  float z[2][3];
#define GATHER_(W)                                                                                  \
  _Pragma("unroll") for (int r = 0; r < 2; r++) _Pragma("unroll") for (int t = 0; t < 3; t++)       \
      z[r][t] = odd ? s[4 * (2 * W + r + t) + 2 * r + 1] : s[4 * (2 * W + r + t) + 2 * r];
  if (wwarp < 2) {
    if (wwarp == 0) { GATHER_(0) } else { GATHER_(1) }
  } else {
    if (wwarp == 2) { GATHER_(2) } else { GATHER_(3) }
  }
#undef GATHER_
  float y[2];
  y[0] = D >= 2 ? z[0][0] : z[0][2];
  y[1] = D >= 2 ? z[1][0] : z[1][2];
  if (edge) {
    z[0][1] = -INFINITY;
    if (D >= 2) y[0] = y[1] = -INFINITY;
  }
  float m0 = fmaxf(z[0][1], y[0]), m1 = fmaxf(z[1][1], y[1]);
  m0 = fmaxf(m0, __shfl_xor_sync(0xffffffffu, m0, 1));
  m1 = fmaxf(m1, __shfl_xor_sync(0xffffffffu, m1, 1));
  m0 = fmaxf(m0, __shfl_xor_sync(0xffffffffu, m0, 2));
  m1 = fmaxf(m1, __shfl_xor_sync(0xffffffffu, m1, 2));
  const float e00 = ex2_approx(z[0][1] - m0), e01 = ex2_approx(y[0] - m0);
  const float e10 = ex2_approx(z[1][1] - m1), e11 = ex2_approx(y[1] - m1);
  sum[0] = e00 + e01;
  sum[1] = e10 + e11;
  const int sh = odd ? 16 : 0;
  const uint32_t a0 = pack_bf16x2(e00, 0.f) << sh, a1 = pack_bf16x2(e10, 0.f) << sh;
  const uint32_t b0 = pack_bf16x2(e01, 0.f) << sh, b1 = pack_bf16x2(e11, 0.f) << sh;
  const int kb = wwarp + (D >= 2 ? 0 : 1);
#pragma unroll
  for (int k = 0; k < 5; k++) {
    p[k][0] = k == kb ? b0 : 0u;
    p[k][1] = k == wwarp + 1 ? a1 : 0u;
    p[k][2] = k == wwarp ? a0 : 0u;
    p[k][3] = k == kb ? b1 : 0u;
#pragma unroll
    for (int q = 0; q < 4; q++) asm volatile("" : "+r"(p[k][q]));
  }
}

__device__ __forceinline__ void attnB_s(float (&s)[40], int HH, int h) {
  constexpr uint32_t sq = SBASE + OFF_SLOT + 3 * 16384;
#pragma unroll
  for (int ks = 0; ks < 2; ks++)
    wgmma_n80_ss_ta0_tb0(s, make_desc(sq + h * 8192 + HH * 64 + ks * 32, 16),
                         make_desc(KB_ROW0 + h * 8192 - 2048 + HH * 64 + ks * 32, 16), ks);
}
__device__ __forceinline__ void attnB_pv(float (&o)[16], const uint32_t (&p)[5][4], int HH, int h) {
#pragma unroll
  for (int k = 0; k < 5; k++)
    wgmma_n32_rs_tb1(o, p[k], make_desc(VB_ROW0 + h * 8192 - 2048 + k * 2048 + HH * 64, 16), k);
}

__device__ __forceinline__ void attention_b(int HH, int gb, uint32_t par0, int wwarp, int lane, bool ston) {
  constexpr uint32_t bars = SBASE + OFF_BAR, sq = SBASE + OFF_SLOT + 3 * 16384;
  float s[40];
  reg_define<40>(s);
  wgmma_fence();
  attnB_s(s, HH, 1);
  wgmma_commit();
  const int g = lane >> 2;
  const bool odd = g & 1;
  const int D = 2 * (lane & 3) + (g & 1) - g;
  const uint32_t ra = sq + (wwarp * 16 + ((lane >> 3) & 1) * 8 + (lane & 7)) * 128;
  wgmma_wait<0>();
  reg_fence<40>(s);
  STAMP(ston, 21);
#pragma unroll 1
  for (int h = 1; h >= 0; h--) {
    float o[16], inv[2];
    uint32_t p[5][4];
    reg_define<16>(o);
    attnB_soft(s, wwarp, D, h == 0 && gb == 0 && wwarp == 0, odd, p, inv);
    STAMP(ston, 25 - 3 * h);
    wgmma_fence();
    attnB_pv(o, p, HH, h);
    wgmma_commit();
#pragma unroll
    for (int r = 0; r < 2; r++) {
      inv[r] += __shfl_xor_sync(0xffffffffu, inv[r], 1);
      inv[r] += __shfl_xor_sync(0xffffffffu, inv[r], 2);
      inv[r] = rcp_fast(inv[r]);
    }
    if (h == 1) {
      mbar_wait(bars + 8u * B_HALO, par0);
      STAMP(ston, 23);
      wgmma_fence();
      attnB_s(s, HH, 0);
      wgmma_commit();
      wgmma_wait<1>();
    } else {
      wgmma_wait<0>();
    }
    reg_fence<16>(o);
    store_o(o, inv, ra + h * 8192, HH, lane);
    if (h == 1) {
      fence_proxy_async_smem();
      named_bar_arrive(9, 288);
    }
    wgmma_wait<0>();
    reg_fence<40>(s);
    STAMP(ston, 26 - 2 * h);
  }
}

#define TRICKLE 300
#define TRSP 10
#define TRICK2 150
#define PDL 600
#define CSN 1000
#define HAND 0x3F
#define OH 0xFF
#define CSI 1
#define PCA 1
#define PCB 3
#define PXB 4
#define EPW1 4
#define EPW0 12
#define PRENS 500
#define LOCE 1
#define QTURN 2
constexpr int NPT = 240 + 8;
struct Params {
  CUtensorMap xq[2], xr[2], xw[2], o, wqkv[2], wo[2];
  const __nv_bfloat16* in_x;
  const __nv_bfloat16* wqkv_p1;
  const __nv_bfloat16* wo_p[2];
  uint32_t zero;
  uint2 wtab[4][17];
  uint2 ptab[NPT + 1];
};
static_assert(sizeof(Params) <= 4096, "");

__device__ __forceinline__ void colsum_part(const CUtensorMap* wmap, int ty, int qr, int hp) {
  constexpr uint32_t bars = SBASE + OFF_BAR, slots = SBASE + OFF_SLOT;
  PHASE_IDS
  const unsigned ep1 = (*(volatile unsigned*)(g_flags + F_DONE)) / NCTA + 1u;
  if (wwarp == 0 && elect_one()) {
    mbar_expect_tx(bars + 8u * B_CS, 6 * UNIT);
#pragma unroll 1
    for (int j = 0; j < 2; j++) {
      if (ty == 0) mbar_pace(bars + 8u * (B_EMPTY + PCA + PCB * j), 0);
      else __nanosleep(CSN);
      tma_load_3d(slots + j * 3 * UNIT, wmap, bars + 8u * B_CS, hp * 64, qr * 128 + j * 64, 0);
    }
  }
  __syncwarp();
  if (ty) {
#pragma unroll 1
    for (int j = 0; j < 4; j++) poison(g_kvB[j >> 1][(j & 1) * 8 + qr][hp] + tid * 16, 2, POI1);
  }
  mbar_wait(bars + 8u * B_CS, ty);
  STAMP(KSQ == 0 && ty == 0, 49);
  const uint32_t src = slots + (tid >> 3) * 128 + (((tid & 7) ^ ((tid >> 3) & 7)) << 4);
#pragma unroll 1
  for (int p = 0; p < 3; p++) {
    float s[8];
#pragma unroll
    for (int e = 0; e < 8; e++) s[e] = 0.f;
#pragma unroll
    for (int j = 0; j < 8; j++) {
      const uint4 v = lds128(src + p * UNIT + (j >> 2) * 3 * UNIT + (j & 3) * 2048);
      const uint32_t x[4] = {v.x, v.y, v.z, v.w};
#pragma unroll
      for (int e = 0; e < 4; e++) {
        s[2 * e] += bf_lo(x[e]);
        s[2 * e + 1] += bf_hi(x[e]);
      }
    }
#pragma unroll
    for (int st = 0; st < 2; st++) {
      const bool up = (lane >> (st + 3)) & 1;
#pragma unroll
      for (int e = 0; e < (4 >> st); e++) {
        const float keep = up ? s[e + (4 >> st)] : s[e], give = up ? s[e] : s[e + (4 >> st)];
        s[e] = keep + __shfl_xor_sync(0xffffffffu, give, 8 << st);
      }
    }
    const uint32_t dst = slots + 6 * UNIT + ((wwarp * 3 + p) * 64 + (lane & 7) * 8 + ((lane >> 3) & 1) * 4 + (lane >> 4) * 2) * 4;
    sts32(dst, __float_as_uint(s[0]));
    sts32(dst + 4, __float_as_uint(s[1]));
  }
  named_bar_sync(6, 128);
  float r[3] = {0.f, 0.f, 0.f};
#pragma unroll
  for (int e = 0; e < 12; e++) r[e % 3] += __uint_as_float(lds32(slots + 6 * UNIT + (e * 64 + (tid & 63)) * 4));
  __syncwarp();
  warp_arrive(bars + 8u * (ty ? B_CSD : B_AFREE), ty || wwarp < 2);
  if (tid < 64) {
    if (ty) {
      asm volatile("fence.release.gpu;" ::: "memory");
      fence_proxy_async_all();
    }
    st_rec(&g_cs[ty][hp][qr][tid], r[0], r[1], r[2], ep1);
    STAMP(KSQ == 0 && ty == 0, 50);
  }
}

__device__ __forceinline__ void cs_put(int blk, int ty, int col, float v) {
  const uint32_t hi = pack_bf16x2(v, 0.f), lo = pack_bf16x2(v - bf_lo(hi), 0.f);
  const uint32_t a = SBASE + OFF_CS + blk * 512 + ty * 256 + col * 2;
  asm volatile("st.shared.b16 [%0], %1;" ::"r"(sw(a ^ (((a >> 7) & 7) << 4))), "h"((unsigned short)hi) : "memory");
  asm volatile("st.shared.b16 [%0], %1;" ::"r"(sw((a + 128) ^ ((((a >> 7) + 1) & 7) << 4))), "h"((unsigned short)lo) : "memory");
}

__device__ __forceinline__ uint32_t ln_params(float s1, float s2) {
  const float mean = s1 * (1.0f / DM);
  const float var = fmaxf(fmaf(-mean, mean, s2 * (1.0f / DM)), 0.f);
  float sd;
  asm("sqrt.approx.f32 %0, %1;" : "=f"(sd) : "f"(bf16_round(bf16_round(var) + 1e-5f)));
  return pack_bf16x2(mean, sd);
}

#define SPLITS 0x085866688ull
__host__ __device__ __forceinline__ int q_split(int inst) { return (int)((SPLITS >> (4 * inst)) & 15ull); }
__device__ __forceinline__ int q_first(int inst) { return inst == 0 ? 0 : 32 * inst - 16; }
__device__ __forceinline__ int w_first(int inst) { return 32 * inst + 16 + 2 * q_split(inst + 1); }
#define PREMASK 0x2Cu
#define WBUF 0x0400103000201000ull
static_assert((PREMASK & 0xC0u) == 0 && (SPLITS & 0xF0) == 0x80, "");
__host__ __device__ __forceinline__ bool w_pre(int inst) { return (PREMASK >> inst) & 1u; }
struct WPlan {
  int v[6][21];
  int own[28], len;
};
__host__ __device__ constexpr WPlan w_plan(int mode) {
  WPlan p{};
  for (int u = 0; u < 28; u++) p.own[u] = u < 20 ? u / 5 - 4 : -16;
  if (mode == 2) {
    const WPlan q = w_plan(0);
    for (int u = 0; u < 20; u++) p.own[u] = q.own[(u + q.len) % 20] - 16;
  }
  int pos = 0, mx = -16;
  for (int kt = 0; kt < 21; kt++) {
    const int code = mode == 1 && kt < 16 ? (int)(WBUF >> (4 * kt)) & 15 : 0, st = kt > 16 ? kt - 1 : kt;
    const int na = kt == 16 ? 0 : (kt < 16 ? 1 : 2), nb = kt < 17 ? 2 : 3;
    const bool hole = code == 0 || (code & 8), swap = kt < 16 && hole && pos % 10 == 8;
    const int ua = (pos + (swap ? 2 : 0)) % 20, ub = code ? NUNITS - 2 + 2 * (code & 7) : (pos + (swap ? 0 : na)) % 20;
    int ra = st - 8, rb = kt == 16 ? -16 : st - 8;
    for (int i = 0; i < na; i++) ra = p.own[ua + i] > ra ? p.own[ua + i] : ra;
    for (int i = 0; i < nb; i++) rb = p.own[ub + i] > rb ? p.own[ub + i] : rb;
    p.v[0][kt] = ua;
    p.v[1][kt] = ub;
    p.v[2][kt] = st - ra;
    p.v[3][kt] = st - rb;
    p.v[4][kt] = rb > mx;
    p.v[5][kt] = p.own[ub] == -16;
    mx = rb > mx ? rb : mx;
    if (kt < 17) {
      for (int i = 0; i < na; i++) p.own[ua + i] = kt;
      for (int i = 0; i < nb; i++) p.own[ub + i] = kt < 16 ? kt : 15;
    }
    pos += na + (hole ? nb : 0);
    if (kt == 16) p.len = pos;
  }
  return p;
}
__host__ __device__ constexpr uint64_t w_tab(int f, int mode, int k0, int dk, int n, int bits) {
  const WPlan p = w_plan(mode);
  uint64_t r = 0;
  for (int j = 0; j < n; j++) r |= (uint64_t)p.v[f][k0 + j * dk] << (bits * j);
  return r;
}
__host__ __device__ constexpr uint32_t q_backs(bool act, int rank, bool pre) {
  return act ? 0x44444400u | (uint32_t)w_tab(2, pre, 17 + rank, 2, 2, 4) : 0x44440000u | (uint32_t)w_tab(3, pre, 17, 1, 4, 4);
}
__host__ __device__ constexpr uint32_t w_early() {
  const WPlan p = w_plan(1);
  uint32_t r = 0;
  for (int kt = 0; kt < 16; kt++)
    if (p.v[5][kt]) r |= (uint32_t)kt << (2 * (p.v[1][kt] - NUNITS));
  return r;
}
__host__ __device__ constexpr uint32_t w_emask() {
  const WPlan p = w_plan(1);
  uint32_t r = 0;
  for (int kt = 0; kt < 16; kt++) r |= (uint32_t)p.v[5][kt] << kt;
  return r;
}
static_assert((w_emask() & 3) == 0 && (w_early() & 15) < ((w_early() >> 4) & 15) && ((w_early() >> 4) & 15) < ((w_early() >> 8) & 15) &&
              ((w_early() >> 8) & 15) < (w_early() >> 12), "");
static_assert(w_plan(1).len % 10 == 0 && w_tab(2, 0, 0, 2, 8, 4) == 0x77776654u && w_tab(2, 2, 1, 2, 8, 4) == 0x77777666u &&
              q_backs(false, 0, false) == 0x44444445u && q_backs(true, 0, false) == 0x44444456u, "");
constexpr bool PRE_FLIP = w_plan(1).len % 20 != 0;
__device__ __forceinline__ int w_flips(int n) { return PRE_FLIP ? n : __popc(~PREMASK & ((1u << n) - 1u)); }
__host__ __device__ __forceinline__ uint32_t unit_off(int u, uint32_t dl) { return u * UNIT + (u < 10 ? dl : (u < 20 ? 0u - dl : 0u)); }

__global__ void __cluster_dims__(2, 1, 1) __launch_bounds__(512, 1) fused_kernel(const __grid_constant__ Params P) {
  constexpr uint32_t base = SBASE, bars = base + OFF_BAR, slots = base + OFF_SLOT;
  const int warp = __shfl_sync(0xffffffffu, threadIdx.x >> 5, 0), lane = threadIdx.x & 31;
  const int b = blockIdx.x, rank = b & 1;
  if (smem_u32(smem_raw) != base + (rank << 24)) __trap();
  int role = 0;
  {
    unsigned smid;
    asm volatile("mov.u32 %0, %smid;" : "=r"(smid));
    const int tc = smid >> 1;
    role = (tc < 32 ? (tc & 7) * 8 + (tc >> 3) : (tc < 62 ? ((tc - 32) % 7 + 1) * 8 + 4 + (tc - 32) / 7 : tc - 58)) & 63;
  }
  if (warp == 12) {
    if (elect_one()) {
#pragma unroll
      for (int s = 0; s < 8; s++) {
        mbar_init(bars + 8u * (B_FULL + s), 1);
        mbar_init(bars + 8u * (B_EMPTY + s), LOCE ? 2 : 4);
        mbar_init(bars + 8u * (B_LOC + s), 2);
      }
      mbar_init(bars + 8u * B_GO, 1);
      mbar_init(bars + 8u * B_ROLE, 1);
      mbar_expect_tx(bars + 8u * B_ROLE, 4);
      fence_barrier_init();
    }
    __syncwarp();
  }
  asm volatile("barrier.cluster.arrive.relaxed.aligned;" ::: "memory");
  if (threadIdx.x == 0) {
    mbar_init(bars + 8u * B_PREP, 1);
    mbar_init(bars + 8u * (B_PREP + 1), 1);
    for (int s = 0; s < 4; s++) mbar_init(bars + 8u * (B_HALO + s), 1);
    for (int s = 0; s < 3; s++) mbar_init(bars + 8u * (B_REL + s), 8);
    mbar_init(bars + 8u * B_AFREE, 2);
    mbar_init(bars + 8u * B_TURN, 4);
    mbar_init(bars + 8u * (B_TURN + 1), 4);
    mbar_init(bars + 8u * B_CS, 1);
    mbar_init(bars + 8u * B_HB, 1);
    mbar_init(bars + 8u * B_KVS, 1);
    for (int s = 0; s < 4; s++) mbar_init(bars + 8u * (B_PRE + s), 1);
    mbar_init(bars + 8u * B_RESF, 1);
    mbar_init(bars + 8u * B_RESE, 4);
    mbar_init(bars + 8u * B_CSD, 4);
    mbar_init(bars + 8u * B_XRDY, 1);
    mbar_init(bars + 8u * (B_XRDY + 1), 1);
    fence_barrier_init();
  }
  if (warp == 15 && rank == 0) {
    const unsigned ep = *(volatile unsigned*)(g_flags + F_DONE);
    int r = role;
#pragma unroll 1
    for (int it = 0; it < 64; it++, r = (r + 1) & 63) {
      if (__all_sync(0xffffffffu, (ep - atom_add(g_flags + F_ROLE + r * RSTR, NCTA, lane == 0) < NCTA) | (lane != 0))) break;
      atom_add(g_flags + F_ROLE + r * RSTR, 0u - NCTA, lane == 0);
    }
    asm volatile("barrier.cluster.wait.aligned;" ::: "memory");
    asm volatile("{\n.reg .pred p;\nsetp.lt.u32 p, %3, 2;\n"
                 "@p st.async.weak.shared::cluster.mbarrier::complete_tx::bytes.b32 [%0], %1, [%2];\n}\n" ::"r"(base + OFF_ROLE + (lane << 24)),
                 "r"(r), "r"(bars + 8u * B_ROLE + (lane << 24)), "r"(lane)
                 : "memory");
  } else if (warp != 12) {
    asm volatile("barrier.cluster.wait.aligned;" ::: "memory");
  }
#define ROLE_IDS                                                                                   \
  const int qr = role & 7, hp = (role >> 3) * 2 + rank, rt = role & 15, ct = ((role >> 3) & 6) + rank; \
  (void)qr; (void)hp; (void)rt; (void)ct;
#define ROLE_GET                                                          \
  named_bar_sync(0, 512);                                                 \
  role = __shfl_sync(0xffffffffu, (int)lds32(base + OFF_ROLE), 0);

  if (warp < 12) {
    const bool asst = warp >= 8;
    ROLE_GET
    ROLE_IDS
    uint32_t tpar = 0;
    const uint32_t ebar = LOCE && (warp & 2) ? bars + 8u * B_LOC + (rank << 24) : bars + 8u * B_EMPTY + ((warp & 1) << 24);
    GTL(0);
#pragma unroll 1
    for (int inst = (warp < 4 ? 0 : -1) + (int)P.zero; inst < 8; inst += asst ? 1 : 2) {
      const int L = inst >> 1, ch = inst & 1, gb = ch * 8 + qr;
      if (inst >= 0) {
      if (asst) {
        setmaxnreg_dec<24>();
        named_bar_sync(4, 256);
        setmaxnreg_inc<128>();
      } else {
      setmaxnreg_inc<224>();
      {
        float acc[2][96];
        const int ksp = q_split(inst);
        int n = q_first(inst);
        uint32_t dlt = inst > 0 && (w_flips(inst - 1) & 1) ? 10u * (UNIT >> 4) : 0u;
        if (inst == 1 || (inst > 1 && q_split(inst - 1) != 8)) {
          mbar_wait_lazy<100>(bars + 8u * (B_TURN + ch), tpar);
          tpar ^= 1u;
        }
        if (L == 3) GTL(37);
        mbar_wait(bars + 8u * (B_FULL + (n & 7)), (n >> 3) & 1);
        GTL(1 + L * 8);
        {
          const uint32_t da = (base >> 4) + 0x10000u + dlt;
          const uint64_t db = desc_lo(da - 0x10000u + ((UNIT >> 4) << 16) + 2 * (UNIT >> 4));
          wgmma_fence();
          wgmma_n192_ssz_ta0_tb1(acc[0], desc_lo(da), db);
          wgmma_commit();
          wgmma_n192_ssz_ta0_tb1(acc[1], desc_lo(da + (UNIT >> 4)), db);
          wgmma_commit();
        }
#pragma unroll 1
        for (int k2 = 0; k2 < 7; k2++) {
          const bool brk = k2 + 1 == ksp;
#pragma unroll
          for (int ks = 0; ks < 2; ks++, n++) {
            STAMP(inst == KSQ, k2 * 2 + ks);
            const uint32_t da = ((base + ks * 5 * UNIT) >> 4) + 0x10000u + dlt;
            const uint32_t dbb = da - 0x10000u + ((UNIT >> 4) << 16) + 2 * (UNIT >> 4);
#pragma unroll
            for (int k16 = 0; k16 < 4; k16++) {
              if (ks == 0 && k16 == 0 && k2 == 0) continue;
              const uint64_t db = desc_lo(dbb + k16 * 128);
              wgmma_fence();
              wgmma_n192_ss_ta0_tb1(acc[0], desc_lo(da + k16 * 2), db, 1);
              wgmma_commit();
              wgmma_wait<1>();
              if (k16 == 0) warp_arrive_cl(ebar + 8u * ((n - 1) & 7), ks != 0 || k2 != ksp);
              wgmma_fence();
              wgmma_n192_ss_ta0_tb1(acc[1], desc_lo(da + (UNIT >> 4) + k16 * 2), db, 1);
              wgmma_commit();
              bool ok = true;
              if (k16 == 2) ok = mbar_test(bars + 8u * (B_FULL + ((n + 1) & 7)), ((n + 1) >> 3) & 1) || (ks == 1 && brk);
              if (k16 == QTURN && ks == 1) warp_arrive(bars + 8u * (B_TURN + (ch ^ 1)), brk);
              if (ks == 0 || k16 < 3) wgmma_wait<1>();
              if (k16 == 2 && !ok) mbar_wait(bars + 8u * (B_FULL + ((n + 1) & 7)), ((n + 1) >> 3) & 1);
            }
          }
          if (brk) {
            wgmma_wait<0>();
            warp_arrive_cl(ebar + 8u * ((n - 1) & 7));
            n += 16;
            mbar_wait_lazy<100>(bars + 8u * (B_TURN + ch), tpar);
            tpar ^= 1u;
            STAMP(inst == KSQ, 17);
            mbar_wait(bars + 8u * (B_FULL + (n & 7)), (n >> 3) & 1);
          }
          if (!brk || (!PRE_FLIP && w_pre(inst - 1))) dlt ^= 10u * (UNIT >> 4);
        }
        auto tail_group = [&](int u) {
          const uint32_t da = ((base + (u & 1) * 5 * UNIT) >> 4) + 0x10000u + dlt;
          const uint32_t dbb = da - 0x10000u + ((UNIT >> 4) << 16) + 2 * (UNIT >> 4);
          if (u < 3) wgmma_fence();
#pragma unroll
          for (int k16 = 0; k16 < 4; k16++)
            wgmma_n192_ss_ta0_tb1(acc[u < 2], desc_lo(da + (u < 2 ? UNIT >> 4 : 0) + k16 * 2), desc_lo(dbb + k16 * 128), 1);
          wgmma_commit();
        };
        STAMP(inst == KSQ, 14);
        tail_group(0);
        wgmma_wait<1>();
        STAMP(inst == KSQ && KSPN, 42);
        warp_arrive_cl(ebar + 8u * ((n - 1) & 7), ksp != 7);
        PHASE_IDS
        mbar_wait(bars + 8u * (B_PREP + ch), L & 1);
        STAMP(inst == KSQ && KSPN, 43);
        uint32_t rs[4];
#pragma unroll
        for (int i = 0; i < 4; i++)
          rs[i] = lds32(base + OFF_RS + (ch * 128 + (i >> 1) * 64 + wwarp * 16 + g + 8 * (i & 1)) * 4);
        auto fold = [&](int h) {
          uint32_t a[2];
#pragma unroll
          for (int r = 0; r < 2; r++) a[r] = c == (L & 1) ? __byte_perm(rs[2 * h + r], 0, 0x1010) ^ 0x80008000u : 0u;
          uint64_t d;
          asm("mov.b64 %0, {%1, %2};" : "=l"(d) : "r"(((base + OFF_CS) >> 4) + ((512 >> 4) << 16)), "r"(0x40000000u));
          wgmma_fence();
          wgmma_n192_rs_tb1(acc[h], a[0], a[1], d);
        };
        fold(1);
        wgmma_commit();
        mbar_wait(bars + 8u * (B_FULL + ((n + 1) & 7)), ((n + 1) >> 3) & 1);
        STAMP(inst == KSQ && KSPN, 44);
        tail_group(1);
        tail_group(2);
        STAMP(inst == KSQ && KSPN, 45);
        const bool ppre = ksp == 7 && w_pre(inst - 1);
        const uint32_t fbar = bars + 8u * (ppre ? (LOCE ? B_LOC : B_EMPTY) + ((n - 1) & 7) : (inst == CSI + 1 ? B_CSD : B_AFREE));
        const uint32_t fpar = ppre ? ((n - 1) >> 3) & 1 : (inst == CSI + 1 ? 0 : ch);
        const bool afree = mbar_test(fbar, fpar);
        float rinv[2][2];
#pragma unroll
        for (int i = 0; i < 4; i++) rinv[i >> 1][i & 1] = rcp_fast(bf_hi(rs[i]));
        const int mat = lane >> 3;
        const uint32_t soff = (wwarp * 16 + (mat & 1) * 8 + (lane & 7)) * 128;
        const uint32_t kdst = ((L & 1) ? KB_ROW0 : slots) + soff, vdst = ((L & 1) ? VB_ROW0 : slots + 8192) + soff;
        const uint32_t hs = (L & 1) ? 8192 : 16384;
        const int rg = 2 * wwarp + (mat & 1);
        const uint32_t qdst = slots + 3 * 16384 + ((L & 1) ? soff : ((rg < 4 ? 2 * rg : 15 - 2 * rg) * 8 + (lane & 7)) * 128);
        wgmma_wait<2>();
        STAMP(inst == KSQ && KSPN, 46);
        fold(0);
        tail_group(3);
        STAMP(inst == KSQ && KSPN, 47);
        warp_arrive(bars + 8u * (B_TURN + (ch ^ 1)));
        if (!afree) {
          wgmma_wait<1>();
          warp_arrive_cl(ebar + 8u * (n & 7));
          wgmma_wait<0>();
          warp_arrive_cl(ebar + 8u * ((n + 1) & 7));
          mbar_wait(fbar, fpar);
        }
        wgmma_wait<2>();
        reg_fence<96>(acc[1]);
        STAMP(inst == KSQ, 15);
#pragma unroll
        for (int t = 0; t < 24; t++) {
          const int h = t < 12 ? 1 : 0, p = (t % 12 / 4 + 1) % 3, jp = t & 3;
          if (t == EPW1) {
            wgmma_wait<1>();
            warp_arrive_cl(ebar + 8u * (n & 7), afree);
          }
          if (t == EPW0) {
            wgmma_wait<0>();
            reg_fence<96>(acc[0]);
            warp_arrive_cl(ebar + 8u * ((n + 1) & 7), afree);
            STAMP(inst == KSQ, 16);
            GTL(2 + L * 8);
          }
          if (t % 12 == 8) {
            rinv[h][0] *= SM_C;
            rinv[h][1] *= SM_C;
          }
          const uint32_t swz = ((2 * jp + (mat >> 1)) ^ (lane & 7)) << 4;
          const float* a = &acc[h][32 * p + 8 * jp];
          const uint32_t dst = p == 0 ? qdst + h * 8192 : (p == 1 ? kdst : vdst) + h * hs;
          stmatrix_x4(dst + swz, pack_bf16x2(a[0] * rinv[h][0], a[1] * rinv[h][0]), pack_bf16x2(a[2] * rinv[h][1], a[3] * rinv[h][1]),
                      pack_bf16x2(a[4] * rinv[h][0], a[5] * rinv[h][0]), pack_bf16x2(a[6] * rinv[h][1], a[7] * rinv[h][1]));
          if (t % 12 == 7) {
            fence_proxy_async_smem();
            if (t == 7) named_bar_arrive(3, (L & 1) ? 192 : 160);
            else if ((L & 1) == 0) named_bar_arrive(7, 160);
            if (t > EPW0) sched_fence(P.zero);
          }
        }
      }
      fence_proxy_async_smem();
      setmaxnreg_dec<128>();
      named_bar_sync(4, 256);
      }
      GTL(3 + L * 8);
      {
        PHASE_IDS
        if ((L & 1) == 0) attention_a(asst, L, gb, hp, inst & 1, ch, (tid_ >> 5) & 3, lane, P.zero);
        else attention_b(asst, gb, inst & 1, wwarp, lane, KSAON);
        GTL(4 + L * 8);
        fence_proxy_async_smem();
      }
      if (!asst) {
      {
        const CUtensorMap* omap = &P.o;
        uint32_t osrc = sw((L & 1) ? slots + 3 * 16384 : OA_TILE);
        int oc1 = gb * 128, oc2 = hp;
        asm volatile("" : "+l"(omap), "+r"(osrc), "+r"(oc1), "+r"(oc2));
        named_bar_sync(5, 256);
        STAMP(KSAON, 27);
        if ((warp & 3) == 0 && elect_one()) {
          asm volatile("cp.async.bulk.tensor.3d.global.shared::cta.bulk_group [%0, {%2, %3, %4}], [%1];" ::"l"(omap), "r"(osrc),
                       "r"(0), "r"(oc1), "r"(oc2) : "memory");
          bulk_commit();
          bulk_wait0();
          STAMP(KSAON, 31);
          mbar_arrive(bars + 8u * B_AFREE);
        }
        __syncwarp();
        if ((warp & 3) == 0 && !((OH >> inst) & 1)) {
          mbar_wait(bars + 8u * B_AFREE, ch ^ 1);
          if (elect_one()) announce(g_flags + F_O + gb * OSTR + hp);
          __syncwarp();
        }
      }
      GTL(5 + L * 8);

      {
        float acc[64];
        const int n0 = w_first(inst);
        const bool pre = w_pre(inst);
        const uint32_t dl = ((w_flips(inst) + q_split(inst + 1)) & 1) * 10u * UNIT;
        const uint2* tab = P.wtab[2 * pre + (dl != 0)];
        const uint32_t ppar = __popc(PREMASK & ((1u << inst) - 1u)) & 1;
        uint32_t pbar = bars + 8u * B_PRE;
        const uint32_t flg = (pre ? w_emask() >> 1 : 0u) | (inst >= 6 || q_split(inst + 1) != 8 ? 1u << 30 : 0u);
        uint2 e = tab[0];
        mbar_wait_lazy<100>(bars + 8u * (B_TURN + ch), tpar);
        tpar ^= 1u;
        mbar_wait(bars + 8u * (B_FULL + (n0 & 7)), (n0 >> 3) & 1);
        GTL(6 + L * 8);
        auto wstep = [&](auto first_, int kt) {
          constexpr bool first = decltype(first_)::value;
          const int n = n0 + kt;
          STAMP(inst == KSW, 20 + kt);
          wgmma_fence();
          if (first) wgmma_n128_ssz_ta0_tb1(acc, desc_lo(e.x), desc_lo(e.y));
#pragma unroll
          for (int k16 = first ? 1 : 0; k16 < 4; k16++) wgmma_n128_ss_ta0_tb1(acc, desc_lo(e.x + 2 * k16), desc_lo(e.y + 128 * k16), 1);
          wgmma_commit();
          if (!first) warp_arrive(bars + 8u * (B_TURN + (ch ^ 1)), (flg >> kt) & 0x8000u);
          e = tab[kt + 1];
          const uint32_t nb = bars + 8u * (kt == 15 ? B_RESF : B_FULL + ((n + 1) & 7)), np = kt == 15 ? ch : ((n + 1) >> 3) & 1;
          const bool ok = mbar_test(nb, np);
          if (!first) {
            wgmma_wait<1>();
            warp_arrive_cl(ebar + 8u * ((n - 1) & 7));
            if ((flg >> kt) & 1u) {
              mbar_wait(pbar, ppar);
              pbar += 8u;
            }
          }
          if (!ok) mbar_wait(nb, np);
        };
        wstep(std::true_type(), 0);
#pragma unroll WUNR
        for (int kt = 1; kt < 16; kt++) wstep(std::false_type(), kt);
        PHASE_IDS
        const uint32_t xb = e.x;
        const int grow = ch * 1024 + rt * 64;
        const int mat = lane >> 3;
        const uint32_t xrow = xb + (wwarp * 16 + (mat & 1) * 8 + (lane & 7)) * 128;
        uint32_t xv[8][4];
#pragma unroll
        for (int jp = 0; jp < 8; jp++)
          ldmatrix_x4(xv[jp], xrow + (jp >> 2) * UNIT + (((2 * (jp & 3) + (mat >> 1)) ^ (lane & 7)) << 4));
        const CUtensorMap* xmap = &P.xw[L == 3];
        uint32_t xsrc[2] = {sw(xb + wwarp * 2048), sw(xb + UNIT + wwarp * 2048)};
        int xc1 = grow + wwarp * 16, xc2[2] = {ct * 2, ct * 2 + 1};
        asm volatile("" : "+l"(xmap), "+r"(xsrc[0]), "+r"(xsrc[1]), "+r"(xc1), "+r"(xc2[0]), "+r"(xc2[1]));
        wgmma_wait<0>();
        reg_fence<64>(acc);
        warp_arrive_cl(ebar + 8u * ((n0 + 15) & 7));
        STAMP(inst == KSW, 36);
        GTL(7 + L * 8);
#pragma unroll
        for (int jp = 0; jp < 8; jp++) {
#pragma unroll
          for (int q = 0; q < 4; q++) xv[jp][q] = add_bf16x2(xv[jp][q], pack_bf16x2(acc[8 * jp + 2 * q], acc[8 * jp + 2 * q + 1]));
          stmatrix_x4(xrow + (jp >> 2) * UNIT + (((2 * (jp & 3) + (mat >> 1)) ^ (lane & 7)) << 4), xv[jp][0], xv[jp][1],
                      xv[jp][2], xv[jp][3]);
          if ((jp & 3) == 3) {
            fence_proxy_async_smem();
            __syncwarp();
            asm volatile(
                "{\n.reg .pred p;\nelect.sync _|p, 0xffffffff;\n"
                "@p cp.async.bulk.tensor.3d.global.shared::cta.bulk_group [%0, {%2, %3, %4}], [%1];\n"
                "@p cp.async.bulk.commit_group;\n}\n" ::"l"(xmap), "r"(xsrc[jp >> 2]), "r"(0), "r"(xc1), "r"(xc2[jp >> 2])
                : "memory");
          }
        }
        STAMP(inst == KSW, 37);
        if (elect_one()) {
          bulk_wait0();
          mbar_arrive(bars + 8u * B_RESE);
        }
        __syncwarp();
        if (wwarp == 0 && L < 3 && !((HAND >> inst) & 1)) {
          mbar_wait(bars + 8u * B_RESE, ch);
          STAMP(inst == KSW, 38);
          if (elect_one()) announce(g_flags + F_X + (ch * 8 + (rt >> 1)) * XSTR + ct);
          __syncwarp();
          STAMP(inst == KSW, 39);
        }
        if (L < 3) {
          const unsigned ep1 = lds32(base + OFF_EPOCH);
          float s1[2] = {0.f, 0.f}, s2[2] = {0.f, 0.f};
#pragma unroll
          for (int jp = 0; jp < 8; jp++)
#pragma unroll
            for (int q = 0; q < 4; q++) {
              const float x0 = bf_lo(xv[jp][q]), x1 = bf_hi(xv[jp][q]);
              s1[q & 1] += x0 + x1;
              s2[q & 1] = fmaf(x0, x0, fmaf(x1, x1, s2[q & 1]));
            }
#pragma unroll
          for (int r = 0; r < 2; r++) {
            s1[r] += __shfl_xor_sync(0xffffffffu, s1[r], 1);
            s2[r] += __shfl_xor_sync(0xffffffffu, s2[r], 1);
            s1[r] += __shfl_xor_sync(0xffffffffu, s1[r], 2);
            s2[r] += __shfl_xor_sync(0xffffffffu, s2[r], 2);
            if (c == 0) st_rec(&g_stats[L + 1][ct][grow + wwarp * 16 + g + 8 * r], s1[r], s2[r], 0.f, ep1);
          }
        }
        GTL(8 + L * 8);
      }
      continue;
      }
      named_bar_arrive(5, 256);
      if (inst != CSI) continue;
      mbar_wait(bars + 8u * B_AFREE, CSI ^ 1);
      }
      if (asst) {
        colsum_part(&P.wqkv[inst >= 0], inst >= 0, qr, hp);
      } else {
      PHASE_IDS
      {
        const unsigned ep1 = (*(volatile unsigned*)(g_flags + F_DONE)) / NCTA + 1u;
        const int row = b * 16 + (tid >> 3);
        const uint4* src = reinterpret_cast<const uint4*>(P.in_x + (size_t)row * DM) + (tid & 7);
        float s1 = 0.f, s2 = 0.f;
#pragma unroll 1
        for (int k = 0; k < 4; k++) {
          mbar_pace(bars + 8u * (B_EMPTY + PXB * k / 2), 0);
          uint4 v[4];
#pragma unroll
          for (int j = 0; j < 4; j++) v[j] = __ldg(src + (k * 4 + j) * 8);
#pragma unroll
          for (int j = 0; j < 4; j++) {
            const uint32_t w[4] = {v[j].x, v[j].y, v[j].z, v[j].w};
#pragma unroll
            for (int e = 0; e < 4; e++) {
              const float x0 = bf_lo(w[e]), x1 = bf_hi(w[e]);
              s1 += x0 + x1;
              s2 = fmaf(x0, x0, fmaf(x1, x1, s2));
            }
          }
        }
#pragma unroll
        for (int o = 1; o < 8; o <<= 1) {
          s1 += __shfl_xor_sync(0xffffffffu, s1, o);
          s2 += __shfl_xor_sync(0xffffffffu, s2, o);
        }
        if ((tid & 7) == 0) st_rec(&g_stats[0][0][row], s1, s2, 0.f, ep1);
        if (tid == 0) sts32(base + OFF_EPOCH, ep1);
        STAMP(KSQ == 0, 51);
        float4 v[6];
#pragma unroll 1
        for (uint32_t it = 0; it < (1u << 17); ++it) {
          bool ok = true;
#pragma unroll
          for (int t = 0; t < 6; t++) {
            v[t] = ld_rec(t < 2 ? &g_stats[0][0][(t * 8 + qr) * 128 + tid] : &g_cs[0][hp][(tid & 1) * 4 + t - 2][tid >> 1]);
            ok &= __float_as_uint(v[t].w) == ep1;
          }
          STAMP(KSQ == 0 && it == 0, 18);
          if (ok) break;
          __nanosleep(100);
        }
        STAMP(KSQ == 0, 17);
        __syncwarp();
        STAMP(KSQ == 0, 19);
#pragma unroll
        for (int cc = 0; cc < 2; cc++) sts32(base + OFF_RS + (cc * 128 + tid) * 4, ln_params(v[cc].x, v[cc].y));
        const float cs[3] = {(v[2].x + v[3].x) + (v[4].x + v[5].x), (v[2].y + v[3].y) + (v[4].y + v[5].y),
                             (v[2].z + v[3].z) + (v[4].z + v[5].z)};
#pragma unroll
        for (int blk = 0; blk < 3; blk++) {
          const float t = cs[blk] + __shfl_xor_sync(0xffffffffu, cs[blk], 1);
          cs_put(blk, tid & 1, tid >> 1, (tid & 1) ? 0.f : t);
        }
        fence_proxy_async_smem();
        named_bar_sync(2, 128);
        if (tid < 2) mbar_arrive(bars + 8u * (B_PREP + tid));
        STAMP(KSQ == 0, 48);
      }
      }
    }
    if (threadIdx.x == 128) atomicAdd(g_flags + F_DONE, 1u);
    if (!asst) asm volatile("barrier.cluster.arrive.relaxed.aligned;\nbarrier.cluster.wait.aligned;" ::: "memory");
    if (P.zero == 0) return;
  } else {
    setmaxnreg_dec<32>();
    if (warp != 12) {
      ROLE_GET
    }
    if (warp != 15) {
    if (warp == 14) {
      ROLE_IDS
      const unsigned ep1 = (*(volatile unsigned*)(g_flags + F_DONE)) / NCTA + 1u;
      uint32_t hbp = 0;
#pragma unroll 1
      for (int inst = 0; inst < 8; inst++) {
        const int L = inst >> 1, ch = inst & 1, gb = ch * 8 + qr;
        if ((L & 1) == 0) {
          const unsigned* fp = g_flags + F_KV + (max(gb - 1 - ((lane >> 1) & 1), 0) * 16 + hp) * KSTR + (lane & 1);
          uint32_t seen = gb == 0 ? 15u : (gb == 1 ? 12u : 0u);
          named_bar_sync(3, 160);
          STA(34);
          if (elect_one()) {
#pragma unroll 1
            for (int o = 0, pc = (PCM >> inst) & 1 ? PCS : 16384; o < 16384; o += pc) {
              bulk_store(g_kvA[L >> 1][gb][hp][1] + o, slots + 16384 + o, pc);
              if ((PCM >> inst) & 1) spin(PCN);
            }
            bulk_commit();
            bulk_wait0();
            STA(35);
            announce(g_flags + F_KV + (gb * 16 + hp) * KSTR);
            STA(41);
          }
          __syncwarp();
#pragma unroll 1
          for (int i = 0; i < 4; i++) {
            wait_lanes(fp, 2u * ep1 - 1u + (L >> 1), 1u << i, seen);
            STA(36 + i);
            if (i > 0) mbar_wait_lazy<RELNS>(bars + 8u * (B_REL + i - 1), ch);
            if (i == 2) mbar_wait(bars + 8u * B_KVS, ch);
            if (elect_one()) {
              mbar_expect_tx(bars + 8u * (B_HALO + i), 16384);
              bulk_load(slots + (i == 3 ? 2 : 2 - i) * 16384, gb > (i >> 1) ? g_kvA[L >> 1][gb - 1 - (i >> 1)][hp][(i & 1) ^ 1] : g_zero,
                        16384, bars + 8u * (B_HALO + i));
            }
          }
        } else {
          const uint8_t* src = gb > 0 ? g_kvB[L >> 1][gb - 1][hp] : g_zero;
          const uint32_t o = slots + lane * 32 + (lane & 28);
          named_bar_sync(3, 192);
          STA(34);
          if (elect_one()) spin(HBD);
          __syncwarp();
#pragma unroll 1
          for (uint32_t it = 0; it < (1u << 16); ++it) {
            if (elect_one()) {
              mbar_expect_tx(bars + 8u * B_HB, 4096);
              bulk_load(KB_ROW0 - 2048, src, 2048, bars + 8u * B_HB);
              bulk_load(VB_ROW0 - 2048, src + 2048, 2048, bars + 8u * B_HB);
            }
            mbar_wait(bars + 8u * B_HB, hbp);
            hbp ^= 1u;
            const uint32_t m = max(max(lds32(o), lds32(o + 1024)), max(lds32(o + 24576), lds32(o + 24576 + 1024)));
            STA(36 + min(it, 3u));
            if (__reduce_max_sync(0xffffffffu, m) != 0xffffffffu) break;
            fence_proxy_async_smem();
            __syncwarp();
          }
          warp_arrive(bars + 8u * B_HALO);
        }
        const bool xann = ((HAND >> inst) & 1) && q_split(inst + 1) != 8;
        named_bar_sync(9, 288);
        if (xann) mbar_wait(bars + 8u * B_RESE, ch ^ 1);
        if (elect_one()) {
          tma_store_3d(&P.o, ((L & 1) ? slots + 3 * 16384 : OA_TILE) + 8192, 0, gb * 128 + 64, hp);
          bulk_commit();
          bulk_wait0();
          mbar_arrive(bars + 8u * B_AFREE);
        }
        __syncwarp();
        if ((OH >> inst) & 1) {
          mbar_wait(bars + 8u * B_AFREE, ch ^ 1);
          if (elect_one()) announce(g_flags + F_O + gb * OSTR + hp);
          __syncwarp();
        }
        if (w_pre(inst)) {
          mbar_wait(bars + 8u * B_KVS, ch);
          mbar_wait(bars + 8u * B_AFREE, (inst & 1) ^ 1);
          if (inst == CSI) mbar_wait(bars + 8u * B_CSD, 0);
#pragma unroll 1
          for (int j = 0; j < 4; j++) {
            constexpr uint32_t early = w_early();
            if (elect_one()) {
              mbar_expect_tx(bars + 8u * (B_PRE + j), 2 * UNIT);
              tma_load_3d(slots + j * 2 * UNIT, &P.wo[L & 1], bars + 8u * (B_PRE + j), ct * 128, ((early >> (4 * j)) & 15) * 64, 0);
            }
            if (j < 3) __nanosleep(PRENS);
          }
        }
        if (xann) {
          mbar_wait(bars + 8u * B_RESE, ch);
          if (elect_one()) announce(g_flags + F_X + (ch * 8 + (rt >> 1)) * XSTR + ct);
          __syncwarp();
        }
      }
    } else if (warp == 13) {
      ROLE_IDS
      uint32_t n = 16 + rank, dl = 0;
      uint32_t back = 0x44444444u;
      mbar_wait(bars + 8u * B_GO, 0);
      const unsigned ep1 = __shfl_sync(0xffffffffu, (*(volatile unsigned*)(g_flags + F_DONE)) / NCTA + 1u, 0);
#pragma unroll 1
      for (int sg = 4; sg < 34; sg++) {
        const int part = sg & 3, si = (sg >> 2) - (part & 1), L = si >> 1, ch = si & 1;
        const int k0 = part == 2 ? 2 * q_split(si) : 0, k1 = part == 0 ? 2 * q_split(si) : 16;
        if (part == 3 || k0 == k1) continue;
        const bool wj = part == 1;
        uint32_t seen = 0u;
        if (!wj && (L == 0 || __any_sync(0xffffffffu, mbar_test(bars + 8u * (B_XRDY + ch), (L & 1) ^ 1)))) {
          seen = 0xFFFFu;
          fence_proxy_async_all();
        }
        const CUtensorMap* map = wj ? &P.o : &P.xq[L == 0 ? 0 : 1];
        const unsigned* fl = g_flags + (wj ? F_O + (ch * 8 + (rt >> 1)) * OSTR : F_X + (ch * 8 + qr) * XSTR);
        const unsigned target = wj ? 4u * ep1 - 3u + L : 6u * ep1 - 6u + 2u * L;
        const int row = ch * 1024 + (wj ? rt * 64 : qr * 128);
        const bool pre = w_pre(si);
        uint64_t units = rank ? 0x0f050f050f050f05ull : 0x0a000a000a000a00ull;
        if (wj) {
          constexpr uint32_t b00 = (uint32_t)w_tab(2, 0, 0, 2, 8, 4), b01 = (uint32_t)w_tab(2, 0, 1, 2, 8, 4), b10 = (uint32_t)w_tab(2, 1, 0, 2, 8, 4),
                             b11 = (uint32_t)w_tab(2, 1, 1, 2, 8, 4), b20 = (uint32_t)w_tab(2, 2, 0, 2, 8, 4), b21 = (uint32_t)w_tab(2, 2, 1, 2, 8, 4);
          constexpr uint64_t u00 = w_tab(0, 0, 0, 2, 8, 8), u01 = w_tab(0, 0, 1, 2, 8, 8), u10 = w_tab(0, 1, 0, 2, 8, 8), u11 = w_tab(0, 1, 1, 2, 8, 8);
          back = pre ? (rank ? b11 : b10) : (si == 7 ? (rank ? b21 : b20) : (rank ? b01 : b00));
          units = pre ? (rank ? u11 : u10) : (rank ? u01 : u00);
        }
#pragma unroll 1
        for (int kt = k0 + rank; kt < k1; kt += 2, n += 2, back = (back >> 4) | 0x40000000u, units >>= 8) {
          wait_mask<false>(fl, 16, target, 1u << (wj ? kt : kt >> 1), seen, lane);
          const uint32_t nw = n - (back & 15u), pos = ((uint32_t)units & 31u) * UNIT + dl;
          mbar_wait(bars + 8u * (B_EMPTY + (nw & 7u)), (nw >> 3) & 1u);
          if (elect_one())
            tma_load_3d_mc(base + (pos >= 20 * UNIT ? pos - 20 * UNIT : pos), map, bars + 8u * (B_FULL + (n & 7u)), 0, row, kt);
        }
        if (wj ? !pre || PRE_FLIP : ((k1 - k0) & 2)) dl ^= 10u * UNIT;
        constexpr uint32_t q00 = q_backs(true, 0, false), q01 = q_backs(true, 1, false), q10 = q_backs(true, 0, true), q11 = q_backs(true, 1, true);
        if (wj) back = pre ? (rank ? q11 : q10) : (rank ? q01 : q00);
      }
    } else {
#pragma unroll 1
      for (int att = P.zero; att < 2; att++) {
        ROLE_IDS
#pragma unroll 1
        for (int s = 0; s < 4; s++) {
          if (elect_one()) {
            mbar_expect_tx(bars + 8u * (B_FULL + s), 5 * UNIT);
            tma_load_3d(base + s * 5 * UNIT, &P.xq[0], bars + 8u * (B_FULL + s), 0, qr * 128, s);
            tma_load_3d(base + (s * 5 + 2) * UNIT, &P.wqkv[0], bars + 8u * (B_FULL + s), hp * 64, s * 64, 0);
          }
        }
        if (att) break;
        asm volatile("barrier.cluster.wait.aligned;" ::: "memory");
        mbar_wait(bars + 8u * B_ROLE, 0);
        const int r = __shfl_sync(0xffffffffu, (int)lds32(base + OFF_ROLE), 0);
        if (r == role) break;
        role = r;
#pragma unroll 1
        for (int s = 0; s < 4; s++) {
          mbar_wait(bars + 8u * (B_FULL + s), 0);
          __syncwarp();
          if (elect_one()) {
            asm volatile("mbarrier.inval.shared::cta.b64 [%0];" ::"r"(sw(bars + 8u * (B_FULL + s))) : "memory");
            mbar_init(bars + 8u * (B_FULL + s), 1);
          }
        }
        fence_barrier_init();
        fence_proxy_async_smem();
        __syncwarp();
      }
      named_bar_arrive(0, 512);
      ROLE_IDS
#pragma unroll 1
      for (int s = 4; s < 16; s++) {
        const uint32_t fb = bars + 8u * (B_FULL + (s & 7)), sa = base + (s & 3) * 5 * UNIT;
        mbar_wait(bars + 8u * (B_EMPTY + ((s - 4) & 7)), ((s - 4) >> 3) & 1);
        if (elect_one()) {
          mbar_expect_tx(fb, 5 * UNIT);
          if ((s & 1) == rank) tma_load_3d_mc(sa, &P.xq[0], fb, 0, qr * 128, s);
          tma_load_3d(sa + 2 * UNIT, &P.wqkv[0], fb, hp * 64, s * 64, 0);
        }
      }
      if (elect_one()) mbar_arrive(bars + 8u * B_GO);
      const uint32_t wbase = sw(base), wbars = sw(bars);
      uint2 e = P.ptab[0];
#pragma unroll 1
      for (int i = 1; i <= NPT; i++) {
        const uint32_t wb = (e.x & 0x1f8u) | wbars, par = e.x >> 31, fl = e.x;
        uint32_t dst = (e.x & 0x3e000u) | wbase, fb = (e.y & 0x1f8u) | wbars, bytes = e.y & 0xe000u, nold = e.y & 1u;
        int c0 = (e.x & (1u << 29)) ? hp * 64 : ct * 128, c1 = ((e.x >> 18) & 0x7ffu) + ((e.x & (1u << 30)) ? rt * 64 : 0);
        const char* map = reinterpret_cast<const char*>(&P) + (e.y >> 21);
        asm volatile("" : "+r"(dst), "+r"(fb), "+r"(bytes), "+r"(nold), "+r"(c0), "+r"(c1), "+l"(map));
        e = P.ptab[i];
        if (fl & 2u) mbar_wait(bars + 8u * B_RESE, (fl >> 2) & 1u);
        if (!(fl & 1u)) mbar_wait_raw(wb, par);
        asm volatile(
            "{\n.reg .pred p, q;\nelect.sync _|p, 0xffffffff;\nsetp.eq.and.u32 q, %6, 0, p;\n"
            "@p mbarrier.arrive.expect_tx.shared::cta.b64 _, [%2], %5;\n"
            "@q cp.async.bulk.tensor.3d.shared::cluster.global.mbarrier::complete_tx::bytes [%0], [%1, {%3, %4, %7}], [%2];\n}\n" ::"r"(dst),
            "l"(map), "r"(fb), "r"(c0), "r"(c1), "r"(bytes), "r"(nold), "r"(0)
            : "memory");
      }
    }
    return;
    }
  }
  {
    {
      ROLE_IDS
      const unsigned ep1 = (*(volatile unsigned*)(g_flags + F_DONE)) / NCTA + 1u;
#pragma unroll 1
      for (int inst = 0; inst < 8; inst++) {
        const int L = inst >> 1, ch = inst & 1, gb = ch * 8 + qr;
        if (inst == 1 || inst == 2) {
#pragma unroll 1
          for (int i = inst == 1 ? 0 : TRSP; i < (inst == 1 ? TRSP : 20); i++) {
            const char* src = i < 4 ? reinterpret_cast<const char*>(P.wo_p[0]) + i * 524288
                                    : (i < 16 ? reinterpret_cast<const char*>(P.wqkv_p1) + (i - 4) * 524288
                                              : reinterpret_cast<const char*>(P.wo_p[1]) + (i - 16) * 524288);
            asm volatile("prefetch.global.L2 [%0];" ::"l"(src + b * 4096 + lane * 128));
            __nanosleep(inst == 1 ? TRICKLE : TRICK2);
          }
        }
        if (inst >= 2) {
        uint32_t seen = 0;
        wait_mask<true>(g_flags + F_X + gb * XSTR, 8, 6u * ep1 - 6u + 2u * L, 0xFFu, seen, lane);
        if (lane == 0) mbar_arrive(bars + 8u * (B_XRDY + ch));
#pragma unroll 1
        for (int h = 0; h < 4; h++) {
          const float4* sp = &g_stats[L][0][gb * 128 + h * 32 + lane];
          const float4 s0 = sum_recs<4>(sp, S_LEN, ep1), s1 = sum_recs<4>(sp + 4 * S_LEN, S_LEN, ep1);
          sts32(base + OFF_RS + (ch * 128 + h * 32 + lane) * 4, ln_params(s0.x + s1.x, s0.y + s1.y));
        }
        if (inst == 2) {
          mbar_wait(bars + 8u * B_CSD, 0);
#pragma unroll 1
          for (int hf = 0; hf < 2; hf++) {
            const float4* cp = &g_cs[1][hp][0][hf * 32 + lane];
            const float4 s0 = sum_recs<4>(cp, 64, ep1), s1 = sum_recs<4>(cp + 4 * 64, 64, ep1);
            cs_put(0, 1, hf * 32 + lane, s0.x + s1.x);
            cs_put(1, 1, hf * 32 + lane, s0.y + s1.y);
            cs_put(2, 1, hf * 32 + lane, s0.z + s1.z);
          }
          fence_proxy_async_smem();
        }
        __syncwarp();
        if (lane == 0) mbar_arrive(bars + 8u * (B_PREP + ch));
        }
        named_bar_sync((L & 1) ? 3 : 7, (L & 1) ? 192 : 160);
        if (elect_one()) {
          if (L & 1) {
            bulk_store(g_kvB[L >> 1][gb][hp], KB_ROW0 + 112 * 128, 2048);
            bulk_store(g_kvB[L >> 1][gb][hp] + 2048, VB_ROW0 + 112 * 128, 2048);
          } else {
            spin(PDL);
#pragma unroll 1
            for (int o = 0, pc = (PCM >> inst) & 1 ? PCS : 16384; o < 16384; o += pc) {
              bulk_store(g_kvA[L >> 1][gb][hp][0] + o, slots + o, pc);
              if ((PCM >> inst) & 1) spin(PCN);
            }
          }
          bulk_commit();
          bulk_wait0();
          mbar_arrive(bars + 8u * B_KVS);
          STA(32);
          if ((L & 1) == 0) {
            announce(g_flags + F_KV + (gb * 16 + hp) * KSTR + 1);
          }
          STA(33);
        }
        __syncwarp();
        if ((((2 * HAND) >> inst) & 1) && q_split(inst) == 8) {
          mbar_wait(bars + 8u * B_RESE, ch ^ 1);
          if (elect_one()) announce(g_flags + F_X + ((ch ^ 1) * 8 + (rt >> 1)) * XSTR + ct);
          __syncwarp();
        }
      }
    }
  }
}

typedef CUresult (*PFN_tmEncode)(CUtensorMap*, CUtensorMapDataType, cuuint32_t, void*, const cuuint64_t*,
                                 const cuuint64_t*, const cuuint32_t*, const cuuint32_t*, CUtensorMapInterleave,
                                 CUtensorMapSwizzle, CUtensorMapL2promotion, CUtensorMapFloatOOBfill);

PFN_tmEncode get_encode_fn() {
  static PFN_tmEncode fn = nullptr;
  if (!fn) {
    cudaDriverEntryPointQueryResult qr;
    void* p = nullptr;
    cudaGetDriverEntryPoint("cuTensorMapEncodeTiled", &p, cudaEnableDefault, &qr);
    fn = (PFN_tmEncode)p;
  }
  return fn;
}

CUtensorMap make_map(const void* ptr, int rows, int cols, int inner, int blocks, int bs, int box_rows, int box_blk) {
  CUtensorMap m;
  cuuint64_t gdim[3] = {(cuuint64_t)inner, (cuuint64_t)rows, (cuuint64_t)blocks};
  cuuint64_t gstr[2] = {(cuuint64_t)cols * 2, (cuuint64_t)bs * 2};
  cuuint32_t box[3] = {64, (cuuint32_t)box_rows, (cuuint32_t)box_blk};
  cuuint32_t estr[3] = {1, 1, 1};
  get_encode_fn()(&m, CU_TENSOR_MAP_DATA_TYPE_BFLOAT16, 3, const_cast<void*>(ptr), gdim, gstr, box, estr,
                  CU_TENSOR_MAP_INTERLEAVE_NONE, CU_TENSOR_MAP_SWIZZLE_128B, CU_TENSOR_MAP_L2_PROMOTION_L2_128B,
                  CU_TENSOR_MAP_FLOAT_OOB_FILL_NONE);
  return m;
}

void make_tables(Params& P) {
  const WPlan pl[3] = {w_plan(0), w_plan(1), w_plan(2)};
  for (int m = 0; m < 4; m++)
    for (int kt = 0; kt < 17; kt++) {
      const WPlan& p = pl[m >> 1];
      const uint32_t dl = (m & 1) * 10u * UNIT;
      P.wtab[m][kt] = make_uint2(kt == 16 ? SBASE + unit_off(p.v[1][kt], dl) : ((SBASE + unit_off(p.v[0][kt], dl)) >> 4) + 0x10000u,
                                 ((SBASE + unit_off(p.v[1][kt], dl)) >> 4) + ((UNIT >> 4) << 16));
    }
  int np = 0;
  auto put = [&](int nw, int rp, uint32_t off, int c1, int kind, int fb, int units, const CUtensorMap* map) {
    P.ptab[np++] = make_uint2((nw < 0 ? 1u : 8u * ((LOCE ? B_LOC : B_EMPTY) + (nw & 7)) | (uint32_t)((nw >> 3) & 1) << 31) | (rp < 0 ? 0u : 2u | 4u * rp) |
                                  off | (uint32_t)c1 << 18 | (uint32_t)kind << 29,
                              8u * fb | (map ? 0u : 1u) | units * UNIT |
                                  (map ? (uint32_t)(reinterpret_cast<const char*>(map) - reinterpret_cast<const char*>(&P)) << 21 : 0u));
  };
  int n = 16, aw = 0;
  uint32_t dl = 0;
  uint32_t back = 0x44444444u;
  for (int sg = 4; sg < 34; sg++) {
    const int part = sg & 3, si = (sg >> 2) - (part & 1), L = si >> 1, ch = si & 1;
    const int k0 = part == 2 ? 2 * q_split(si) : 0, k1 = part == 0 ? 2 * q_split(si) : 16;
    if (part == 3) continue;
    if (part != 1) {
      for (int k2 = k0; k2 < k1; k2 += 2, aw--, dl ^= 10u * UNIT)
        for (int ks = 0; ks < 2; ks++, n++, back = (back >> 4) | 0x40000000u)
          put(n - (int)(back & 15u), ks == 1 && aw == 1 ? (part == 2) ^ ch : -1, (ks * 5 + 2) * UNIT + dl, (k2 + ks) * 64, 1,
              B_FULL + (n & 7), 5, &P.wqkv[L & 1]);
    } else {
      const bool pre = w_pre(si);
      const WPlan& p = pl[pre ? 1 : (aw == 2 ? 2 : 0)];
      for (int kt = 0; kt < 17; kt++) {
        const bool early = kt < 16 && p.v[5][kt];
        put(p.v[4][kt] ? n + kt - p.v[3][kt] : -1, !pre && kt == 6 && aw == 2 ? ch ^ 1 : -1, unit_off(p.v[1][kt], dl),
            kt == 16 ? ch * 1024 : kt * 64, kt == 16 ? 2 : 0, kt == 16 ? B_RESF : B_FULL + ((n + kt) & 7),
            kt == 16 ? 2 : (early ? 1 : 3), kt == 16 ? &P.xr[L == 0 ? 0 : 1] : (early ? nullptr : &P.wo[L & 1]));
      }
      n += 16;
      if (!pre || PRE_FLIP) dl ^= 10u * UNIT;
      back = q_backs(false, 0, pre);
      aw = 2;
    }
  }
  P.ptab[np] = make_uint2(0, 0);
}

}

extern "C" void kernel_launch(void* const* d_in, const int* in_sizes, int n_in, void* d_out, int out_size) {
  (void)in_sizes; (void)n_in; (void)out_size;
  void *p_o, *p_x;
  cudaGetSymbolAddress(&p_o, g_o);
  cudaGetSymbolAddress(&p_x, g_x);
  static bool attr_done = false;
  if (!attr_done) {
    cudaFuncSetAttribute(fused_kernel, cudaFuncAttributeMaxDynamicSharedMemorySize, SMEM_BYTES);
    attr_done = true;
  }
  Params P;
  P.in_x = (const __nv_bfloat16*)d_in[0];
  P.wo_p[0] = (const __nv_bfloat16*)d_in[2];
  P.wqkv_p1 = (const __nv_bfloat16*)d_in[4];
  P.wo_p[1] = (const __nv_bfloat16*)d_in[5];
  P.zero = 0;
  P.xq[0] = make_map(P.in_x, S_LEN, DM, 64, 16, 64, 128, 1);
  P.xq[1] = make_map(p_x, S_LEN, DM, 64, 16, 64, 128, 1);
  P.xr[0] = make_map(P.in_x, S_LEN, DM, DM - 64, 2, 64, 64, 2);
  P.xr[1] = make_map(p_x, S_LEN, DM, DM - 64, 2, 64, 64, 2);
  P.xw[0] = make_map(p_x, S_LEN, DM, 64, 16, 64, 16, 1);
  P.xw[1] = make_map(d_out, S_LEN, DM, 64, 16, 64, 16, 1);
  P.o = make_map(p_o, S_LEN, DM, 64, 16, 64, 64, 1);
  for (int t = 0; t < 2; t++) {
    P.wqkv[t] = make_map(d_in[3 * t + 1], DM, NQKV, 1024, 3, 1024, 64, 3);
    P.wo[t] = make_map(P.wo_p[t], DM, DM, DM - 64, 2, 64, 64, 2);
  }
  make_tables(P);
  fused_kernel<<<NCTA, 512, SMEM_BYTES>>>(P);
}
```
